```python
import torch

def _softmax(x, axis=-1):
    return torch.softmax(x, dim=axis)
def _gelu(x):
    return torch.nn.functional.gelu(x, approximate="tanh")
def _silu(x):
    return torch.nn.functional.silu(x)
def _sigmoid(x):
    return torch.sigmoid(x)
def _layernorm(x, axis=-1, eps=1e-5):
    m = x.mean(dim=axis, keepdim=True)
    v = x.var(dim=axis, keepdim=True, unbiased=False)
    return (x - m) / torch.sqrt(v + eps)
def _scatter_add(tgt, idx, src, axis=0):
    return tgt.clone().index_add_(axis, idx, src)
def _segment_sum(src, seg, n):
    out = torch.zeros((n,) + src.shape[1:], dtype=src.dtype)
    return out.index_add_(0, seg, src)
def _pad(x, pw):
    flat = tuple(v for pair in reversed(pw) for v in pair)
    return torch.nn.functional.pad(x, flat)

kernel_name = 'recurrent_scan__ssm_conv_s4__dense_activation_silu__prompt'

def setup_inputs():

    _w = (lambda a: (lambda t: t.to(torch.bfloat16) if t.is_floating_point() else t)(torch.as_tensor(a)))
    def _A_setup():
        B, L, D, N = 1, 2048, 640, 192
        A_re = -(lambda _x: torch.exp(torch.as_tensor(_x)))((lambda *s: torch.randn(*s, dtype=torch.bfloat16) * 3.2)(D, N))
        A_im = torch.pi * (lambda *s: torch.randn(*s, dtype=torch.bfloat16) * 0.2)(D, N)
        B_re = (lambda *s: torch.randn(*s, dtype=torch.bfloat16) * 0.2)(D, N)
        B_im = (lambda *s: torch.randn(*s, dtype=torch.bfloat16) * 0.2)(D, N)
        C_re = (lambda *s: torch.randn(*s, dtype=torch.bfloat16) * 0.2)(D, N)
        C_im = (lambda *s: torch.randn(*s, dtype=torch.bfloat16) * 0.2)(D, N)
        log_dt = (lambda *s: torch.randn(*s, dtype=torch.bfloat16) * 0.2)(D) * 0.5 - 4.0
        Dskip = (lambda *s: torch.randn(*s, dtype=torch.bfloat16) * 0.2)(D)
        return {
            "u": _w((lambda *s: torch.randn(*s, dtype=torch.bfloat16) * 0.05)(B, L, D)),
            "A_re": _w(A_re),
            "A_im": _w(A_im),
            "B_re": _w(B_re),
            "B_im": _w(B_im),
            "C_re": _w(C_re),
            "C_im": _w(C_im),
            "log_dt": _w(log_dt),
            "Dskip": _w(Dskip),
        }
    _A_in = _A_setup()

    def _B_setup():
        B, S, D, F = 1, 2048, 640, 1536
        return {
            "x": _w((lambda *s: torch.randn(*s, dtype=torch.bfloat16) * 0.05)(B, S, D)),
            "w1": _w((lambda *s: torch.randn(*s, dtype=torch.bfloat16) * 0.8)(D, F) * (D ** -0.5)),
            "w2": _w((lambda *s: torch.randn(*s, dtype=torch.bfloat16) * 0.1)(F, D) * (F ** -0.5)),
        }
    _B_in = _B_setup()

    return {
        "A_u": _A_in["u"],
        "A_A_re": _A_in["A_re"],
        "A_A_im": _A_in["A_im"],
        "A_B_re": _A_in["B_re"],
        "A_B_im": _A_in["B_im"],
        "A_C_re": _A_in["C_re"],
        "A_C_im": _A_in["C_im"],
        "A_log_dt": _A_in["log_dt"],
        "A_Dskip": _A_in["Dskip"],
        "B_x": _B_in["x"],
        "B_w1": _B_in["w1"],
        "B_w2": _B_in["w2"],
    }

def reference(A_u, A_A_re, A_A_im, A_B_re, A_B_im, A_C_re, A_C_im, A_log_dt, A_Dskip, B_x, B_w1, B_w2):
    def _A_ref(u, A_re, A_im, B_re, B_im, C_re, C_im, log_dt, Dskip):
        Bsz, L, D = u.shape
        dt = torch.exp(log_dt)[:, None]
        A = A_re + 1j * A_im
        Bc = B_re + 1j * B_im
        Cc = C_re + 1j * C_im
        logdA = dt * A
        dB = dt * Bc
        l = (lambda x, dt: x.to(dt))(torch.arange(L), A_re.dtype)
        P = torch.exp(logdA[:, :, None] * l[None, None, :])
        K = torch.einsum("dn,dnl,dn->dl", Cc, P, dB).real
        L2 = 2 * L
        Kp = _pad(K, ((0, 0), (0, L)))
        up = (lambda x, *d: x.permute(*d))(u, 0, 2, 1)
        up = _pad(up, ((0, 0), (0, 0), (0, L)))
        Kf = (lambda x, axes=(-2,-1): torch.fft.rfft2(x.float(), dim=axes))(Kp[:, None, :], axes=(-2, -1))
        Uf = (lambda x, axes=(-2,-1): torch.fft.rfft2(x.float(), dim=axes))(up[:, :, None, :], axes=(-2, -1))
        Yf = Uf * Kf[None, :, :, :]
        y = (lambda x, s, axes=(-2,-1): torch.fft.irfft2(x, s=s, dim=axes).to(torch.bfloat16))(Yf, (1, L2), axes=(-2, -1))[:, :, 0, :L]
        y = (lambda x, *d: x.permute(*d))(y, 0, 2, 1) + u * Dskip[None, None, :]
        return y

    def _B_ref(x, w1, w2):
        h = torch.einsum("bsd,df->bsf", x, w1)
        h = _silu(h)
        out = torch.einsum("bsf,fd->bsd", h, w2)
        return out

    x = A_u
    xn = _layernorm(x, axis=-1)
    s = _A_ref(xn, A_A_re, A_A_im, A_B_re, A_B_im, A_C_re, A_C_im, A_log_dt, A_Dskip)
    g = _silu(_B_ref(xn, B_w1, B_w2))
    return x + s * g
```

```cpp
#include <cuda_runtime.h>
#include <cuda_bf16.h>
#include <cuda_fp16.h>
#include <cuda.h>
#include <stdint.h>

namespace {

constexpr int SEQ = 2048, DM = 640, NMODE = 192, FF = 1536;

constexpr int SLOT1 = 40960;
constexpr int SLOT2 = 26624;
constexpr int NS2 = 6;
constexpr int OFF_Z = 81920, ZSZ = 21504;
constexpr int ZA1 = 0, ZB1 = 4608, ZA2 = 9216, ZB2 = 12288, ZA3 = 15360, ZB3 = 17408, ZS = 19456;
constexpr int OFF_U = 189440;
constexpr int OFF_P = 209920;
constexpr int OFF_KS = 163840;
constexpr int OFF_LNT = 204800;
constexpr int OFF_MISC = 225280;
constexpr int OFF_ZERO = OFF_MISC + 128;
constexpr int OFF_STAT = OFF_MISC + 384;
constexpr int OFF_CS = OFF_MISC + 1408;
constexpr int OFF_CHC = OFF_MISC + 2176;
constexpr int OFF_K0 = OFF_MISC + 2304;
constexpr int OFF_EP = OFF_MISC + 2432;
constexpr int OFF_BAR = OFF_MISC + 2560;
constexpr int SMEM_BYTES = OFF_MISC + 3072;
constexpr int P0 = 8, PA1 = 280, PB1 = 360, PA2 = 448, PB2 = 544, PA3 = 632, PB3 = 704;
enum { B_FULL1 = 0, B_EMPTY1 = 4, B_DRAIN = 8, B_UFULL = 12, B_EPI = 13, B_ZRDY = 14, B_SFULL = 15,
       B_MMA = 16, B_FREE = 21, B_FULL2 = 26, B_EMPTY2 = 32, B_NUM = 38 };
enum { C_LN = 0, C_W2 = 1, C_H0 = 2, C_H1 = 18, C_S = 34, C_NUM = 42 };

__device__ uint4 g_uT[DM * 256];
__device__ uint4 g_h[16 * 24 * 1024];
__device__ uint4 g_w2p[8 * 24 * 640];
__device__ uint4 g_sT[8 * 16 * 1280];
__device__ float2 g_stats[SEQ];
__device__ float g_csp[16 * FF];
__device__ unsigned g_cnt[C_NUM * 32];
__device__ unsigned g_epoch[160];

struct Params {
  const __nv_bfloat16 *x, *are, *aim, *bre, *bim, *cre, *cim, *logdt, *dskip, *w1, *w2;
  __nv_bfloat16* out;
  int use_smid;
};

__device__ __forceinline__ void mbar_init(uint32_t a, int c) { asm volatile("mbarrier.init.shared::cta.b64 [%0], %1;" ::"r"(a), "r"(c)); }
__device__ __forceinline__ void mbar_expect(uint32_t a, int b) { asm volatile("mbarrier.arrive.expect_tx.shared::cta.b64 _, [%0], %1;" ::"r"(a), "r"(b) : "memory"); }
__device__ __forceinline__ void mbar_arrive(uint32_t a) { asm volatile("mbarrier.arrive.shared::cta.b64 _, [%0];" ::"r"(a) : "memory"); }
__device__ __forceinline__ void mbar_wait(uint32_t a, int ph) {
  asm volatile(
      "{\n.reg .pred p;\n.reg .u32 n;\nmov.u32 n, 0;\n"
      "LW:\nmbarrier.try_wait.parity.shared::cta.b64 p, [%0], %1;\n@p bra LD;\n"
      "add.u32 n, n, 1;\nsetp.lt.u32 p, n, 4000000;\n@p bra LW;\ntrap;\nLD:\n}\n" ::"r"(a), "r"(ph) : "memory");
}
__device__ __forceinline__ void poll_cnt(int idx, unsigned target) {
  const unsigned* p = g_cnt + idx * 32;
  unsigned v; int n = 0;
  do {
    asm volatile("ld.acquire.gpu.global.u32 %0, [%1];" : "=r"(v) : "l"(p) : "memory");
    if (++n > 4000000) __trap();
  } while ((int)(v - target) < 0);
}
__device__ __forceinline__ void publish(int idx) {
  asm volatile("fence.proxy.async;\nfence.acq_rel.gpu;\nred.relaxed.gpu.global.add.u32 [%0], 1;" ::"l"(g_cnt + idx * 32) : "memory");
}
__device__ __forceinline__ void fence_async() { asm volatile("fence.proxy.async;" ::: "memory"); }
__device__ __forceinline__ void fence_async_smem() { asm volatile("fence.proxy.async.shared::cta;" ::: "memory"); }
__device__ __forceinline__ bool elect1() { uint32_t p; asm volatile("{\n.reg .pred P;\nelect.sync _|P, 0xffffffff;\nselp.u32 %0,1,0,P;\n}\n" : "=r"(p)); return p; }
__device__ __forceinline__ void bar_sync(int id, int n) { asm volatile("bar.sync %0, %1;" ::"r"(id), "r"(n) : "memory"); }
__device__ __forceinline__ void bar_arrive(int id, int n) { asm volatile("bar.arrive %0, %1;" ::"r"(id), "r"(n) : "memory"); }
__device__ __forceinline__ void bulk_g2s(uint32_t dst, const void* src, int bytes, uint32_t mb) {
  asm volatile("cp.async.bulk.shared::cluster.global.mbarrier::complete_tx::bytes [%0], [%1], %2, [%3];" ::"r"(dst), "l"(src), "r"(bytes), "r"(mb) : "memory");
}
__device__ __forceinline__ void bulk_prefetch(const void* src, int bytes) { asm volatile("cp.async.bulk.prefetch.L2.global [%0], %1;" ::"l"(src), "r"(bytes) : "memory"); }
__device__ __forceinline__ void tma2d(uint32_t dst, const CUtensorMap* m, int c0, int c1, uint32_t mb) {
  asm volatile("cp.async.bulk.tensor.2d.shared::cluster.global.mbarrier::complete_tx::bytes [%0], [%1, {%3, %4}], [%2];" ::"r"(dst), "l"(m), "r"(mb), "r"(c0), "r"(c1) : "memory");
}
__device__ __forceinline__ uint64_t mkdesc(uint32_t addr, int lbo, int sbo, int sw) {
  return (uint64_t)((addr & 0x3FFFF) >> 4) | ((uint64_t)(lbo >> 4) << 16) | ((uint64_t)(sbo >> 4) << 32) | ((uint64_t)sw << 62);
}
__device__ __forceinline__ void wg_fence() { asm volatile("wgmma.fence.sync.aligned;" ::: "memory"); }
__device__ __forceinline__ void wg_commit() { asm volatile("wgmma.commit_group.sync.aligned;" ::: "memory"); }
template <int N> __device__ __forceinline__ void wg_wait() { asm volatile("wgmma.wait_group.sync.aligned %0;" ::"n"(N) : "memory"); }
__device__ __forceinline__ void wgmma_n192(float (&d)[96], uint64_t da, uint64_t db, int scale_d) {
  asm volatile("{\n.reg .pred p;\nsetp.ne.b32 p, %98, 0;\n"
    "wgmma.mma_async.sync.aligned.m64n192k16.f32.bf16.bf16 "
    "{"
    "%0, %1, %2, %3, %4, %5, %6, %7, %8, %9, %10, %11, %12, %13, %14, %15, "
    "%16, %17, %18, %19, %20, %21, %22, %23, %24, %25, %26, %27, %28, %29, %30, %31, "
    "%32, %33, %34, %35, %36, %37, %38, %39, %40, %41, %42, %43, %44, %45, %46, %47, "
    "%48, %49, %50, %51, %52, %53, %54, %55, %56, %57, %58, %59, %60, %61, %62, %63, "
    "%64, %65, %66, %67, %68, %69, %70, %71, %72, %73, %74, %75, %76, %77, %78, %79, "
    "%80, %81, %82, %83, %84, %85, %86, %87, %88, %89, %90, %91, %92, %93, %94, %95"
    "}, "
    "%96, %97, p, 1, 1, 0, 1;\n}\n"
    : "+f"(d[0]), "+f"(d[1]), "+f"(d[2]), "+f"(d[3]), "+f"(d[4]), "+f"(d[5]), "+f"(d[6]), "+f"(d[7]),
      "+f"(d[8]), "+f"(d[9]), "+f"(d[10]), "+f"(d[11]), "+f"(d[12]), "+f"(d[13]), "+f"(d[14]), "+f"(d[15]),
      "+f"(d[16]), "+f"(d[17]), "+f"(d[18]), "+f"(d[19]), "+f"(d[20]), "+f"(d[21]), "+f"(d[22]), "+f"(d[23]),
      "+f"(d[24]), "+f"(d[25]), "+f"(d[26]), "+f"(d[27]), "+f"(d[28]), "+f"(d[29]), "+f"(d[30]), "+f"(d[31]),
      "+f"(d[32]), "+f"(d[33]), "+f"(d[34]), "+f"(d[35]), "+f"(d[36]), "+f"(d[37]), "+f"(d[38]), "+f"(d[39]),
      "+f"(d[40]), "+f"(d[41]), "+f"(d[42]), "+f"(d[43]), "+f"(d[44]), "+f"(d[45]), "+f"(d[46]), "+f"(d[47]),
      "+f"(d[48]), "+f"(d[49]), "+f"(d[50]), "+f"(d[51]), "+f"(d[52]), "+f"(d[53]), "+f"(d[54]), "+f"(d[55]),
      "+f"(d[56]), "+f"(d[57]), "+f"(d[58]), "+f"(d[59]), "+f"(d[60]), "+f"(d[61]), "+f"(d[62]), "+f"(d[63]),
      "+f"(d[64]), "+f"(d[65]), "+f"(d[66]), "+f"(d[67]), "+f"(d[68]), "+f"(d[69]), "+f"(d[70]), "+f"(d[71]),
      "+f"(d[72]), "+f"(d[73]), "+f"(d[74]), "+f"(d[75]), "+f"(d[76]), "+f"(d[77]), "+f"(d[78]), "+f"(d[79]),
      "+f"(d[80]), "+f"(d[81]), "+f"(d[82]), "+f"(d[83]), "+f"(d[84]), "+f"(d[85]), "+f"(d[86]), "+f"(d[87]),
      "+f"(d[88]), "+f"(d[89]), "+f"(d[90]), "+f"(d[91]), "+f"(d[92]), "+f"(d[93]), "+f"(d[94]), "+f"(d[95])
    : "l"(da), "l"(db), "r"(scale_d));
}

__device__ __forceinline__ void wgmma_n80(float (&d)[40], uint64_t da, uint64_t db, int scale_d) {
  asm volatile("{\n.reg .pred p;\nsetp.ne.b32 p, %42, 0;\n"
    "wgmma.mma_async.sync.aligned.m64n80k16.f32.bf16.bf16 "
    "{"
    "%0, %1, %2, %3, %4, %5, %6, %7, %8, %9, %10, %11, %12, %13, %14, %15, "
    "%16, %17, %18, %19, %20, %21, %22, %23, %24, %25, %26, %27, %28, %29, %30, %31, "
    "%32, %33, %34, %35, %36, %37, %38, %39"
    "}, "
    "%40, %41, p, 1, 1, 0, 1;\n}\n"
    : "+f"(d[0]), "+f"(d[1]), "+f"(d[2]), "+f"(d[3]), "+f"(d[4]), "+f"(d[5]), "+f"(d[6]), "+f"(d[7]),
      "+f"(d[8]), "+f"(d[9]), "+f"(d[10]), "+f"(d[11]), "+f"(d[12]), "+f"(d[13]), "+f"(d[14]), "+f"(d[15]),
      "+f"(d[16]), "+f"(d[17]), "+f"(d[18]), "+f"(d[19]), "+f"(d[20]), "+f"(d[21]), "+f"(d[22]), "+f"(d[23]),
      "+f"(d[24]), "+f"(d[25]), "+f"(d[26]), "+f"(d[27]), "+f"(d[28]), "+f"(d[29]), "+f"(d[30]), "+f"(d[31]),
      "+f"(d[32]), "+f"(d[33]), "+f"(d[34]), "+f"(d[35]), "+f"(d[36]), "+f"(d[37]), "+f"(d[38]), "+f"(d[39])
    : "l"(da), "l"(db), "r"(scale_d));
}

__device__ __forceinline__ void hmma(float* c, uint32_t a0, uint32_t a1, uint32_t a2, uint32_t a3, uint32_t b0, uint32_t b1) {
  asm("mma.sync.aligned.m16n8k16.row.col.f32.f16.f16.f32 {%0,%1,%2,%3}, {%4,%5,%6,%7}, {%8,%9}, {%0,%1,%2,%3};"
      : "+f"(c[0]), "+f"(c[1]), "+f"(c[2]), "+f"(c[3]) : "r"(a0), "r"(a1), "r"(a2), "r"(a3), "r"(b0), "r"(b1));
}
__device__ __forceinline__ void ldsm4(uint32_t* r, uint32_t a) { asm volatile("ldmatrix.sync.aligned.m8n8.x4.shared.b16 {%0,%1,%2,%3}, [%4];" : "=r"(r[0]), "=r"(r[1]), "=r"(r[2]), "=r"(r[3]) : "r"(a) : "memory"); }
__device__ __forceinline__ void ldsm4t(uint32_t* r, uint32_t a) { asm volatile("ldmatrix.sync.aligned.m8n8.x4.trans.shared.b16 {%0,%1,%2,%3}, [%4];" : "=r"(r[0]), "=r"(r[1]), "=r"(r[2]), "=r"(r[3]) : "r"(a) : "memory"); }
__device__ __forceinline__ void stsm4(uint32_t a, uint32_t r0, uint32_t r1, uint32_t r2, uint32_t r3) { asm volatile("stmatrix.sync.aligned.m8n8.x4.shared.b16 [%0], {%1,%2,%3,%4};" ::"r"(a), "r"(r0), "r"(r1), "r"(r2), "r"(r3) : "memory"); }
__device__ __forceinline__ void stsm4t(uint32_t a, uint32_t r0, uint32_t r1, uint32_t r2, uint32_t r3) { asm volatile("stmatrix.sync.aligned.m8n8.x4.trans.shared.b16 [%0], {%1,%2,%3,%4};" ::"r"(a), "r"(r0), "r"(r1), "r"(r2), "r"(r3) : "memory"); }
__device__ __forceinline__ uint32_t lds32(uint32_t a) { uint32_t v; asm volatile("ld.shared.u32 %0, [%1];" : "=r"(v) : "r"(a) : "memory"); return v; }
__device__ __forceinline__ uint2 lds64(uint32_t a) { uint2 v; asm volatile("ld.shared.v2.u32 {%0,%1}, [%2];" : "=r"(v.x), "=r"(v.y) : "r"(a) : "memory"); return v; }
__device__ __forceinline__ uint4 lds128(uint32_t a) { uint4 v; asm volatile("ld.shared.v4.u32 {%0,%1,%2,%3}, [%4];" : "=r"(v.x), "=r"(v.y), "=r"(v.z), "=r"(v.w) : "r"(a) : "memory"); return v; }
__device__ __forceinline__ void sts16(uint32_t a, uint32_t v) { asm volatile("st.shared.u16 [%0], %1;" ::"r"(a), "h"((unsigned short)v) : "memory"); }
__device__ __forceinline__ void sts32(uint32_t a, uint32_t v) { asm volatile("st.shared.u32 [%0], %1;" ::"r"(a), "r"(v) : "memory"); }
__device__ __forceinline__ void sts64(uint32_t a, uint32_t x, uint32_t y) { asm volatile("st.shared.v2.u32 [%0], {%1,%2};" ::"r"(a), "r"(x), "r"(y) : "memory"); }
__device__ __forceinline__ void sts128(uint32_t a, uint32_t x, uint32_t y, uint32_t z, uint32_t w) { asm volatile("st.shared.v4.u32 [%0], {%1,%2,%3,%4};" ::"r"(a), "r"(x), "r"(y), "r"(z), "r"(w) : "memory"); }
__device__ __forceinline__ float bflo(uint32_t v) { return __uint_as_float(v << 16); }
__device__ __forceinline__ float bfhi(uint32_t v) { return __uint_as_float(v & 0xffff0000u); }
__device__ __forceinline__ uint32_t pack_bf(float lo, float hi) { uint32_t r; asm("cvt.rn.bf16x2.f32 %0, %1, %2;" : "=r"(r) : "f"(hi), "f"(lo)); return r; }
__device__ __forceinline__ uint32_t pack_h(float lo, float hi) { uint32_t r; asm("cvt.rn.f16x2.f32 %0, %1, %2;" : "=r"(r) : "f"(hi), "f"(lo)); return r; }
__device__ __forceinline__ float rnd_bf(float v) { return __bfloat162float(__float2bfloat16_rn(v)); }
__device__ __forceinline__ float ex2a(float v) { float r; asm("ex2.approx.ftz.f32 %0, %1;" : "=f"(r) : "f"(v)); return r; }
__device__ __forceinline__ float tanha(float v) { float r; asm("tanh.approx.f32 %0, %1;" : "=f"(r) : "f"(v)); return r; }
__device__ __forceinline__ uint32_t hadd(uint32_t a, uint32_t b) { uint32_t r; asm("add.rn.f16x2 %0, %1, %2;" : "=r"(r) : "r"(a), "r"(b)); return r; }
__device__ __forceinline__ uint32_t badd(uint32_t a, uint32_t b) { uint32_t r; asm("add.rn.bf16x2 %0, %1, %2;" : "=r"(r) : "r"(a), "r"(b)); return r; }
__device__ __forceinline__ uint32_t odd_pair(uint32_t a, uint32_t b) { return __byte_perm(a, b, 0x5432); }
__device__ __forceinline__ int upos(int c) { return c ^ (c >> 5) ^ ((c >> 3) & 1); }

struct cf { float r, i; };
__device__ __forceinline__ cf cmul(cf a, cf b) { cf o; o.r = fmaf(a.r, b.r, -a.i * b.i); o.i = fmaf(a.r, b.i, a.i * b.r); return o; }
__device__ __forceinline__ cf csq(cf a) { cf o; o.r = fmaf(a.r, a.r, -a.i * a.i); o.i = (a.r + a.r) * a.i; return o; }
struct hp { uint32_t r, i; };
__device__ __forceinline__ hp hpack(cf a, cf b) { hp o; o.r = pack_h(a.r, b.r); o.i = pack_h(a.i, b.i); return o; }
__device__ __forceinline__ hp hmulc(hp a, uint32_t c) {
  __half2 ar = *reinterpret_cast<__half2*>(&a.r), ai = *reinterpret_cast<__half2*>(&a.i), cc = *reinterpret_cast<__half2*>(&c);
  __half2 orr = __hfma2(ar, __low2half2(cc), __hneg2(__hmul2(ai, __high2half2(cc))));
  __half2 oi = __hfma2(ar, __high2half2(cc), __hmul2(ai, __low2half2(cc)));
  hp o; o.r = *reinterpret_cast<uint32_t*>(&orr); o.i = *reinterpret_cast<uint32_t*>(&oi); return o;
}
__device__ __forceinline__ void sts_tile(uint32_t a, const hp* t) {
  sts128(a, t[0].r, t[1].r, t[2].r, t[3].r);
  sts128(a + 512, t[0].i, t[1].i, t[2].i, t[3].i);
}
template <int STEP> __device__ __forceinline__ void put_tap(uint32_t a, float v) {
  uint32_t h = pack_h(v, v);
  sts16(a, h);
  sts16(a + STEP * 4 + 2, h);
}

__global__ void __launch_bounds__(512, 1)
fused_s4_ffn_kernel(const __grid_constant__ CUtensorMap tmX, const __grid_constant__ CUtensorMap tmW1, const Params p) {
  extern __shared__ __align__(1024) unsigned char smem_raw[];
  const uint32_t sb = (uint32_t)__cvta_generic_to_shared(smem_raw);
  const int tid = threadIdx.x, lane = tid & 31;
  const int warp = __shfl_sync(0xffffffffu, tid >> 5, 0);
  const int g = lane >> 2, q = lane & 3;
  int wid;
  if (p.use_smid) {
    uint32_t s; asm("mov.u32 %0, %smid;" : "=r"(s));
    int gp, i;
    if (s < 64) { gp = (s & 15) >> 1; i = s >> 4; }
    else if (s < 120) { int t = s - 64; i = t / 14; gp = 1 + ((t - i * 14) >> 1); i += 4; }
    else if (s < 124) { gp = 8; i = (s - 120) >> 1; }
    else { gp = 0; i = 4 + ((s - 124) >> 1); }
    wid = gp < 8 ? gp * 16 + ((0x52741630 >> (4 * i)) & 7) * 2 + (s & 1) : 128 + i * 2 + (s & 1);
  } else {
    wid = blockIdx.x;
  }
  if (wid >= 128) {
    if (tid == 0) {
      unsigned ep = g_epoch[wid];
      g_epoch[wid] = ep + 1;
      poll_cnt(C_LN, (ep + 1) * 128);
    }
    return;
  }
  const int gpc = wid >> 4, qi = wid & 15;
  const int rg1 = 4 * (gpc >> 1) + (qi >> 2), j1 = 4 * (gpc & 1) + (qi & 3);
  const int rg2 = 2 * gpc + (qi >> 3), j2 = qi & 7;
  const uint32_t bar = sb + OFF_BAR;

  float kacc[5][4];
  const int kch = warp % 5, kpart = warp / 5;
  float dskip = 0.f;
  {
    uint32_t pa[6] = {0, 0, 0, 0, 0, 0};
    float ldt = 0.f;
    if (warp < 15) {
      const int ch = wid * 5 + kch;
      const int o = (ch * NMODE + kpart * 64) / 2 + lane;
      pa[0] = __ldg((const uint32_t*)p.are + o); pa[1] = __ldg((const uint32_t*)p.aim + o);
      pa[2] = __ldg((const uint32_t*)p.bre + o); pa[3] = __ldg((const uint32_t*)p.bim + o);
      pa[4] = __ldg((const uint32_t*)p.cre + o); pa[5] = __ldg((const uint32_t*)p.cim + o);
      ldt = __bfloat162float(p.logdt[ch]);
      dskip = __bfloat162float(p.dskip[ch]);
    } else {
      if (lane == 0) {
        unsigned ep = g_epoch[wid];
        if (sb & 1023) __trap();
        for (int i = 0; i < B_NUM; i++) {
          int c = 1;
          if ((i >= B_EMPTY1 && i < B_UFULL) || i == B_EPI || i == B_ZRDY || i >= B_EMPTY2) c = 8;
          if (i >= B_MMA && i < B_FULL2) c = 4;
          mbar_init(bar + 8 * i, c);
        }
        asm volatile("fence.mbarrier_init.release.cluster;" ::: "memory");
        fence_async_smem();
        g_epoch[wid] = ep + 1;
        sts32(sb + OFF_EP, ep + 1);
      }
      sts64(sb + OFF_ZERO + lane * 8, 0, 0);
      __syncwarp();
      if (elect1()) {
#pragma unroll 1
        for (int s = 0; s < 4; s++) {
          const uint32_t d = sb + s * SLOT1, mb = bar + 8 * (B_FULL1 + s);
          mbar_expect(mb, SLOT1);
          tma2d(d, &tmX, s * 64, rg1 * 128, mb);
#pragma unroll
          for (int b = 0; b < 3; b++) tma2d(d + 16384 + b * 8192, &tmW1, j1 * 192 + b * 64, s * 64, mb);
        }
        bulk_prefetch(p.x + wid * 16 * DM, 16 * DM * 2);
        bulk_prefetch(p.w1 + wid * 5 * FF, 5 * FF * 2);
        bulk_prefetch(p.w2 + wid * 12 * DM, 12 * DM * 2);
      }
      __syncwarp();
    }
#pragma unroll
    for (int j = 0; j < 5; j++) { kacc[j][0] = kacc[j][1] = kacc[j][2] = kacc[j][3] = 0.f; }
    if (warp < 15) {
      const float dt = rnd_bf(expf(ldt));
      cf c0 = cmul(cf{bflo(pa[4]), bflo(pa[5])}, cf{bflo(pa[2]), bflo(pa[3])});
      cf c1 = cmul(cf{bfhi(pa[4]), bfhi(pa[5])}, cf{bfhi(pa[2]), bfhi(pa[3])});
      float mx = fmaxf(fmaxf(fabsf(c0.r), fabsf(c0.i)), fmaxf(fabsf(c1.r), fabsf(c1.i)));
      int ex = (int)(__reduce_max_sync(0xffffffffu, __float_as_uint(mx)) >> 23);
      ex = min(max(ex, 20), 240);
      const float sc = __uint_as_float((262 - ex) << 23);
      const float isc = __uint_as_float((ex - 8) << 23) * dt;
      float k0 = c0.r + c1.r;
#pragma unroll
      for (int o = 16; o; o >>= 1) k0 += __shfl_xor_sync(0xffffffffu, k0, o);
      if (lane == 0) sts32(sb + OFF_K0 + warp * 4, __float_as_uint(k0 * dt));
      float zr = bflo(pa[0]) * dt * 1.4426950408889634f, th = bflo(pa[1]) * dt;
      cf c = cf{c0.r * sc, c0.i * sc};
      const uint32_t ks = sb + OFF_KS + warp * 4096;
      const uint32_t ka = ks + (lane >> 3) * 512 + (lane & 7) * 16;
      const uint32_t kb = ks + ((lane >> 3) & 1) * 512 + ((lane >> 4) * 8 + (lane & 7)) * 16;
#pragma unroll 1
      for (int it = 0; it < 2; it++) {
        float m = ex2a(zr);
        const cf w1 = cf{m * __cosf(th), m * __sinf(th)};
        m = ex2a(zr * 8.f);
        const cf w8 = cf{m * __cosf(th * 8.f), m * __sinf(th * 8.f)};
        const cf w16 = csq(w8), w32 = csq(w16), w64 = csq(w32), w128 = csq(w64), w256 = csq(w128), w512 = csq(w256), w1024 = csq(w512);
        hp lo[8];
        lo[0] = hpack(cf{1.f, 0.f}, cf{w8.r, -w8.i});
        lo[1] = hmulc(lo[0], pack_h(w16.r, -w16.i));
        { const uint32_t k = pack_h(w32.r, -w32.i); lo[2] = hmulc(lo[0], k); lo[3] = hmulc(lo[1], k); }
        { const uint32_t k = pack_h(w64.r, -w64.i);
#pragma unroll
          for (int i = 0; i < 4; i++) lo[4 + i] = hmulc(lo[i], k); }
        const uint32_t st = ks + lane * 16;
        sts128(st, lo[0].r, lo[1].r, lo[2].r, lo[3].r);
        sts128(st + 512, lo[4].r, lo[5].r, lo[6].r, lo[7].r);
        sts128(st + 1024, lo[0].i, lo[1].i, lo[2].i, lo[3].i);
        sts128(st + 1536, lo[4].i, lo[5].i, lo[6].i, lo[7].i);
        const cf t1 = cmul(c, w1), t2 = cmul(t1, w1), t3 = cmul(t2, w1), t4 = cmul(t3, w1);
        const cf t5 = cmul(t4, w1), t6 = cmul(t5, w1), t7 = cmul(t6, w1), t8 = cmul(c, w8);
        hp T0[4], T1[4], T2[4], T3[4], T4[4];
        T0[0] = hpack(t4, t8); T0[1] = hpack(t2, t6); T0[2] = hpack(t1, t5); T0[3] = hpack(t3, t7);
        const uint32_t k128 = pack_h(w128.r, w128.i), k256 = pack_h(w256.r, w256.i), k512 = pack_h(w512.r, w512.i);
#pragma unroll
        for (int i = 0; i < 4; i++) T1[i] = hmulc(T0[i], k128);
        sts_tile(st + 2048, T0);
        sts_tile(st + 3072, T1);
        __syncwarp();
        uint32_t af[4][4];
#pragma unroll
        for (int mg = 0; mg < 4; mg++) ldsm4t(af[mg], ka + mg * 128);
#pragma unroll
        for (int j = 0; j < 2; j++)
#pragma unroll
          for (int mg = 0; mg < 4; mg += 2) {
            uint32_t b[4];
            ldsm4t(b, kb + 2048 + j * 1024 + mg * 128);
            hmma(kacc[j], af[mg][0], af[mg][1], af[mg][2], af[mg][3], b[0], b[1]);
            hmma(kacc[j], af[mg + 1][0], af[mg + 1][1], af[mg + 1][2], af[mg + 1][3], b[2], b[3]);
          }
        T2[0] = hmulc(T0[0], k256); T2[1] = hmulc(T0[1], k256); T2[2] = hmulc(T1[0], k256); T2[3] = hmulc(T1[1], k256);
        T3[0] = hmulc(T0[0], k512); T3[1] = hmulc(T1[0], k512); T3[2] = hmulc(T2[0], k512); T3[3] = hmulc(T2[2], k512);
        { const cf u0 = cmul(t8, w1024), u1 = cmul(u0, w128);
          T4[0] = hpack(u0, u1); T4[1] = hmulc(T4[0], k256); T4[2] = hmulc(T4[0], k512); T4[3] = hmulc(T4[1], k512); }
        __syncwarp();
        sts_tile(st, T2);
        sts_tile(st + 1024, T3);
        sts_tile(st + 2048, T4);
        __syncwarp();
#pragma unroll
        for (int j = 0; j < 3; j++)
#pragma unroll
          for (int mg = 0; mg < 4; mg += 2) {
            uint32_t b[4];
            ldsm4t(b, kb + j * 1024 + mg * 128);
            hmma(kacc[2 + j], af[mg][0], af[mg][1], af[mg][2], af[mg][3], b[0], b[1]);
            hmma(kacc[2 + j], af[mg + 1][0], af[mg + 1][1], af[mg + 1][2], af[mg + 1][3], b[2], b[3]);
          }
        __syncwarp();
        zr = bfhi(pa[0]) * dt * 1.4426950408889634f; th = bfhi(pa[1]) * dt;
        c = cf{c1.r * sc, c1.i * sc};
      }
#pragma unroll
      for (int j = 0; j < 5; j++) {
#pragma unroll
        for (int e = 0; e < 4; e++) kacc[j][e] *= isc;
        if (warp < 10) sts128(ks + j * 512 + lane * 16, __float_as_uint(kacc[j][0]), __float_as_uint(kacc[j][1]), __float_as_uint(kacc[j][2]), __float_as_uint(kacc[j][3]));
      }
    }
  }
  __syncthreads();
  const unsigned ep = lds32(sb + OFF_EP);

  if (warp < 8) {
    float acc[96];
    const int wg = warp >> 2;
#pragma unroll 1
    for (int s = 0; s < 10; s++) {
      const uint32_t st = sb + (s & 3) * SLOT1;
      mbar_wait(bar + 8 * (B_FULL1 + (s & 3)), (s >> 2) & 1);
      wg_fence();
#pragma unroll
      for (int kk = 0; kk < 4; kk++)
        wgmma_n192(acc, mkdesc(st + wg * 8192 + kk * 32, 16, 1024, 1), mkdesc(st + 16384 + kk * 2048, 8192, 1024, 1), (s | kk) != 0);
      wg_commit();
      if (s > 0) {
        wg_wait<1>();
        const int sp = s - 1;
        if (lane == 0) mbar_arrive(bar + 8 * (sp < 6 ? B_EMPTY1 + (sp & 3) : B_DRAIN + sp - 6));
        if (warp == 0 && sp < 6) {
          mbar_wait(bar + 8 * (B_EMPTY1 + (sp & 3)), (sp >> 2) & 1);
          if (elect1()) {
            const uint32_t d = sb + (sp & 3) * SLOT1, mb = bar + 8 * (B_FULL1 + (sp & 3));
            mbar_expect(mb, SLOT1);
            tma2d(d, &tmX, (sp + 4) * 64, rg1 * 128, mb);
#pragma unroll
            for (int b = 0; b < 3; b++) tma2d(d + 16384 + b * 8192, &tmW1, j1 * 192 + b * 64, (sp + 4) * 64, mb);
          }
        }
        __syncwarp();
      }
    }
    wg_wait<0>();
    if (lane == 0) mbar_arrive(bar + 8 * (B_DRAIN + 3));
    mbar_wait(bar + 8 * B_EPI, 0);
    const uint2 s0 = lds64(sb + OFF_STAT + (warp * 16 + g) * 8), s1 = lds64(sb + OFF_STAT + (warp * 16 + g + 8) * 8);
    const float nm0 = -__uint_as_float(s0.x), r0 = __uint_as_float(s0.y), nm1 = -__uint_as_float(s1.x), r1 = __uint_as_float(s1.y);
    uint4* hd = g_h + (rg1 * 24 + j1) * 1024 + warp * 128 + q * 8 + g;
#pragma unroll
    for (int grp = 0; grp < 6; grp++) {
      uint32_t o0[4], o1[4];
#pragma unroll
      for (int tl = 0; tl < 4; tl++) {
        const int nt = grp * 4 + tl;
        const uint2 cs = lds64(sb + OFF_CS + (nt * 8 + 2 * q) * 4);
        const float ca = __uint_as_float(cs.x), cb = __uint_as_float(cs.y);
        const float a = fmaf(nm0, ca, acc[4 * nt]) * r0, b = fmaf(nm0, cb, acc[4 * nt + 1]) * r0;
        const float c = fmaf(nm1, ca, acc[4 * nt + 2]) * r1, d = fmaf(nm1, cb, acc[4 * nt + 3]) * r1;
        o0[tl] = pack_bf(fmaf(a, tanha(a), a), fmaf(b, tanha(b), b));
        o1[tl] = pack_bf(fmaf(c, tanha(c), c), fmaf(d, tanha(d), d));
      }
      uint4* dst = hd + (grp >> 1) * 8192 + (grp & 1) * 32;
      dst[0] = make_uint4(o0[0], o0[1], o0[2], o0[3]);
      dst[64] = make_uint4(o1[0], o1[1], o1[2], o1[3]);
      if (grp == 1) {
        if (warp == 7) { bar_sync(2, 256); if (lane == 0) publish(C_H0 + rg1); __syncwarp(); }
        else bar_arrive(2, 256);
      }
    }
    if (warp == 6) { bar_sync(11, 256); if (lane == 0) publish(C_H1 + rg1); __syncwarp(); }
    else bar_arrive(11, 256);
    if (warp == 4) {
      const uint4* srcA = g_h + rg2 * 24 * 1024;
      const uint4* srcB = g_w2p + j2 * 24 * 640;
      mbar_wait(bar + 8 * (B_DRAIN + 3), 0);
      if (elect1()) {
        poll_cnt(C_W2, ep * 128);
        fence_async();
#pragma unroll 1
        for (int s = 0; s < 3; s++) {
          mbar_expect(bar + 8 * (B_FULL2 + s), SLOT2);
          bulk_g2s(sb + s * SLOT2 + 16384, srcB + s * 640, 10240, bar + 8 * (B_FULL2 + s));
        }
        poll_cnt(C_H0 + rg2, ep * 8);
        fence_async();
#pragma unroll 1
        for (int s = 0; s < 3; s++) bulk_g2s(sb + s * SLOT2, srcA + s * 1024, 16384, bar + 8 * (B_FULL2 + s));
        mbar_wait(bar + 8 * (B_FREE + 0), 0);
#pragma unroll 1
        for (int s = 3; s < 5; s++) {
          mbar_wait(bar + 8 * (B_FREE + s - 2), 0);
          mbar_expect(bar + 8 * (B_FULL2 + s), SLOT2);
          bulk_g2s(sb + s * SLOT2 + 16384, srcB + s * 640, 10240, bar + 8 * (B_FULL2 + s));
          bulk_g2s(sb + s * SLOT2, srcA + s * 1024, 16384, bar + 8 * (B_FULL2 + s));
        }
      }
      __syncwarp();
    }
  } else {
    const int cw = warp - 8, ct = tid - 256;
    {
      uint2 xv[2][5];
#pragma unroll
      for (int r = 0; r < 2; r++)
#pragma unroll
        for (int i = 0; i < 5; i++) xv[r][i] = __ldg((const uint2*)(p.x + (wid * 16 + cw * 2 + r) * DM) + lane + 32 * i);
      uint4 wv[4];
      const int cc = ct % 24, rr = ct / 24;
      if (ct < 240) {
#pragma unroll
        for (int i = 0; i < 4; i++) wv[i] = __ldg((const uint4*)(p.w1 + (qi * 40 + rr * 4 + i) * FF + gpc * 192) + cc);
      }
      float sm[2], sq[2], x0[2];
#pragma unroll
      for (int r = 0; r < 2; r++) {
        x0[r] = bflo(__shfl_sync(0xffffffffu, xv[r][0].x, 0));
        float a = 0.f, b = 0.f;
#pragma unroll
        for (int i = 0; i < 5; i++) {
          const float v0 = bflo(xv[r][i].x) - x0[r], v1 = bfhi(xv[r][i].x) - x0[r], v2 = bflo(xv[r][i].y) - x0[r], v3 = bfhi(xv[r][i].y) - x0[r];
          a += (v0 + v1) + (v2 + v3);
          b = fmaf(v0, v0, b); b = fmaf(v1, v1, b); b = fmaf(v2, v2, b); b = fmaf(v3, v3, b);
        }
        sm[r] = a; sq[r] = b;
      }
#pragma unroll
      for (int o = 16; o; o >>= 1)
#pragma unroll
        for (int r = 0; r < 2; r++) { sm[r] += __shfl_xor_sync(0xffffffffu, sm[r], o); sq[r] += __shfl_xor_sync(0xffffffffu, sq[r], o); }
#pragma unroll
      for (int r = 0; r < 2; r++) {
        const float md = sm[r] * (1.f / DM);
        const float var = fmaxf(fmaf(-md, md, sq[r] * (1.f / DM)), 0.f);
        const float mb = rnd_bf(x0[r] + md);
        const float rinv = 1.f / rnd_bf(sqrtf(rnd_bf(rnd_bf(var) + 1e-5f)));
        const int row = cw * 2 + r;
        if (lane == 0) g_stats[wid * 16 + row] = make_float2(mb, 0.5f * rinv);
        const int key = ((row >> 2) << 1) | (row & 1);
        const uint32_t a = sb + OFF_LNT + row * 1280 + (((lane >> 1) ^ key) << 4) + (lane & 1) * 8;
#pragma unroll
        for (int i = 0; i < 5; i++)
          sts64(a + i * 256, pack_h((bflo(xv[r][i].x) - mb) * rinv, (bfhi(xv[r][i].x) - mb) * rinv),
                pack_h((bflo(xv[r][i].y) - mb) * rinv, (bfhi(xv[r][i].y) - mb) * rinv));
      }
      if (ct < 240) {
        float s[8];
#pragma unroll
        for (int e = 0; e < 4; e++) {
          const uint32_t a = (&wv[0].x)[e], b = (&wv[1].x)[e], c = (&wv[2].x)[e], d = (&wv[3].x)[e];
          s[2 * e] = (bflo(a) + bflo(b)) + (bflo(c) + bflo(d));
          s[2 * e + 1] = (bfhi(a) + bfhi(b)) + (bfhi(c) + bfhi(d));
        }
        const uint32_t a = sb + OFF_KS + rr * 4096 + 2560 + cc * 32;
        sts128(a, __float_as_uint(s[0]), __float_as_uint(s[1]), __float_as_uint(s[2]), __float_as_uint(s[3]));
        sts128(a + 16, __float_as_uint(s[4]), __float_as_uint(s[5]), __float_as_uint(s[6]), __float_as_uint(s[7]));
      }
    }
    bar_sync(1, 256);
    {
      const int i = lane & 7, mi = lane >> 3;
      const int row = ((i >> 1) << 2) + (i & 1) + (mi & 1) * 2;
      const int ctk = 2 * wid + (q >> 1);
      uint2* dst = (uint2*)(g_uT + (cw * 80 + g) * 256 + upos(ctk)) + (q & 1);
#pragma unroll
      for (int k = 0; k < 5; k++) {
        uint32_t r[4];
        const int c = cw * 10 + k * 2 + (mi >> 1);
        ldsm4t(r, sb + OFF_LNT + row * 1280 + ((c ^ i) << 4));
        dst[(k * 16) * 512] = make_uint2(r[0], r[1]);
        dst[(k * 16 + 8) * 512] = make_uint2(r[2], r[3]);
      }
      if (ct < 192) {
        float s = 0.f;
#pragma unroll
        for (int r = 0; r < 10; r++) s += __uint_as_float(lds32(sb + OFF_KS + r * 4096 + 2560 + ct * 4));
        g_csp[qi * FF + gpc * 192 + ct] = s;
      }
    }
    bar_sync(1, 256);
    if (warp == 15) { if (lane == 0) publish(C_LN); __syncwarp(); }
    uint4 wv[4];
    const int uu = ct / 80, ur = ct - uu * 80;
    const int U = 3 * wid + uu, uj = U & 7, ugrp = U >> 3;
    const int kp = ur < 64 ? (ur & 31) : (ur - 64);
    if (ct < 240) {
      const int fl = 8 * ((kp & 7) >> 1) + 2 * (kp >> 3) + (kp & 1);
      const uint4* src = (const uint4*)(p.w2 + (ugrp * 32 + fl) * DM + uj * 80);
      if (ur < 64) {
#pragma unroll
        for (int i = 0; i < 4; i++) wv[i] = __ldg(src + (ur >> 5) * 4 + i);
      } else {
        wv[0] = __ldg(src + 8); wv[1] = __ldg(src + 9); wv[2] = __ldg(src + 4 * 80 + 8); wv[3] = __ldg(src + 4 * 80 + 9);
      }
    }
    if (warp >= 10 && warp < 15) {
      const uint32_t pb = sb + OFF_P + kch * 3072;
#pragma unroll
      for (int i = 0; i < 6; i++) sts128(pb + i * 512 + lane * 16, 0, 0, 0, 0);
      float k0 = __uint_as_float(lds32(sb + OFF_K0 + kch * 4)) + __uint_as_float(lds32(sb + OFF_K0 + kch * 4 + 20)) +
                 __uint_as_float(lds32(sb + OFF_K0 + kch * 4 + 40)) + dskip;
      float mx = fabsf(k0);
#pragma unroll
      for (int j = 0; j < 5; j++) {
        const uint4 a = lds128(sb + OFF_KS + kch * 4096 + j * 512 + lane * 16), b = lds128(sb + OFF_KS + (kch + 5) * 4096 + j * 512 + lane * 16);
#pragma unroll
        for (int e = 0; e < 4; e++) {
          kacc[j][e] += __uint_as_float((&a.x)[e]) + __uint_as_float((&b.x)[e]);
          mx = fmaxf(mx, fabsf(kacc[j][e]));
        }
      }
      int ex = (int)(__reduce_max_sync(0xffffffffu, __float_as_uint(mx)) >> 23);
      ex = min(max(ex, 20), 240);
      const float sc = __uint_as_float((267 - ex) << 23);
#pragma unroll
      for (int j = 0; j < 5; j++)
#pragma unroll
        for (int e = 0; e < 4; e++) kacc[j][e] *= sc;
      const float k256 = __shfl_sync(0xffffffffu, kacc[1][3], 28);
      if (lane == 31) kacc[1][3] -= k256;
      __syncwarp();
      {
        const uint32_t a = pb + (P0 + 8 * g + ((0x3124 >> (4 * q)) & 7)) * 4;
#pragma unroll
        for (int j = 0; j < 2; j++)
#pragma unroll
          for (int e = 0; e < 4; e++) {
            uint32_t ad = a + (j * 128 + (e >> 1) * 64 + (e & 1) * 4) * 4;
            if (j == 1 && e == 3 && lane == 28) ad = pb + PB1 * 4;
            put_tap<1>(ad, kacc[j][e]);
          }
      }
      {
        const uint32_t a = pb + (((q & 1) ? PA1 : PB1 + 1) + 32 * (q >> 1) + 2 * g) * 4;
#pragma unroll
        for (int e = 0; e < 4; e++) put_tap<1>(a + ((e >> 1) * 16 + (e & 1)) * 4, kacc[2][e]);
        if (lane == 30) put_tap<1>(pb + (PA1 + 64) * 4, kacc[2][3]);
      }
      {
        const uint32_t a = pb + (PA2 + g + 16 * q) * 4;
#pragma unroll
        for (int e = 0; e < 4; e++) put_tap<2>(a + ((e >> 1) * 8 + (e & 1) * (PB2 - PA2)) * 4, kacc[3][e]);
      }
      {
        const uint32_t a = pb + (((g & 1) ? PB3 : PA3) + (g >> 1) + 16 * q) * 4;
#pragma unroll
        for (int e = 0; e < 4; e++) put_tap<1>(a + ((e >> 1) * 4 + (e & 1) * 8) * 4, kacc[4][e]);
      }
      if (lane == 0) put_tap<1>(pb + P0 * 4, k0 * sc);
      if (lane == 31) sts64(sb + OFF_CHC + kch * 8, (ex - 13) << 23, pack_h(kacc[3][3], kacc[3][3]));
    }
    if (ct < 240) {
      const int f0 = ugrp * 32, jj = f0 / 192, rem = f0 - jj * 192;
      uint4* dst = g_w2p + (uj * 24 + 8 * (rem >> 6) + jj) * 640 + (((rem >> 5) & 1) * 4 + (kp >> 3)) * 80 + (kp & 7);
      if (ur < 64) {
        dst += (ur >> 5) * 32;
        dst[0] = make_uint4(wv[0].x, wv[1].x, wv[2].x, wv[3].x);
        dst[8] = make_uint4(wv[0].y, wv[1].y, wv[2].y, wv[3].y);
        dst[16] = make_uint4(wv[0].z, wv[1].z, wv[2].z, wv[3].z);
        dst[24] = make_uint4(wv[0].w, wv[1].w, wv[2].w, wv[3].w);
      } else {
        dst[64] = make_uint4(wv[0].x, wv[0].z, wv[1].x, wv[1].z);
        dst[72] = make_uint4(wv[0].y, wv[0].w, wv[1].y, wv[1].w);
        dst[160 + 64] = make_uint4(wv[2].x, wv[2].z, wv[3].x, wv[3].z);
        dst[160 + 72] = make_uint4(wv[2].y, wv[2].w, wv[3].y, wv[3].w);
      }
    }
    fence_async_smem();
    bar_sync(1, 256);
    if (warp == 15) { if (lane == 0) publish(C_W2); __syncwarp(); }
    else {
      if (lane == 0) poll_cnt(C_LN, ep * 128);
      __syncwarp();
      if (warp == 8) {
        if (elect1()) {
          fence_async();
          mbar_expect(bar + 8 * B_UFULL, 20480);
          bulk_g2s(sb + OFF_U, g_uT + wid * 5 * 256, 20480, bar + 8 * B_UFULL);
        }
        __syncwarp();
      }
      if (ct < 192) {
        float s = 0.f;
#pragma unroll
        for (int r = 0; r < 16; r++) s += __ldcg(g_csp + r * FF + j1 * 192 + ct);
        sts32(sb + OFF_CS + ct * 4, __float_as_uint(s));
      } else {
        const uint4* src = (const uint4*)(g_stats + rg1 * 128) + lane;
        const uint4 a = __ldcg(src), b = __ldcg(src + 32);
        sts128(sb + OFF_STAT + lane * 16, a.x, a.y, a.z, a.w);
        sts128(sb + OFF_STAT + 512 + lane * 16, b.x, b.y, b.z, b.w);
      }
      __syncwarp();
    }
    if (lane == 0) mbar_arrive(bar + 8 * B_EPI);
    mbar_wait(bar + 8 * B_UFULL, 0);
    mbar_wait(bar + 8 * (B_DRAIN + 1), 0);
#pragma unroll 1
    for (int task = cw; task < 27; task += 8) {
      if (task < 15) {
        const int ch = task / 3, j = (task - ch * 3) * 32 + lane;
        const uint32_t ub = sb + OFF_U + ch * 4096, zb = sb + OFF_Z + ch * ZSZ;
        uint32_t w_[16];
        uint32_t* w = w_ + 8;
        {
          uint2 a = make_uint2(0, 0); uint4 b = make_uint4(0, 0, 0, 0);
          if (j > 0) { a = lds64(ub + upos(2 * j - 2) * 16 + 8); b = lds128(ub + upos(2 * j - 1) * 16); }
          const uint4 c = lds128(ub + upos(2 * j) * 16), d = lds128(ub + upos(2 * j + 1) * 16);
          w[-6] = a.x; w[-5] = a.y; w[-4] = b.x; w[-3] = b.y; w[-2] = b.z; w[-1] = b.w;
          w[0] = c.x; w[1] = c.y; w[2] = c.z; w[3] = c.w; w[4] = d.x; w[5] = d.y; w[6] = d.z;
        }
        uint32_t o_[16], d_[16], e_[16], b3_[16], b5_[16];
        uint32_t *o = o_ + 8, *d = d_ + 8, *e = e_ + 8, *b3 = b3_ + 8, *b5 = b5_ + 8;
#pragma unroll
        for (int i = -6; i <= 5; i++) { o[i] = odd_pair(w[i], w[i + 1]); d[i] = hadd(w[i], o[i]); }
#pragma unroll
        for (int i = -5; i <= 5; i++) b3[i] = hadd(d[i], o[i - 1]);
#pragma unroll
        for (int i = -5; i <= 4; i++) e[i] = hadd(d[i - 1], d[i]);
#pragma unroll
        for (int i = -4; i <= 4; i++) b5[i] = hadd(e[i], w[i + 1]);
        const uint32_t a2 = zb + ((j >> 3) * 16 + (j & 7)) * 16;
        sts128(a2 + ZA2, b3[-2], b3[-1], b3[0], b3[1]);
        sts128(a2 + ZA2 + 128, b3[2], b3[3], b3[4], b3[5]);
        sts128(a2 + ZB2, b5[-4], b5[-3], b5[-2], b5[-1]);
        sts128(a2 + ZB2 + 128, b5[0], b5[1], b5[2], b5[3]);
        if (j < 64) {
          sts128(a2 + ZS, d[-2], d[-1], d[0], d[1]);
          sts128(a2 + ZS + 128, d[2], d[3], d[4], d[5]);
          uint32_t b7[8], b9[8];
#pragma unroll
          for (int i = -4; i <= 3; i++) { b7[i + 4] = hadd(b3[i - 1], e[i + 1]); b9[i + 4] = hadd(e[i - 1], b5[i + 1]); }
          const uint32_t a3 = zb + ((j >> 4) * 32 + (j & 15)) * 16;
          sts128(a3 + ZA3, b7[0], b7[1], b7[2], b7[3]);
          sts128(a3 + ZA3 + 256, b7[4], b7[5], b7[6], b7[7]);
          sts128(a3 + ZB3 + 256, b9[0], b9[1], b9[2], b9[3]);
          const int jn = (j + 1) & 63;
          if (jn == 0) { b9[4] = b9[5] = b9[6] = b9[7] = 0; }
          sts128(zb + ZB3 + ((jn >> 4) * 32 + (jn & 15)) * 16, b9[4], b9[5], b9[6], b9[7]);
        }
      } else {
        const int fl = (task - 15) * 32 + lane;
        if (fl < 360) {
          const int ch = fl / 72, a = fl - ch * 72;
          const uint32_t ub = sb + OFF_U + ch * 4096, zb = sb + OFF_Z + ch * ZSZ;
          uint32_t w[2][10], b3[2][8];
#pragma unroll
          for (int hf = 0; hf < 2; hf++) {
            const int c0 = 2 * a - 32 + 112 * hf;
            uint4 x = make_uint4(0, 0, 0, 0), y = x; uint32_t l = 0, r = 0;
            if (c0 > 0) l = lds32(ub + upos(c0 - 1) * 16 + 12);
            if (c0 >= 0) { x = lds128(ub + upos(c0) * 16); y = lds128(ub + upos(c0 + 1) * 16); }
            if (c0 >= -2) r = lds32(ub + upos(c0 + 2) * 16);
            w[hf][0] = l; w[hf][1] = x.x; w[hf][2] = x.y; w[hf][3] = x.z; w[hf][4] = x.w;
            w[hf][5] = y.x; w[hf][6] = y.y; w[hf][7] = y.z; w[hf][8] = y.w; w[hf][9] = r;
            uint32_t o[9];
#pragma unroll
            for (int i = 0; i < 9; i++) o[i] = odd_pair(w[hf][i], w[hf][i + 1]);
#pragma unroll
            for (int i = 0; i < 8; i++) b3[hf][i] = hadd(hadd(o[i], o[i + 1]), w[hf][i + 1]);
          }
#pragma unroll
          for (int r = 0; r < 4; r++) {
            const uint32_t ad = zb + (4 * a + (r ^ ((a >> 1) & 3))) * 16;
            sts128(ad + ZA1, w[0][2 * r], w[0][2 * r + 1], w[1][2 * r], w[1][2 * r + 1]);
            sts128(ad + ZB1, b3[0][2 * r], b3[0][2 * r + 1], b3[1][2 * r], b3[1][2 * r + 1]);
          }
        }
      }
    }
    __syncwarp();
    if (lane == 0) mbar_arrive(bar + 8 * B_ZRDY);
  }

  {
    const int wg = warp >> 2, role = warp & 3;
    if (wg != 1) {
      mbar_wait(bar + 8 * B_ZRDY, 0);
      mbar_wait(bar + 8 * (B_DRAIN + 3), 0);
    }
#pragma unroll 1
    for (int ch = (wg == 0 ? 2 : wg == 1 ? 9 : wg - 2); ch < 5; ch += 3) {
      const uint32_t ub = sb + OFF_U + ch * 4096, zb = sb + OFF_Z + ch * ZSZ, pb = sb + OFF_P + ch * 3072;
      const uint2 chc = lds64(sb + OFF_CHC + ch * 8);
      const float isc = __uint_as_float(chc.x);
      if (ch >= 2) mbar_wait(bar + 8 * (B_MMA + ch - 2), 0);
      if (role < 2) {
        float acc[8][4];
#pragma unroll
        for (int r = 0; r < 8; r++) { acc[r][0] = acc[r][1] = acc[r][2] = acc[r][3] = 0.f; }
        if (role == 1 && lane == 28) {
          const uint32_t k = lds32(pb + PB1 * 4), u0 = lds32(ub);
          acc[7][2] = __low2float(*reinterpret_cast<const __half2*>(&k)) * __low2float(*reinterpret_cast<const __half2*>(&u0));
        }
        uint32_t ga[3];
#pragma unroll
        for (int gm = 0; gm < 3; gm++) {
          const int hb = 2 * (lane & 7) + role - 2 + gm;
          ga[gm] = (hb < 0 ? sb + OFF_ZERO : ub + hb * 256) + ((((lane >> 3) ^ (hb >> 1)) & 7) << 4);
        }
        uint32_t b[12][4], R[35];
        const uint32_t pa = pb + (P0 + g - 2 * q) * 4;
        R[0] = 0; R[34] = 0;
#pragma unroll
        for (int i = 11; i >= 8; i--) ldsm4(b[i], (ga[2] ^ ((i & 1) * 64 + ((i >> 1) & 1) * 16)) + ((i >> 1) & 1) * 128);
#pragma unroll
        for (int m = 0; m <= 16; m++) {
          R[2 * m + 1] = lds32(pa + (2 * m) * 32);
          if (m < 16) R[2 * m + 2] = lds32(pa + (2 * m + 1) * 32);
          if ((m & 1) == 0 && m < 16) {
            const int i = 7 - (m >> 1);
            ldsm4(b[i], (ga[i >> 2] ^ ((i & 1) * 64 + ((i >> 1) & 1) * 16)) + ((i >> 1) & 1) * 128);
          }
#pragma unroll
          for (int r = 7; r >= 0; r--) {
            const int f = 16 + r - m;
            hmma(acc[r], R[2 * m + 1], R[2 * m + 2], R[2 * m], R[2 * m + 1], b[f >> 1][(f & 1) * 2], b[f >> 1][(f & 1) * 2 + 1]);
          }
        }
        uint32_t o[16];
#pragma unroll
        for (int r = 0; r < 8; r++) { o[2 * r] = pack_bf(acc[r][0] * isc, acc[r][1] * isc); o[2 * r + 1] = pack_bf(acc[r][2] * isc, acc[r][3] * isc); }
        if (lane == 0) mbar_arrive(bar + 8 * (B_MMA + ch));
        bar_sync(7 + wg, 64);
#pragma unroll
        for (int i = 0; i < 4; i++)
          stsm4t((ga[2] ^ ((i & 1) * 64 + ((i >> 1) & 1) * 16)) + ((i >> 1) & 1) * 128, o[4 * i], o[4 * i + 1], o[4 * i + 2], o[4 * i + 3]);
      } else if (role == 2) {
        float acc[14][4];
#pragma unroll
        for (int r = 0; r < 14; r++) { acc[r][0] = acc[r][1] = acc[r][2] = acc[r][3] = 0.f; }
#pragma unroll 1
        for (int arr = 0; arr < 2; arr++) {
          uint32_t R[11];
          const uint32_t pa = pb + (PA1 + arr * (PB1 - PA1) + g - 2 * q) * 4;
          const uint32_t za = zb + ZA1 + arr * (ZB1 - ZA1) + ((lane ^ (lane >> 3)) << 4);
          R[0] = 0; R[10] = 0;
#pragma unroll
          for (int i = 0; i < 9; i++) R[i + 1] = lds32(pa + i * 32);
#pragma unroll
          for (int ip = 0; ip < 9; ip++) {
            uint32_t b[4];
            ldsm4t(b, za + ip * 512);
#pragma unroll
            for (int hh = 0; hh < 2; hh++)
#pragma unroll
              for (int m = 0; m < 5; m++) {
                const int i = 2 * ip + hh - 4 + m;
                if (i >= 0 && i < 14) hmma(acc[i], R[2 * m + 1], R[2 * m + 2], R[2 * m], R[2 * m + 1], b[2 * hh], b[2 * hh + 1]);
              }
          }
        }
        uint32_t o[28];
#pragma unroll
        for (int r = 0; r < 14; r++) { o[2 * r] = pack_bf(acc[r][0] * isc, acc[r][1] * isc); o[2 * r + 1] = pack_bf(acc[r][2] * isc, acc[r][3] * isc); }
        if (lane == 0) mbar_arrive(bar + 8 * (B_MMA + ch));
        __syncwarp();
        const uint32_t a = zb + (q >> 1) * (14 * 128 + 64) + (2 * g + (q & 1)) * 4;
#pragma unroll
        for (int r = 0; r < 28; r++) sts32(a + r * 64, o[r]);
      } else {
        float acc[12][4];
        {
          float d[4][2][4];
#pragma unroll
          for (int r = 0; r < 8; r++) { d[r >> 1][r & 1][0] = d[r >> 1][r & 1][1] = d[r >> 1][r & 1][2] = d[r >> 1][r & 1][3] = 0.f; }
#pragma unroll 1
          for (int arr = 0; arr < 2; arr++) {
            uint32_t R[9];
            const uint32_t pa = pb + (PA3 + arr * (PB3 - PA3) + g - 2 * q) * 4;
            const uint32_t za = zb + ZA3 + arr * (ZB3 - ZA3) + lane * 16;
            R[0] = 0;
#pragma unroll
            for (int i = 0; i < 8; i++) R[i + 1] = lds32(pa + i * 32);
#pragma unroll
            for (int io = 0; io < 4; io++) {
              uint32_t b[4];
              ldsm4t(b, za + io * 512);
#pragma unroll
              for (int m = 0; m + io < 4; m++) {
                hmma(d[io + m][0], R[2 * m + 1], R[2 * m + 2], R[2 * m], R[2 * m + 1], b[0], b[1]);
                hmma(d[io + m][1], R[2 * m + 1], R[2 * m + 2], R[2 * m], R[2 * m + 1], b[2], b[3]);
              }
            }
          }
#pragma unroll
          for (int r = 0; r < 4; r++) {
            acc[r][0] = acc[r][1] = acc[r][2] = acc[r][3] = 0.f;
            acc[4 + 2 * r][0] = d[r][0][0]; acc[4 + 2 * r][1] = d[r][0][1]; acc[4 + 2 * r][2] = d[r][1][0]; acc[4 + 2 * r][3] = d[r][1][1];
            acc[5 + 2 * r][0] = d[r][0][2]; acc[5 + 2 * r][1] = d[r][0][3]; acc[5 + 2 * r][2] = d[r][1][2]; acc[5 + 2 * r][3] = d[r][1][3];
          }
        }
        {
          const uint32_t kd = (g >> 1) == q ? (chc.y & ((g & 1) ? 0xffff0000u : 0xffffu)) : 0u;
#pragma unroll
          for (int ip = 0; ip < 4; ip++) {
            uint32_t b[4];
            ldsm4t(b, zb + ZS + lane * 16 + ip * 512);
            hmma(acc[4 + 2 * ip], kd, 0, 0, kd, b[0], b[1]);
            hmma(acc[5 + 2 * ip], kd, 0, 0, kd, b[2], b[3]);
          }
        }
#pragma unroll 1
        for (int arr = 0; arr < 2; arr++) {
          uint32_t A0[5], A1[5], A2[5];
          const uint32_t pa = pb + (PA2 + arr * (PB2 - PA2) + 2 * g - 4 * q) * 4;
          const uint32_t za = zb + ZA2 + arr * (ZB2 - ZA2) + lane * 16;
#pragma unroll
          for (int m = 0; m < 5; m++) { const uint2 v = lds64(pa + m * 64); A0[m] = v.x; A1[m] = v.y; A2[m] = lds32(pa + m * 64 - 4); }
#pragma unroll
          for (int ip = 0; ip < 6; ip++) {
            uint32_t b[4];
            ldsm4t(b, za + ip * 512);
#pragma unroll
            for (int hh = 0; hh < 2; hh++)
#pragma unroll
              for (int m = 0; m < 5; m++) {
                const int i = 2 * ip + hh + m;
                if (i < 12) hmma(acc[i], A0[m], A1[m], A2[m], A0[m], b[2 * hh], b[2 * hh + 1]);
              }
          }
        }
        uint32_t o[24];
#pragma unroll
        for (int r = 0; r < 12; r++) { o[2 * r] = pack_bf(acc[r][0] * isc, acc[r][1] * isc); o[2 * r + 1] = pack_bf(acc[r][2] * isc, acc[r][3] * isc); }
        if (lane == 0) mbar_arrive(bar + 8 * (B_MMA + ch));
        __syncwarp();
        const uint32_t a = zb + ZA2 + ((lane ^ ((lane >> 1) & 4)) << 4);
#pragma unroll
        for (int i = 0; i < 6; i++) stsm4(a + i * 512, o[4 * i], o[4 * i + 1], o[4 * i + 2], o[4 * i + 3]);
      }
      bar_sync(3 + wg, 128);
      {
        const int dl = qi * 5 + ch;
        int row;
        if (dl < 64) row = 8 * (4 * (dl >> 5) + ((dl >> 1) & 3)) + ((dl >> 3) & 3) * 2 + (dl & 1);
        else row = 8 * (8 + ((dl >> 1) & 1)) + ((dl - 64) >> 2) * 2 + (dl & 1);
#pragma unroll
        for (int hh = 0; hh < 2; hh++) {
          const int c = (tid & 127) + 128 * hh;
          uint4 v = lds128(ub + upos(c) * 16);
          if (c >= 32) {
            const uint4 y = lds128(zb + (c - 32) * 16 + (c >= 144 ? 64 : 0));
            v.x = badd(v.x, y.x); v.y = badd(v.y, y.y); v.z = badd(v.z, y.z); v.w = badd(v.w, y.w);
          }
          if (c >= 64) {
            const uint4 y = lds128(zb + ZA2 + (((c - 64) & ~15) + ((((c >> 1) & 7) + (c & 1) * 8) ^ ((c & 1) * 4))) * 16);
            v.x = badd(v.x, y.x); v.y = badd(v.y, y.y); v.z = badd(v.z, y.z); v.w = badd(v.w, y.w);
          }
          g_sT[((gpc * 16 + (c >> 4)) * 80 + row) * 16 + ((c & 15) ^ (row & 7))] = v;
        }
      }
      fence_async_smem();
      __syncwarp();
      if (lane == 0) mbar_arrive(bar + 8 * (B_FREE + ch));
    }
  }

  if (warp < 8) {
    const int wg = warp >> 2;
    uint4 xa[2][2]; uint2 xb[2];
    const size_t go = (size_t)(rg2 * 128 + warp * 16 + g) * DM + j2 * 80;
#pragma unroll
    for (int hh = 0; hh < 2; hh++) {
      xa[hh][0] = __ldg((const uint4*)(p.x + go + hh * 8 * DM) + q);
      xa[hh][1] = __ldg((const uint4*)(p.x + go + hh * 8 * DM) + 4 + q);
      xb[hh] = __ldg((const uint2*)(p.x + go + hh * 8 * DM + 64) + q);
    }
    float acc[40];
    mbar_wait(bar + 8 * (B_MMA + 3), 0);
    mbar_wait(bar + 8 * (B_MMA + 4), 0);
    int slot = 0, ph = 0;
#pragma unroll 1
    for (int s = 0; s < 24; s++) {
      const uint32_t st = sb + slot * SLOT2;
      mbar_wait(bar + 8 * (B_FULL2 + slot), ph);
      wg_fence();
#pragma unroll
      for (int kk = 0; kk < 4; kk++)
        wgmma_n80(acc, mkdesc(st + wg * 8192 + kk * 256, 128, 1024, 0), mkdesc(st + 16384 + kk * 2560, 1280, 128, 0), (s | kk) != 0);
      wg_commit();
      if (s > 0) {
        wg_wait<1>();
        if (lane == 0) mbar_arrive(bar + 8 * (B_EMPTY2 + (slot == 0 ? NS2 - 1 : slot - 1)));
        __syncwarp();
      }
      if (++slot == NS2) { slot = 0; ph ^= 1; }
    }
    mbar_wait(bar + 8 * B_SFULL, 0);
    uint32_t sv[5][4];
    {
      const int i = lane & 7, mi = lane >> 3;
      const uint32_t a = sb + OFF_U + ((mi >> 1) * 8 + i) * 256 + (((2 * warp + (mi & 1)) ^ i) << 4);
#pragma unroll
      for (int k = 0; k < 5; k++) ldsm4t(sv[k], a + k * 4096);
    }
    wg_wait<0>();
#pragma unroll
    for (int hh = 0; hh < 2; hh++) {
      uint32_t o[10];
#pragma unroll
      for (int tl = 0; tl < 10; tl++) {
        const uint32_t xw = tl < 8 ? (&xa[hh][tl >> 2].x)[tl & 3] : (&xb[hh].x)[tl - 8];
        const uint32_t sw = sv[tl >> 1][(tl & 1) * 2 + hh];
        const float a = 0.5f * acc[4 * tl + 2 * hh], b = 0.5f * acc[4 * tl + 2 * hh + 1];
        o[tl] = pack_bf(fmaf(bflo(sw), fmaf(a, tanha(a), a), bflo(xw)), fmaf(bfhi(sw), fmaf(b, tanha(b), b), bfhi(xw)));
      }
      __nv_bfloat16* op = p.out + go + hh * 8 * DM;
      ((uint4*)op)[q] = make_uint4(o[0], o[1], o[2], o[3]);
      ((uint4*)op)[4 + q] = make_uint4(o[4], o[5], o[6], o[7]);
      ((uint2*)(op + 64))[q] = make_uint2(o[8], o[9]);
    }
  } else if (warp == 8) {
    if (elect1()) {
      const uint4* srcA = g_h + rg2 * 24 * 1024;
      const uint4* srcB = g_w2p + j2 * 24 * 640;
      poll_cnt(C_W2, ep * 128);
      poll_cnt(C_H0 + rg2, ep * 8);
      fence_async();
      mbar_wait(bar + 8 * (B_FREE + 2), 0);
      mbar_wait(bar + 8 * (B_FREE + 3), 0);
      int slot = 5, ph = 1;
#pragma unroll 1
      for (int s = 5; s < 24; s++) {
        if (s == 8) { poll_cnt(C_H1 + rg2, ep * 8); fence_async(); }
        mbar_wait(bar + 8 * (B_EMPTY2 + slot), ph);
        const uint32_t mb = bar + 8 * (B_FULL2 + slot), d = sb + slot * SLOT2;
        mbar_expect(mb, SLOT2);
        bulk_g2s(d, srcA + s * 1024, 16384, mb);
        bulk_g2s(d + 16384, srcB + s * 640, 10240, mb);
        if (++slot == NS2) { slot = 0; ph ^= 1; }
      }
    }
    __syncwarp();
  } else if (warp == 12) {
    if (elect1()) {
#pragma unroll 1
      for (int c = 0; c < 5; c++) mbar_wait(bar + 8 * (B_FREE + c), 0);
      publish(C_S + gpc);
      poll_cnt(C_S + j2, ep * 16);
      fence_async();
      mbar_expect(bar + 8 * B_SFULL, 20480);
      bulk_g2s(sb + OFF_U, g_sT + (j2 * 16 + rg2) * 1280, 20480, bar + 8 * B_SFULL);
    }
    __syncwarp();
  }
}

typedef CUresult (*EncodeFn)(CUtensorMap*, CUtensorMapDataType, cuuint32_t, void*, const cuuint64_t*, const cuuint64_t*,
                             const cuuint32_t*, const cuuint32_t*, CUtensorMapInterleave, CUtensorMapSwizzle,
                             CUtensorMapL2promotion, CUtensorMapFloatOOBfill);

}

extern "C" void kernel_launch(void* const* d_in, const int* in_sizes, int n_in, void* d_out, int out_size) {
  static EncodeFn enc = nullptr;
  static int nsm = 0;
  if (!enc) {
    void* fn = nullptr;
    cudaDriverEntryPointQueryResult qr;
    cudaGetDriverEntryPoint("cuTensorMapEncodeTiled", &fn, cudaEnableDefault, &qr);
    enc = (EncodeFn)fn;
    int dev = 0;
    cudaGetDevice(&dev);
    cudaDeviceGetAttribute(&nsm, cudaDevAttrMultiProcessorCount, dev);
    cudaFuncSetAttribute(fused_s4_ffn_kernel, cudaFuncAttributeMaxDynamicSharedMemorySize, SMEM_BYTES);
  }
  Params p;
  p.x = (const __nv_bfloat16*)d_in[0];
  p.are = (const __nv_bfloat16*)d_in[1]; p.aim = (const __nv_bfloat16*)d_in[2];
  p.bre = (const __nv_bfloat16*)d_in[3]; p.bim = (const __nv_bfloat16*)d_in[4];
  p.cre = (const __nv_bfloat16*)d_in[5]; p.cim = (const __nv_bfloat16*)d_in[6];
  p.logdt = (const __nv_bfloat16*)d_in[7]; p.dskip = (const __nv_bfloat16*)d_in[8];
  p.w1 = (const __nv_bfloat16*)d_in[10]; p.w2 = (const __nv_bfloat16*)d_in[11];
  p.out = (__nv_bfloat16*)d_out;
  p.use_smid = nsm == 132;
  CUtensorMap tmX, tmW1;
  const cuuint32_t es[2] = {1, 1};
  {
    const cuuint64_t gd[2] = {DM, SEQ}, gs[1] = {DM * 2};
    const cuuint32_t bx[2] = {64, 128};
    enc(&tmX, CU_TENSOR_MAP_DATA_TYPE_BFLOAT16, 2, d_in[0], gd, gs, bx, es, CU_TENSOR_MAP_INTERLEAVE_NONE,
        CU_TENSOR_MAP_SWIZZLE_128B, CU_TENSOR_MAP_L2_PROMOTION_L2_128B, CU_TENSOR_MAP_FLOAT_OOB_FILL_NONE);
  }
  {
    const cuuint64_t gd[2] = {FF, DM}, gs[1] = {FF * 2};
    const cuuint32_t bx[2] = {64, 64};
    enc(&tmW1, CU_TENSOR_MAP_DATA_TYPE_BFLOAT16, 2, d_in[10], gd, gs, bx, es, CU_TENSOR_MAP_INTERLEAVE_NONE,
        CU_TENSOR_MAP_SWIZZLE_128B, CU_TENSOR_MAP_L2_PROMOTION_L2_128B, CU_TENSOR_MAP_FLOAT_OOB_FILL_NONE);
  }
  fused_s4_ffn_kernel<<<p.use_smid ? 132 : 128, 512, SMEM_BYTES>>>(tmX, tmW1, p);
}
```

```cpp
#include <cuda_runtime.h>
#include <cuda_bf16.h>
#include <cuda_fp16.h>
#include <cuda.h>
#include <stdint.h>

namespace {

constexpr int SEQ = 2048, DM = 640, NMODE = 192, FF = 1536;

constexpr int SLOT1 = 40960;
constexpr int SLOT2 = 26624;
constexpr int NS2 = 6;
constexpr int OFF_Z = 94976, ZSZ = 19712;
constexpr int ZA3 = 0, ZB3 = 2048, ZS = 4096, ZA2 = 6144, ZB2 = 9216, ZA1 = 12288, ZB1 = 16000;
constexpr int OFF_U = 193536;
constexpr int OFF_P = 214016;
constexpr int OFF_KS = 163840;
constexpr int OFF_MISC = 229376;
constexpr int OFF_ZERO = OFF_MISC + 128;
constexpr int OFF_CHC = OFF_MISC + 16;
constexpr int OFF_EP = OFF_MISC + 64;
constexpr int OFF_K0 = OFF_MISC + 256;
constexpr int OFF_BAR = OFF_MISC + 384;
constexpr int OFF_STAT = OFF_MISC + 1024;
constexpr int OFF_CS = OFF_MISC + 2048;
constexpr int SMEM_BYTES = OFF_MISC + 3072;
constexpr int P0 = 8, PA1 = 280, PB1 = 360, PA2 = 448, PB2 = 544, PA3 = 632, PB3 = 704;
enum { B_FULL1 = 0, B_EMPTY1 = 4, B_DRAIN = 8, B_UFULL = 12, B_EPI = 13, B_ZRDY = 14, B_SFULL = 15,
       B_MMA = 16, B_FREE = 21, B_FULL2 = 26, B_EMPTY2 = 32, B_NUM = 38 };
enum { C_LN = 0, C_CS = 1, C_H0 = 2, C_H1 = 18, C_S = 34, C_W2 = 42, C_NUM = 43 };

struct Scratch {
  unsigned cnt[64 * 32];
  unsigned epoch[256];
  float2 stats[SEQ];
  float cs[FF];
  uint4 uT[DM * 256];
  uint4 w2p[8 * 24 * 640];
  uint4 sT[8 * 16 * 1280];
  uint4 h[16 * 24 * 1024];
};
__device__ __align__(1024) Scratch g_scr;
constexpr uint32_t sb = 1024;
constexpr uint32_t bar = sb + OFF_BAR;

struct Params {
  const __nv_bfloat16 *are, *aim, *bre, *bim, *cre, *cim, *logdt, *dskip, *x, *w1, *w2;
  __nv_bfloat16* out;
  Scratch* scr;
};

__device__ __forceinline__ void mbar_init(uint32_t a, int c) { asm volatile("mbarrier.init.shared::cta.b64 [%0], %1;" ::"r"(a), "r"(c)); }
__device__ __forceinline__ void mbar_expect(uint32_t a, int b) { asm volatile("mbarrier.arrive.expect_tx.shared::cta.b64 _, [%0], %1;" ::"r"(a), "r"(b) : "memory"); }
__device__ __forceinline__ void mbar_arrive(uint32_t a) { asm volatile("mbarrier.arrive.shared::cta.b64 _, [%0];" ::"r"(a) : "memory"); }
__device__ __forceinline__ void mbar_wait(uint32_t a, int ph) {
  asm volatile(
      "{\n.reg .pred p;\n.reg .u32 n;\n"
      "mbarrier.try_wait.parity.shared::cta.b64 p, [%0], %1;\n@p bra LD;\nmov.u32 n, 0;\n"
      "LW:\nmbarrier.try_wait.parity.shared::cta.b64 p, [%0], %1, 20000;\n@p bra LD;\n"
      "add.u32 n, n, 1;\nsetp.lt.u32 p, n, 100000;\n@p bra LW;\ntrap;\nLD:\n}\n" ::"r"(a), "r"(ph) : "memory");
}
__device__ __forceinline__ void poll_cnt(const unsigned* p, unsigned target) {
  asm volatile(
      "{\n.reg .pred p;\n.reg .u32 n;\n.reg .s32 v;\nmov.u32 n, 0;\n"
      "LW:\nld.relaxed.gpu.global.u32 v, [%0];\nsub.s32 v, v, %1;\nsetp.ge.s32 p, v, 0;\n@p bra LD;\n"
      "add.u32 n, n, 1;\nsetp.lt.u32 p, n, 4000000;\n@p bra LW;\ntrap;\n"
      "LD:\nfence.acquire.gpu;\nfence.proxy.async.global;\n}\n" ::"l"(p), "r"(target) : "memory");
}
__device__ __forceinline__ void publish(unsigned* p) {
  asm volatile("fence.proxy.async.global;\nfence.release.gpu;\nred.relaxed.gpu.global.add.u32 [%0], 1;" ::"l"(p) : "memory");
}
__device__ __forceinline__ uint32_t movm(uint32_t v) { uint32_t r; asm volatile("movmatrix.sync.aligned.m8n8.trans.b16 %0, %1;" : "=r"(r) : "r"(v)); return r; }
__device__ __forceinline__ void fence_async_smem() { asm volatile("fence.proxy.async.shared::cta;" ::: "memory"); }
__device__ __forceinline__ bool elect1() { uint32_t p; asm volatile("{\n.reg .pred P;\nelect.sync _|P, 0xffffffff;\nselp.u32 %0,1,0,P;\n}\n" : "=r"(p)); return p; }
__device__ __forceinline__ void bar_sync(int id, int n) { asm volatile("bar.sync %0, %1;" ::"r"(id), "r"(n) : "memory"); }
__device__ __forceinline__ void bar_arrive(int id, int n) { asm volatile("bar.arrive %0, %1;" ::"r"(id), "r"(n) : "memory"); }
__device__ __forceinline__ void bulk_g2s(uint32_t dst, const void* src, int bytes, uint32_t mb) {
  asm volatile("cp.async.bulk.shared::cluster.global.mbarrier::complete_tx::bytes [%0], [%1], %2, [%3];" ::"r"(dst), "l"(src), "r"(bytes), "r"(mb) : "memory");
}
__device__ __forceinline__ void bulk_prefetch(const void* src, int bytes) { asm volatile("cp.async.bulk.prefetch.L2.global [%0], %1;" ::"l"(src), "r"(bytes) : "memory"); }
__device__ __forceinline__ void tma2d(uint32_t dst, const CUtensorMap* m, int c0, int c1, uint32_t mb) {
  asm volatile("cp.async.bulk.tensor.2d.shared::cluster.global.mbarrier::complete_tx::bytes [%0], [%1, {%3, %4}], [%2];" ::"r"(dst), "l"(m), "r"(mb), "r"(c0), "r"(c1) : "memory");
}
__device__ __forceinline__ void tma3d(uint32_t dst, const CUtensorMap* m, int c0, int c1, int c2, uint32_t mb) {
  asm volatile("cp.async.bulk.tensor.3d.shared::cluster.global.mbarrier::complete_tx::bytes [%0], [%1, {%3, %4, %5}], [%2];" ::"r"(dst), "l"(m), "r"(mb), "r"(c0), "r"(c1), "r"(c2) : "memory");
}
__device__ __forceinline__ int frag_col(int l) {
  const int tl = l >> 3, i = l & 7;
  return (tl < 8 ? 32 * (tl >> 2) + 8 * (i >> 1) + 2 * (tl & 3) : 48 + 4 * (i >> 1) + 2 * tl) + (i & 1);
}
__device__ __forceinline__ uint64_t dsc(uint32_t lo, uint32_t hi) { return ((uint64_t)hi << 32) | lo; }
__device__ __forceinline__ void wg_fence() { asm volatile("wgmma.fence.sync.aligned;" ::: "memory"); }
__device__ __forceinline__ void wg_commit() { asm volatile("wgmma.commit_group.sync.aligned;" ::: "memory"); }
template <int N> __device__ __forceinline__ void wg_wait() { asm volatile("wgmma.wait_group.sync.aligned %0;" ::"n"(N) : "memory"); }
__device__ __forceinline__ void wgmma_n192(float (&d)[96], uint64_t da, uint64_t db, int scale_d) {
  asm volatile("{\n.reg .pred p;\nsetp.ne.b32 p, %98, 0;\n"
    "wgmma.mma_async.sync.aligned.m64n192k16.f32.bf16.bf16 "
    "{"
    "%0, %1, %2, %3, %4, %5, %6, %7, %8, %9, %10, %11, %12, %13, %14, %15, "
    "%16, %17, %18, %19, %20, %21, %22, %23, %24, %25, %26, %27, %28, %29, %30, %31, "
    "%32, %33, %34, %35, %36, %37, %38, %39, %40, %41, %42, %43, %44, %45, %46, %47, "
    "%48, %49, %50, %51, %52, %53, %54, %55, %56, %57, %58, %59, %60, %61, %62, %63, "
    "%64, %65, %66, %67, %68, %69, %70, %71, %72, %73, %74, %75, %76, %77, %78, %79, "
    "%80, %81, %82, %83, %84, %85, %86, %87, %88, %89, %90, %91, %92, %93, %94, %95"
    "}, "
    "%96, %97, p, 1, 1, 0, 1;\n}\n"
    : "+f"(d[0]), "+f"(d[1]), "+f"(d[2]), "+f"(d[3]), "+f"(d[4]), "+f"(d[5]), "+f"(d[6]), "+f"(d[7]),
      "+f"(d[8]), "+f"(d[9]), "+f"(d[10]), "+f"(d[11]), "+f"(d[12]), "+f"(d[13]), "+f"(d[14]), "+f"(d[15]),
      "+f"(d[16]), "+f"(d[17]), "+f"(d[18]), "+f"(d[19]), "+f"(d[20]), "+f"(d[21]), "+f"(d[22]), "+f"(d[23]),
      "+f"(d[24]), "+f"(d[25]), "+f"(d[26]), "+f"(d[27]), "+f"(d[28]), "+f"(d[29]), "+f"(d[30]), "+f"(d[31]),
      "+f"(d[32]), "+f"(d[33]), "+f"(d[34]), "+f"(d[35]), "+f"(d[36]), "+f"(d[37]), "+f"(d[38]), "+f"(d[39]),
      "+f"(d[40]), "+f"(d[41]), "+f"(d[42]), "+f"(d[43]), "+f"(d[44]), "+f"(d[45]), "+f"(d[46]), "+f"(d[47]),
      "+f"(d[48]), "+f"(d[49]), "+f"(d[50]), "+f"(d[51]), "+f"(d[52]), "+f"(d[53]), "+f"(d[54]), "+f"(d[55]),
      "+f"(d[56]), "+f"(d[57]), "+f"(d[58]), "+f"(d[59]), "+f"(d[60]), "+f"(d[61]), "+f"(d[62]), "+f"(d[63]),
      "+f"(d[64]), "+f"(d[65]), "+f"(d[66]), "+f"(d[67]), "+f"(d[68]), "+f"(d[69]), "+f"(d[70]), "+f"(d[71]),
      "+f"(d[72]), "+f"(d[73]), "+f"(d[74]), "+f"(d[75]), "+f"(d[76]), "+f"(d[77]), "+f"(d[78]), "+f"(d[79]),
      "+f"(d[80]), "+f"(d[81]), "+f"(d[82]), "+f"(d[83]), "+f"(d[84]), "+f"(d[85]), "+f"(d[86]), "+f"(d[87]),
      "+f"(d[88]), "+f"(d[89]), "+f"(d[90]), "+f"(d[91]), "+f"(d[92]), "+f"(d[93]), "+f"(d[94]), "+f"(d[95])
    : "l"(da), "l"(db), "r"(scale_d));
}

__device__ __forceinline__ void wgmma_n80(float (&d)[40], uint64_t da, uint64_t db, int scale_d) {
  asm volatile("{\n.reg .pred p;\nsetp.ne.b32 p, %42, 0;\n"
    "wgmma.mma_async.sync.aligned.m64n80k16.f32.bf16.bf16 "
    "{"
    "%0, %1, %2, %3, %4, %5, %6, %7, %8, %9, %10, %11, %12, %13, %14, %15, "
    "%16, %17, %18, %19, %20, %21, %22, %23, %24, %25, %26, %27, %28, %29, %30, %31, "
    "%32, %33, %34, %35, %36, %37, %38, %39"
    "}, "
    "%40, %41, p, 1, 1, 0, 1;\n}\n"
    : "+f"(d[0]), "+f"(d[1]), "+f"(d[2]), "+f"(d[3]), "+f"(d[4]), "+f"(d[5]), "+f"(d[6]), "+f"(d[7]),
      "+f"(d[8]), "+f"(d[9]), "+f"(d[10]), "+f"(d[11]), "+f"(d[12]), "+f"(d[13]), "+f"(d[14]), "+f"(d[15]),
      "+f"(d[16]), "+f"(d[17]), "+f"(d[18]), "+f"(d[19]), "+f"(d[20]), "+f"(d[21]), "+f"(d[22]), "+f"(d[23]),
      "+f"(d[24]), "+f"(d[25]), "+f"(d[26]), "+f"(d[27]), "+f"(d[28]), "+f"(d[29]), "+f"(d[30]), "+f"(d[31]),
      "+f"(d[32]), "+f"(d[33]), "+f"(d[34]), "+f"(d[35]), "+f"(d[36]), "+f"(d[37]), "+f"(d[38]), "+f"(d[39])
    : "l"(da), "l"(db), "r"(scale_d));
}

__device__ __forceinline__ void hmma(float* c, uint32_t a0, uint32_t a1, uint32_t a2, uint32_t a3, uint32_t b0, uint32_t b1) {
  asm volatile("mma.sync.aligned.m16n8k16.row.col.f32.f16.f16.f32 {%0,%1,%2,%3}, {%4,%5,%6,%7}, {%8,%9}, {%0,%1,%2,%3};"
      : "+f"(c[0]), "+f"(c[1]), "+f"(c[2]), "+f"(c[3]) : "r"(a0), "r"(a1), "r"(a2), "r"(a3), "r"(b0), "r"(b1));
}
__device__ __forceinline__ void ldsm4(uint32_t* r, uint32_t a) { asm volatile("ldmatrix.sync.aligned.m8n8.x4.shared.b16 {%0,%1,%2,%3}, [%4];" : "=r"(r[0]), "=r"(r[1]), "=r"(r[2]), "=r"(r[3]) : "r"(a) : "memory"); }
__device__ __forceinline__ void ldsm4t(uint32_t* r, uint32_t a) { asm volatile("ldmatrix.sync.aligned.m8n8.x4.trans.shared.b16 {%0,%1,%2,%3}, [%4];" : "=r"(r[0]), "=r"(r[1]), "=r"(r[2]), "=r"(r[3]) : "r"(a) : "memory"); }
__device__ __forceinline__ void stsm4(uint32_t a, uint32_t r0, uint32_t r1, uint32_t r2, uint32_t r3) { asm volatile("stmatrix.sync.aligned.m8n8.x4.shared.b16 [%0], {%1,%2,%3,%4};" ::"r"(a), "r"(r0), "r"(r1), "r"(r2), "r"(r3) : "memory"); }
__device__ __forceinline__ void stsm4t(uint32_t a, uint32_t r0, uint32_t r1, uint32_t r2, uint32_t r3) { asm volatile("stmatrix.sync.aligned.m8n8.x4.trans.shared.b16 [%0], {%1,%2,%3,%4};" ::"r"(a), "r"(r0), "r"(r1), "r"(r2), "r"(r3) : "memory"); }
__device__ __forceinline__ uint32_t lds32(uint32_t a) { uint32_t v; asm volatile("ld.shared.u32 %0, [%1];" : "=r"(v) : "r"(a) : "memory"); return v; }
__device__ __forceinline__ uint2 lds64(uint32_t a) { uint2 v; asm volatile("ld.shared.v2.u32 {%0,%1}, [%2];" : "=r"(v.x), "=r"(v.y) : "r"(a) : "memory"); return v; }
__device__ __forceinline__ uint4 lds128(uint32_t a) { uint4 v; asm volatile("ld.shared.v4.u32 {%0,%1,%2,%3}, [%4];" : "=r"(v.x), "=r"(v.y), "=r"(v.z), "=r"(v.w) : "r"(a) : "memory"); return v; }
__device__ __forceinline__ void sts16(uint32_t a, uint32_t v) { asm volatile("st.shared.u16 [%0], %1;" ::"r"(a), "h"((unsigned short)v) : "memory"); }
__device__ __forceinline__ void sts32(uint32_t a, uint32_t v) { asm volatile("st.shared.u32 [%0], %1;" ::"r"(a), "r"(v) : "memory"); }
__device__ __forceinline__ void sts64(uint32_t a, uint32_t x, uint32_t y) { asm volatile("st.shared.v2.u32 [%0], {%1,%2};" ::"r"(a), "r"(x), "r"(y) : "memory"); }
__device__ __forceinline__ void sts128(uint32_t a, uint32_t x, uint32_t y, uint32_t z, uint32_t w) { asm volatile("st.shared.v4.u32 [%0], {%1,%2,%3,%4};" ::"r"(a), "r"(x), "r"(y), "r"(z), "r"(w) : "memory"); }
__device__ __forceinline__ float bflo(uint32_t v) { return __uint_as_float(v << 16); }
__device__ __forceinline__ float bfhi(uint32_t v) { return __uint_as_float(v & 0xffff0000u); }
__device__ __forceinline__ uint32_t pack_bf(float lo, float hi) { uint32_t r; asm("cvt.rn.bf16x2.f32 %0, %1, %2;" : "=r"(r) : "f"(hi), "f"(lo)); return r; }
__device__ __forceinline__ uint32_t pack_h(float lo, float hi) { uint32_t r; asm("cvt.rn.f16x2.f32 %0, %1, %2;" : "=r"(r) : "f"(hi), "f"(lo)); return r; }
__device__ __forceinline__ float rnd_bf(float v) { return __bfloat162float(__float2bfloat16_rn(v)); }
__device__ __forceinline__ float ex2a(float v) { float r; asm("ex2.approx.ftz.f32 %0, %1;" : "=f"(r) : "f"(v)); return r; }
__device__ __forceinline__ float tanha(float v) { float r; asm("tanh.approx.f32 %0, %1;" : "=f"(r) : "f"(v)); return r; }
__device__ __forceinline__ uint32_t hadd(uint32_t a, uint32_t b) { uint32_t r; asm("add.rn.f16x2 %0, %1, %2;" : "=r"(r) : "r"(a), "r"(b)); return r; }
__device__ __forceinline__ uint32_t badd(uint32_t a, uint32_t b) { uint32_t r; asm("add.rn.bf16x2 %0, %1, %2;" : "=r"(r) : "r"(a), "r"(b)); return r; }
__device__ __forceinline__ uint32_t bmul(uint32_t a, uint32_t b) { uint32_t r; asm("mul.rn.bf16x2 %0, %1, %2;" : "=r"(r) : "r"(a), "r"(b)); return r; }
__device__ __forceinline__ uint32_t bsub(uint32_t a, uint32_t b) { uint32_t r; asm("sub.rn.bf16x2 %0, %1, %2;" : "=r"(r) : "r"(a), "r"(b)); return r; }
__device__ __forceinline__ uint32_t dup(uint32_t v, uint32_t nz) { uint32_t r; asm volatile("add.rn.f32 %0, %1, %2;" : "=r"(r) : "r"(v), "r"(nz)); return r; }
__device__ __forceinline__ void bmma(float* c, uint32_t a0, uint32_t a1, uint32_t a2, uint32_t a3, uint32_t b0, uint32_t b1) {
  asm("mma.sync.aligned.m16n8k16.row.col.f32.bf16.bf16.f32 {%0,%1,%2,%3}, {%4,%5,%6,%7}, {%8,%9}, {%0,%1,%2,%3};"
      : "+f"(c[0]), "+f"(c[1]), "+f"(c[2]), "+f"(c[3]) : "r"(a0), "r"(a1), "r"(a2), "r"(a3), "r"(b0), "r"(b1));
}
__device__ __forceinline__ uint32_t odd_pair(uint32_t a, uint32_t b) { return __byte_perm(a, b, 0x5432); }
__device__ __forceinline__ int upos(int c) { return c ^ (c >> 5) ^ ((c >> 3) & 1); }
__device__ __forceinline__ int uoff(int pos) { return (pos >> 1) * 160 + (pos & 1) * 16; }

struct cf { float r, i; };
__device__ __forceinline__ cf cmul(cf a, cf b) { cf o; o.r = fmaf(a.r, b.r, -a.i * b.i); o.i = fmaf(a.r, b.i, a.i * b.r); return o; }
__device__ __forceinline__ cf csq(cf a) { cf o; o.r = fmaf(a.r, a.r, -a.i * a.i); o.i = (a.r + a.r) * a.i; return o; }
struct hp { uint32_t r, i; };
__device__ __forceinline__ hp hpack(cf a, cf b) { hp o; o.r = pack_h(a.r, b.r); o.i = pack_h(a.i, b.i); return o; }
__device__ __forceinline__ hp hmulc(hp a, uint32_t c) {
  __half2 ar = *reinterpret_cast<__half2*>(&a.r), ai = *reinterpret_cast<__half2*>(&a.i), cc = *reinterpret_cast<__half2*>(&c);
  __half2 orr = __hfma2(ar, __low2half2(cc), __hneg2(__hmul2(ai, __high2half2(cc))));
  __half2 oi = __hfma2(ar, __high2half2(cc), __hmul2(ai, __low2half2(cc)));
  hp o; o.r = *reinterpret_cast<uint32_t*>(&orr); o.i = *reinterpret_cast<uint32_t*>(&oi); return o;
}
__device__ __forceinline__ void sts_tile(uint32_t a, const hp* t) {
  sts128(a, t[0].r, t[1].r, t[2].r, t[3].r);
  sts128(a + 512, t[0].i, t[1].i, t[2].i, t[3].i);
}
template <int STEP> __device__ __forceinline__ void put2(uint32_t a0, uint32_t a1, uint32_t h, uint32_t sel) {
  const uint32_t x = __byte_perm(h, h, sel), y = x >> 16;
  sts16(a0, x); sts16(a0 + STEP * 4 + 2, x);
  sts16(a1, y); sts16(a1 + STEP * 4 + 2, y);
}

__device__ __forceinline__ void spare_work(const Params& p, const CUtensorMap* tmW1, int k, int tid) {
  const int lane = tid & 31;
  unsigned ep = 0;
  if (tid == 480) {
    ep = p.scr->epoch[128 + k] + 1;
    for (int i = 0; i < 8; i++) mbar_init(bar + 8 * i, i < 4 ? 1 : 12);
    asm volatile("fence.mbarrier_init.release.cluster;" ::: "memory");
    fence_async_smem();
  }
  __syncthreads();
  float a[2][4] = {{0.f, 0.f, 0.f, 0.f}, {0.f, 0.f, 0.f, 0.f}};
  if (tid >= 480) {
    if (elect1()) {
#pragma unroll 1
      for (int s = 0; s < 10; s++) {
        mbar_wait(bar + 8 * (4 + (s & 3)), ((s >> 2) & 1) ^ 1);
        mbar_expect(bar + 8 * (s & 3), 49152);
#pragma unroll 1
        for (int b = 0; b < 2; b++) tma3d(sb + (s & 3) * 49152 + b * 24576, tmW1, 0, s * 64, k * 6 + b * 3, bar + 8 * (s & 3));
      }
    }
    __syncwarp();
  } else if (tid < 384) {
    const uint32_t idn = (lane >> 3) == (lane & 3) ? ((lane & 4) ? 0x3f800000u : 0x3f80u) : 0u;
#pragma unroll 1
    for (int s = 0; s < 10; s++) {
      mbar_wait(bar + 8 * (s & 3), (s >> 2) & 1);
      const uint32_t ad = sb + (s & 3) * 49152 + (tid >> 6) * 8192 + (tid & 63) * 16;
#pragma unroll
      for (int i = 0; i < 8; i += 2) {
        const uint4 v = lds128(ad + i * 1024), w = lds128(ad + i * 1024 + 1024);
        bmma(a[0], v.x, v.y, w.x, w.y, idn, idn);
        bmma(a[1], v.z, v.w, w.z, w.w, idn, idn);
      }
      __syncwarp();
      if (lane == 0) mbar_arrive(bar + 8 * (4 + (s & 3)));
    }
    const int rho = (tid >> 3) & 7;
    const uint32_t ad = sb + 196608 + rho * 1536 + ((tid >> 6) * 8 + ((tid & 7) ^ rho)) * 32;
    sts128(ad, __float_as_uint(a[0][0]), __float_as_uint(a[0][1]), __float_as_uint(a[0][2]), __float_as_uint(a[0][3]));
    sts128(ad + 16, __float_as_uint(a[1][0]), __float_as_uint(a[1][1]), __float_as_uint(a[1][2]), __float_as_uint(a[1][3]));
  }
  __syncthreads();
  if (tid < 384) {
    float s = 0.f;
#pragma unroll
    for (int r = 0; r < 8; r++) s += __uint_as_float(lds32(sb + 196608 + r * 1536 + tid * 4));
    p.scr->cs[k * 384 + tid] = s;
  }
  __syncthreads();
  if (tid == 480) {
    publish(p.scr->cnt + C_CS * 32);
    p.scr->epoch[128 + k] = ep;
    poll_cnt(p.scr->cnt + C_LN * 32, ep * 128);
  }
}

__device__ __forceinline__ void load1(int s, const CUtensorMap* tmX, const CUtensorMap* tmW1, int rg1, int j1) {
  const uint32_t d = sb + (s & 3) * SLOT1, mb = bar + 8 * (B_FULL1 + (s & 3));
  mbar_expect(mb, SLOT1);
  tma2d(d, tmX, s * 64, rg1 * 128, mb);
  tma3d(d + 16384, tmW1, 0, s * 64, j1 * 3, mb);
}
template <int WG> __device__ __forceinline__ void gemm2_loop(float (&acc)[40]) {
#pragma unroll 1
  for (int o = 0; o < 24 / NS2; o++) {
#pragma unroll
    for (int s = 0; s < NS2; s++) {
      mbar_wait(bar + 8 * (B_FULL2 + s), o & 1);
      wg_fence();
#pragma unroll
      for (int kk = 0; kk < 4; kk++)
        wgmma_n80(acc, dsc(((sb + WG * 8192 + s * SLOT2 + kk * 256) >> 4) | (8 << 16), 64),
                  dsc(((sb + s * SLOT2 + 16384 + kk * 2560) >> 4) | (80 << 16), 8), (s | kk) ? 1 : o);
      wg_commit();
      wg_wait<1>();
      if ((s > 0 || o > 0) && elect1()) mbar_arrive(bar + 8 * (B_EMPTY2 + (s + NS2 - 1) % NS2));
    }
  }
}

__device__ __forceinline__ void load_x(uint32_t (&xv)[2][10], const __nv_bfloat16* xc, int rstep, int q) {
#pragma unroll
  for (int r = 0; r < 2; r++) {
    const uint4 a = __ldg((const uint4*)(xc + r * rstep) + q), b = __ldg((const uint4*)(xc + r * rstep) + 4 + q);
    const uint2 c = __ldg((const uint2*)(xc + r * rstep + 64) + q);
    xv[r][0] = a.x; xv[r][1] = a.y; xv[r][2] = a.z; xv[r][3] = a.w; xv[r][4] = b.x; xv[r][5] = b.y; xv[r][6] = b.z; xv[r][7] = b.w;
    xv[r][8] = c.x; xv[r][9] = c.y;
  }
}

template <bool USE_SMID>
__global__ void __launch_bounds__(512, 1)
fused_s4_ffn_kernel(const Params p, const __grid_constant__ CUtensorMap tmX, const __grid_constant__ CUtensorMap tmW1,
                    const __grid_constant__ CUtensorMap tmU) {
  extern __shared__ __align__(1024) unsigned char smem_raw[];
  const int tid = threadIdx.x, lane = tid & 31;
  const int warp = __shfl_sync(0xffffffffu, tid >> 5, 0);
  const int g = lane >> 2, q = lane & 3;
  uint32_t sid;
  if (USE_SMID) asm("mov.u32 %0, %smid;" : "=r"(sid)); else sid = blockIdx.x;
  if (sid - 120u < 4u) { spare_work(p, &tmW1, sid - 120, tid); return; }
  const int wid = sid < 120 ? sid : sid - 4;
  unsigned* const cnt = p.scr->cnt;

  float kacc[5][4];
  const int kch = warp % 5, kpart = warp / 5;
  float k0n = 0.f;
  uint32_t xv[2][10];
  const __nv_bfloat16* const xln = p.x + (wid * 16 + ((g >> 1) << 2) + (g & 1)) * DM + (warp - 8) * 80;
  int kex = 0;
  uint32_t pa[6] = {0, 0, 0, 0, 0, 0};
  uint32_t pld = 0, pds = 0;
  if (warp < 15) {
    const int ch = (wid >> 4) * 80 + frag_col((wid & 15) * 5 + kch);
    const int o = (ch * NMODE + kpart * 64) / 2 + lane;
    pa[0] = __ldg((const uint32_t*)p.are + o); pa[1] = __ldg((const uint32_t*)p.aim + o);
    pa[2] = __ldg((const uint32_t*)p.bre + o); pa[3] = __ldg((const uint32_t*)p.bim + o);
    pa[4] = __ldg((const uint32_t*)p.cre + o); pa[5] = __ldg((const uint32_t*)p.cim + o);
    pld = __ldg((const unsigned short*)p.logdt + ch);
    pds = __ldg((const unsigned short*)p.dskip + ch);
  }
  int gpc, qi;
  {
    int i;
    if (sid < 64) { gpc = (sid & 15) >> 1; i = sid >> 4; }
    else if (sid < 120) { const int t = sid - 64; i = t / 14; gpc = 1 + ((t - i * 14) >> 1); i += 4; }
    else { gpc = 0; i = 4 + ((sid - 124) >> 1); }
    qi = ((0x52741630 >> (4 * i)) & 7) * 2 + (sid & 1);
  }
  const int rg1 = 4 * (gpc >> 1) + (qi >> 2), j1 = 4 * (gpc & 1) + (qi & 3);
  const int rg2 = rg1, j2 = j1;
  {
    if (warp < 15) {
    } else {
      if (lane == 0) {
        unsigned ep = p.scr->epoch[wid];
        if ((uint32_t)__cvta_generic_to_shared(smem_raw) != sb) __trap();
        for (int i = 0; i < B_NUM; i++) {
          int c = 1;
          if ((i >= B_EMPTY1 && i < B_UFULL) || i == B_ZRDY || i >= B_EMPTY2) c = 8;
          if (i >= B_MMA && i < B_FULL2) c = 4;
          mbar_init(bar + 8 * i, c);
        }
        asm volatile("fence.mbarrier_init.release.cluster;" ::: "memory");
        fence_async_smem();
        p.scr->epoch[wid] = ep + 1;
        sts32(sb + OFF_EP, ep + 1);
      }
      sts64(sb + OFF_ZERO + (lane & 15) * 8 + (lane >> 4) * 640, 0, 0);
      __syncwarp();
      const uint4* xr = (const uint4*)(p.x + (wid * 16 + ((g >> 1) << 2) + (g & 1)) * DM) + q;
      uint32_t sh[2];
      float sm[2][4], g0[2][4], g1[2][4];
#pragma unroll
      for (int i = 0; i < 8; i++) sm[i >> 2][i & 3] = g0[i >> 2][i & 3] = g1[i >> 2][i & 3] = 0.f;
      if (elect1()) bulk_prefetch(p.x + wid * 16 * DM, 16 * DM * 2);
#pragma unroll 1
      for (int b = 0; b < 2; b++) {
        uint4 v[2][10];
#pragma unroll
        for (int i = 0; i < 10; i++) { v[0][i] = __ldg(xr + b * 40 + i * 4); v[1][i] = __ldg(xr + 160 + b * 40 + i * 4); }
        if (b == 0) {
          if (elect1()) {
#pragma unroll 1
            for (int s = 0; s < 4; s++) load1(s, &tmX, &tmW1, rg1, j1);
            bulk_prefetch(p.w1 + wid * 5 * FF, 5 * FF * 2);
            bulk_prefetch(p.w2 + wid * 12 * DM, 12 * DM * 2);
          }
#pragma unroll
          for (int r = 0; r < 2; r++) {
            const uint32_t w = __shfl_sync(0xffffffffu, v[r][0].x, lane & 28);
            sh[r] = fabsf(bflo(w) - bfhi(w)) * 8.f < fabsf(bflo(w)) ? __byte_perm(w, 0, 0x1010) : 0u;
          }
        }
#pragma unroll
        for (int i = 0; i < 10; i++)
#pragma unroll
          for (int e = 0; e < 2; e++) {
            const uint32_t x0 = (&v[0][i].x)[2 * e], x1 = (&v[1][i].x)[2 * e], x2 = (&v[0][i].x)[2 * e + 1], x3 = (&v[1][i].x)[2 * e + 1];
            const uint32_t a0 = bsub(x0, sh[0]), a1 = bsub(x1, sh[1]), a2 = bsub(x2, sh[0]), a3 = bsub(x3, sh[1]);
            bmma(sm[0], a0, a1, a2, a3, 0x3f803f80u, 0x3f803f80u);
            bmma(g0[e], a0, a1, a2, a3, x0, x2);
            bmma(g1[e], a0, a1, a2, a3, x1, x3);
          }
      }
      load_x(xv, xln, 2 * DM, q);
      if (q == (g >> 1)) {
#pragma unroll
        for (int r = 0; r < 2; r++) {
          const float md = sm[0][2 * r] * (1.f / DM), mean = bflo(sh[r]) + md;
          const float s2 = r ? ((g & 1) ? g1[0][3] + g1[1][3] : g1[0][2] + g1[1][2]) : ((g & 1) ? g0[0][1] + g0[1][1] : g0[0][0] + g0[1][0]);
          const float var = fmaxf(fmaf(-md, mean, s2 * (1.f / DM)), 0.f);
          const float m = rnd_bf(mean);
          const float ri = 1.f / rnd_bf(sqrtf(rnd_bf(rnd_bf(var) + 1e-5f)));
          p.scr->stats[wid * 16 + ((g >> 1) << 2) + (g & 1) + 2 * r] = make_float2(-m, 0.5f * ri);
          sts64(sb + OFF_STAT + g * 16 + r * 8, __float_as_uint(-m * ri), __float_as_uint(ri));
        }
      }
      __syncwarp();
    }
#pragma unroll
    for (int j = 0; j < 5; j++) { kacc[j][0] = kacc[j][1] = kacc[j][2] = kacc[j][3] = 0.f; }
    if (warp < 15) {
      const float dt = rnd_bf(expf(bflo(pld)));
      cf c0 = cmul(cf{bflo(pa[4]), bflo(pa[5])}, cf{bflo(pa[2]), bflo(pa[3])});
      cf c1 = cmul(cf{bfhi(pa[4]), bfhi(pa[5])}, cf{bfhi(pa[2]), bfhi(pa[3])});
      const float mx = fmaxf(fmaxf(fmaxf(fabsf(c0.r), fabsf(c0.i)), fmaxf(fabsf(c1.r), fabsf(c1.i))) * dt, fabsf(bflo(pds)) * (1.f / 256.f));
      const uint32_t mw = __reduce_max_sync(0xffffffffu, __float_as_uint(mx));
      float k0 = c0.r + c1.r;
#pragma unroll
      for (int o = 16; o; o >>= 1) k0 += __shfl_xor_sync(0xffffffffu, k0, o);
      if (lane == 0) sts64(sb + OFF_K0 + warp * 8, __float_as_uint(k0), mw);
      bar_sync(3 + kch, 96);
      const uint2 e0 = lds64(sb + OFF_K0 + kch * 8), e1 = lds64(sb + OFF_K0 + kch * 8 + 40), e2 = lds64(sb + OFF_K0 + kch * 8 + 80);
      kex = min(max((int)(max(max(e0.y, e1.y), e2.y) >> 23), 20), 240);
      const float s2 = __uint_as_float((259 - kex) << 23), sc = s2 * dt;
      k0n = fmaf(__uint_as_float(e0.x) + __uint_as_float(e1.x) + __uint_as_float(e2.x), sc, bflo(pds) * s2);
      const float dl2 = dt * 1.4426950408889634f;
      float zr = bflo(pa[0]) * dl2, th = bflo(pa[1]) * dt;
      cf c = cf{c0.r * sc, c0.i * sc};
      if (warp >= 8) load_x(xv, xln, 2 * DM, q);
      const uint32_t ks = sb + OFF_KS + warp * 4096;
      const uint32_t ka = ks + (lane >> 3) * 512 + (lane & 7) * 16;
      const uint32_t kb = ks + ((lane >> 3) & 1) * 512 + ((lane >> 4) * 8 + (lane & 7)) * 16;
#pragma unroll 1
      for (int it = 0; it < 2; it++) {
        float m = ex2a(zr);
        const cf w1 = cf{m * __cosf(th), m * __sinf(th)};
        m = ex2a(zr * 8.f);
        const cf w8 = cf{m * __cosf(th * 8.f), m * __sinf(th * 8.f)};
        const cf w16 = csq(w8), w32 = csq(w16), w64 = csq(w32), w128 = csq(w64), w256 = csq(w128), w512 = csq(w256), w1024 = csq(w512);
        hp lo[8];
        lo[0] = hpack(cf{1.f, 0.f}, cf{w8.r, -w8.i});
        lo[1] = hmulc(lo[0], pack_h(w16.r, -w16.i));
        { const uint32_t k = pack_h(w32.r, -w32.i); lo[2] = hmulc(lo[0], k); lo[3] = hmulc(lo[1], k); }
        { const uint32_t k = pack_h(w64.r, -w64.i);
#pragma unroll
          for (int i = 0; i < 4; i++) lo[4 + i] = hmulc(lo[i], k); }
        const uint32_t st = ks + lane * 16;
        sts128(st, lo[0].r, lo[1].r, lo[2].r, lo[3].r);
        sts128(st + 512, lo[4].r, lo[5].r, lo[6].r, lo[7].r);
        sts128(st + 1024, lo[0].i, lo[1].i, lo[2].i, lo[3].i);
        sts128(st + 1536, lo[4].i, lo[5].i, lo[6].i, lo[7].i);
        const cf t1 = cmul(c, w1), t2 = cmul(t1, w1), t3 = cmul(t2, w1), t4 = cmul(t3, w1);
        const cf t5 = cmul(t4, w1), t6 = cmul(t5, w1), t7 = cmul(t6, w1), t8 = cmul(c, w8);
        hp T0[4], T1[4], T2[4], T3[4], T4[4];
        T0[0] = hpack(t4, t8); T0[1] = hpack(t2, t6); T0[2] = hpack(t1, t5); T0[3] = hpack(t3, t7);
        const uint32_t k128 = pack_h(w128.r, w128.i), k256 = pack_h(w256.r, w256.i), k512 = pack_h(w512.r, w512.i);
#pragma unroll
        for (int i = 0; i < 4; i++) T1[i] = hmulc(T0[i], k128);
        sts_tile(st + 2048, T0);
        sts_tile(st + 3072, T1);
        __syncwarp();
        uint32_t af[4][4];
#pragma unroll
        for (int mg = 0; mg < 4; mg++) ldsm4t(af[mg], ka + mg * 128);
#pragma unroll
        for (int j = 0; j < 2; j++)
#pragma unroll
          for (int mg = 0; mg < 4; mg += 2) {
            uint32_t b[4];
            ldsm4t(b, kb + 2048 + j * 1024 + mg * 128);
            hmma(kacc[j], af[mg][0], af[mg][1], af[mg][2], af[mg][3], b[0], b[1]);
            hmma(kacc[j], af[mg + 1][0], af[mg + 1][1], af[mg + 1][2], af[mg + 1][3], b[2], b[3]);
          }
        T2[0] = hmulc(T0[0], k256); T2[1] = hmulc(T0[1], k256); T2[2] = hmulc(T1[0], k256); T2[3] = hmulc(T1[1], k256);
        T3[0] = hmulc(T0[0], k512); T3[1] = hmulc(T1[0], k512); T3[2] = hmulc(T2[0], k512); T3[3] = hmulc(T2[2], k512);
        { const cf u0 = cmul(t8, w1024), u1 = cmul(u0, w128);
          T4[0] = hpack(u0, u1); T4[1] = hmulc(T4[0], k256); T4[2] = hmulc(T4[0], k512); T4[3] = hmulc(T4[1], k512); }
        __syncwarp();
        sts_tile(st, T2);
        sts_tile(st + 1024, T3);
        sts_tile(st + 2048, T4);
        __syncwarp();
#pragma unroll
        for (int j = 0; j < 3; j++)
#pragma unroll
          for (int mg = 0; mg < 4; mg += 2) {
            uint32_t b[4];
            ldsm4t(b, kb + j * 1024 + mg * 128);
            hmma(kacc[2 + j], af[mg][0], af[mg][1], af[mg][2], af[mg][3], b[0], b[1]);
            hmma(kacc[2 + j], af[mg + 1][0], af[mg + 1][1], af[mg + 1][2], af[mg + 1][3], b[2], b[3]);
          }
        __syncwarp();
        zr = bfhi(pa[0]) * dl2; th = bfhi(pa[1]) * dt;
        c = cf{c1.r * sc, c1.i * sc};
      }
#pragma unroll
      for (int j = 0; j < 5; j++) {
        if (warp < 10) sts128(ks + j * 512 + lane * 16, __float_as_uint(kacc[j][0]), __float_as_uint(kacc[j][1]), __float_as_uint(kacc[j][2]), __float_as_uint(kacc[j][3]));
      }
    }
  }
  __syncthreads();
  const unsigned ep = lds32(sb + OFF_EP);

  if (warp < 8) {
    float acc[96];
    const uint32_t alo = ((sb >> 4) | (1 << 16)) + (warp >> 2) * 512;
#pragma unroll 1
    for (int s = 0; s < 10; s++) {
      const uint32_t so = (s & 3) * (SLOT1 >> 4);
      mbar_wait(bar + 8 * (B_FULL1 + (s & 3)), (s >> 2) & 1);
      wg_fence();
#pragma unroll
      for (int kk = 0; kk < 4; kk++)
        wgmma_n192(acc, dsc(alo + so + kk * 2, 0x40000040u), dsc((((sb + 16384) >> 4) | (512 << 16)) + so + kk * 128, 0x40000040u), (s | kk) != 0);
      wg_commit();
      if (s > 0) {
        wg_wait<1>();
        const int sp = s - 1;
        if (elect1()) mbar_arrive(bar + 8 * (sp < 6 ? B_EMPTY1 + (sp & 3) : B_DRAIN + sp - 6));
      }
    }
    wg_wait<0>();
    if (lane == 0) mbar_arrive(bar + 8 * (B_DRAIN + 3));
    mbar_wait(bar + 8 * B_EPI, 0);
    const uint2 s0 = lds64(sb + OFF_STAT + (warp * 16 + g) * 8), s1 = lds64(sb + OFF_STAT + (warp * 16 + g + 8) * 8);
    const float nm0 = __uint_as_float(s0.x), r0 = __uint_as_float(s0.y), nm1 = __uint_as_float(s1.x), r1 = __uint_as_float(s1.y);
    uint4* hd = p.scr->h + (rg1 * 24 + j1) * 1024 + warp * 128 + q * 8 + g;
#pragma unroll
    for (int grp = 0; grp < 6; grp++) {
      uint32_t o0[4], o1[4];
#pragma unroll
      for (int tl = 0; tl < 4; tl++) {
        const int nt = grp * 4 + tl;
        const uint2 cs = lds64(sb + OFF_CS + (nt * 8 + 2 * q) * 4);
        const float ca = __uint_as_float(cs.x), cb = __uint_as_float(cs.y);
        const float a = fmaf(nm0, ca, acc[4 * nt]) * r0, b = fmaf(nm0, cb, acc[4 * nt + 1]) * r0;
        const float c = fmaf(nm1, ca, acc[4 * nt + 2]) * r1, d = fmaf(nm1, cb, acc[4 * nt + 3]) * r1;
        o0[tl] = pack_bf(fmaf(a, tanha(a), a), fmaf(b, tanha(b), b));
        o1[tl] = pack_bf(fmaf(c, tanha(c), c), fmaf(d, tanha(d), d));
      }
      uint4* dst = hd + (grp >> 1) * 8192 + (grp & 1) * 32;
      dst[0] = make_uint4(o0[0], o0[1], o0[2], o0[3]);
      dst[64] = make_uint4(o1[0], o1[1], o1[2], o1[3]);
      if (grp == 1) {
        if (warp == 7) {
          bar_sync(2, 256);
          mbar_wait(bar + 8 * B_ZRDY, 0);
          if (lane == 0) publish(cnt + C_H0 * 32);
          __syncwarp();
        }
        else bar_arrive(2, 256);
      }
    }
    if (warp == 6) { bar_sync(11, 256); if (lane == 0) publish(cnt + (C_H1 + rg1) * 32); __syncwarp(); }
    else bar_arrive(11, 256);
    if (warp == 4) {
      const uint4* srcA = p.scr->h + rg2 * 24 * 1024;
      const uint4* srcB = p.scr->w2p + j2 * 24 * 640;
      mbar_wait(bar + 8 * (B_DRAIN + 3), 0);
      if (elect1()) {
        poll_cnt(cnt + C_H0 * 32, ep * 128);
#pragma unroll 1
        for (int s = 0; s < NS2 - 1; s++) {
          if (s >= 3) mbar_wait(bar + 8 * (B_FREE + s - 3), 0);
          mbar_expect(bar + 8 * (B_FULL2 + s), SLOT2);
          bulk_g2s(sb + s * SLOT2, srcA + s * 1024, 16384, bar + 8 * (B_FULL2 + s));
          bulk_g2s(sb + s * SLOT2 + 16384, srcB + s * 640, 10240, bar + 8 * (B_FULL2 + s));
        }
        poll_cnt(cnt + (C_H1 + rg2) * 32, ep * 8);
      }
      __syncwarp();
    }
  } else {
    const int cw = warp - 8;
    {
      const uint4 st = lds128(sb + OFF_STAT + g * 16);
      const float n0 = __uint_as_float(st.x), r0 = __uint_as_float(st.y), n1 = __uint_as_float(st.z), r1 = __uint_as_float(st.w);
      const int up = upos(2 * wid);
      uint2* dst = (uint2*)p.scr->uT + ((up >> 1) * DM + cw * 80) * 4 + (lane ^ ((up & 1) << 1));
#pragma unroll
      for (int i = 0; i < 10; i++) {
        const uint32_t a = movm(pack_h(fmaf(bflo(xv[0][i]), r0, n0), fmaf(bfhi(xv[0][i]), r0, n0)));
        const uint32_t b = movm(pack_h(fmaf(bflo(xv[1][i]), r1, n1), fmaf(bfhi(xv[1][i]), r1, n1)));
        dst[i * 32] = make_uint2(a, b);
      }
    }
    if (warp == 9) {
      bar_sync(12, 256);
      if (elect1()) {
        publish(cnt + C_LN * 32);
        poll_cnt(cnt + C_CS * 32, ep * 4);
        bulk_g2s(sb + OFF_CS, p.scr->cs + j1 * 192, 768, bar + 8 * B_EPI);
      }
      __syncwarp();
    } else bar_arrive(12, 256);
    if (warp == 15) {
      if (elect1()) {
#pragma unroll 1
        for (int s = 4; s < 10; s++) {
          mbar_wait(bar + 8 * (B_EMPTY1 + (s & 3)), ((s >> 2) & 1) ^ 1);
          load1(s, &tmX, &tmW1, rg1, j1);
        }
      }
      __syncwarp();
    }
    if (warp >= 10 && warp < 15) {
      const uint32_t pb = sb + OFF_P + kch * 3072;
#pragma unroll
      for (int i = 0; i < 6; i++) sts128(pb + i * 512 + lane * 16, 0, 0, 0, 0);
      uint32_t h[5][2];
#pragma unroll
      for (int j = 0; j < 5; j++) {
        const uint4 a = lds128(sb + OFF_KS + kch * 4096 + j * 512 + lane * 16), b = lds128(sb + OFF_KS + (kch + 5) * 4096 + j * 512 + lane * 16);
#pragma unroll
        for (int e = 0; e < 4; e++) kacc[j][e] += __uint_as_float((&a.x)[e]) + __uint_as_float((&b.x)[e]);
        if (j == 1) {
          const float k256 = __shfl_sync(0xffffffffu, kacc[1][3], 28);
          if (lane == 31) kacc[1][3] -= k256;
        }
        if (j == 2 || j == 3) { h[j][0] = pack_h(kacc[j][0], kacc[j][2]); h[j][1] = pack_h(kacc[j][1], kacc[j][3]); }
        else { h[j][0] = pack_h(kacc[j][0], kacc[j][1]); h[j][1] = pack_h(kacc[j][2], kacc[j][3]); }
      }
      __syncwarp();
      {
        const int sw = g >> 2;
        const uint32_t sel = sw ? 0x1032 : 0x3210;
        const uint32_t a = pb + (P0 + 8 * g + ((0x3124 >> (4 * q)) & 7)) * 4, a0 = a + sw * 16, a1 = a + 16 - sw * 16;
        put2<1>(a0, a1, h[0][0], sel);
        put2<1>(a0 + 256, a1 + 256, h[0][1], sel);
        put2<1>(a0 + 512, a1 + 512, h[1][0], sel);
        put2<1>(lane == 28 ? pb + PB1 * 4 : a0 + 768, a1 + 768, h[1][1], sel);
      }
      {
        const int sw = q >> 1;
        const uint32_t sel = sw ? 0x1032 : 0x3210;
        uint32_t a = pb + (((q & 1) ? PA1 : PB1 + 1) + 32 * sw + 2 * g) * 4;
        put2<1>(a + sw * 64, a + 64 - sw * 64, h[2][0], sel);
        put2<1>(a + 4 + sw * 64, a + 68 - sw * 64, h[2][1], sel);
        a = pb + (PA2 + g + 16 * q) * 4;
        put2<2>(a + sw * 32, a + 32 - sw * 32, h[3][0], sel);
        put2<2>(a + (PB2 - PA2) * 4 + sw * 32, a + (PB2 - PA2) * 4 + 32 - sw * 32, h[3][1], sel);
        a = pb + (((g & 1) ? PB3 : PA3) + (g >> 1) + 16 * q) * 4;
        const uint32_t hx = sw ? h[4][1] : h[4][0], hy = sw ? h[4][0] : h[4][1];
        put2<1>(a + sw * 16, a + 32 + sw * 16, hx, 0x3210);
        put2<1>(a + 16 - sw * 16, a + 48 - sw * 16, hy, 0x3210);
      }
      if (lane == 30) put2<1>(pb + P0 * 4, pb + (PA1 + 64) * 4, pack_h(k0n, kacc[2][3]), 0x3210);
      if (lane == 31) sts64(sb + OFF_CHC + kch * 8, (kex - 5) * 0x00800080u, __byte_perm(h[3][1], 0, 0x3232));
      fence_async_smem();
    }
    if (warp == 8 && lane == 0) poll_cnt(cnt + C_LN * 32, ep * 128);
    if (warp < 15) bar_sync(1, 224);
    if (warp == 8) {
      if (elect1()) {
        mbar_expect(bar + 8 * B_UFULL, 20480);
        tma2d(sb + OFF_U, &tmU, wid * 80, 0, bar + 8 * B_UFULL);
        mbar_expect(bar + 8 * B_EPI, 1024 + 768);
        bulk_g2s(sb + OFF_STAT, p.scr->stats + rg1 * 128, 1024, bar + 8 * B_EPI);
      }
      __syncwarp();
    }
    uint4 wv[4];
    const int ct = tid - 256, uu = ct / 80, ur = ct - uu * 80;
    const int U = 3 * wid + uu, kp = ur < 64 ? (ur & 31) : (ur - 64);
    if (ct < 240) {
      const int fl = 8 * ((kp & 7) >> 1) + 2 * (kp >> 3) + (kp & 1), st = U >> 4;
      const int o0 = ur < 64 ? (ur >> 5) * 4 : 8, o2 = ur < 64 ? o0 + 2 : 4 * 80 + 8;
      const uint4* src = (const uint4*)(p.w2 + ((st & 7) * 192 + (st >> 3) * 64 + ((U >> 3) & 1) * 32 + fl) * DM + (U & 7) * 80);
      wv[0] = __ldg(src + o0); wv[1] = __ldg(src + o0 + 1); wv[2] = __ldg(src + o2); wv[3] = __ldg(src + o2 + 1);
    }
    if (ct < 240) {
      uint32_t w2w[16];
#pragma unroll
      for (int i = 0; i < 16; i++) w2w[i] = bmul((&wv[i >> 2].x)[i & 3], 0x3f003f00u);
      uint4* dst = p.scr->w2p + ((U & 7) * 24 + (U >> 4)) * 640 + (((U >> 3) & 1) * 4 + (kp >> 3)) * 80 + (kp & 7);
      if (ur < 64) {
        dst += (ur >> 5) * 32;
#pragma unroll
        for (int i = 0; i < 4; i++) dst[8 * i] = make_uint4(w2w[i], w2w[4 + i], w2w[8 + i], w2w[12 + i]);
      } else {
        dst[64] = make_uint4(w2w[0], w2w[2], w2w[4], w2w[6]);
        dst[72] = make_uint4(w2w[1], w2w[3], w2w[5], w2w[7]);
        dst[160 + 64] = make_uint4(w2w[8], w2w[10], w2w[12], w2w[14]);
        dst[160 + 72] = make_uint4(w2w[9], w2w[11], w2w[13], w2w[15]);
      }
    }
    mbar_wait(bar + 8 * B_UFULL, 0);
    mbar_wait(bar + 8 * (B_DRAIN + 1), 0);
#pragma unroll 1
    for (int task = cw; task < 24; task += 8) {
      if (task >= 16 && task < 20) break;
      const int ch = min(task >> 2, 4), qt = (task + (task >> 2)) & 3, j = qt * 32 + lane;
      const uint32_t ub = sb + OFF_U + ch * 32, zb = sb + OFF_Z + ch * ZSZ;
      uint32_t w_[20], o_[20], d_[20], b3_[20];
      uint32_t *w = w_ + 8, *o = o_ + 8, *d = d_ + 8, *b3 = b3_ + 8;
      {
        const uint32_t am = j > 0 ? ub + uoff(upos(2 * j - 2)) : sb + OFF_ZERO, a0 = ub + uoff(upos(2 * j));
        const uint2 a = lds64(am + 8);
        const uint4 b = lds128(am ^ 16), c = lds128(a0), e = lds128(a0 ^ 16);
        w[8] = lds32(ub + uoff(upos((2 * j + 2) & 255)));
        w[-6] = a.x; w[-5] = a.y; w[-4] = b.x; w[-3] = b.y; w[-2] = b.z; w[-1] = b.w;
        w[0] = c.x; w[1] = c.y; w[2] = c.z; w[3] = c.w; w[4] = e.x; w[5] = e.y; w[6] = e.z; w[7] = e.w;
      }
#pragma unroll
      for (int i = -1; i <= 7; i++) o[i] = odd_pair(w[i], w[i + 1]);
#pragma unroll
      for (int i = 0; i <= 7; i++) { d[i] = hadd(w[i], o[i]); b3[i] = hadd(d[i], o[i - 1]); }
      if (j < 112) {
        const int gr = j >> 1;
        const uint32_t a1 = zb + ZA1 + 128 + (gr ^ ((gr >> 2) & 1)) * 64 + ((gr >> 1) & 3) * 16 + (j & 1) * 8;
#pragma unroll
        for (int pp = 0; pp < 4; pp++) {
          const uint32_t sel = (pp & 1) ? 0x7632 : 0x5410;
          const int k = pp >> 1;
          sts64(a1 ^ (pp * 16), __byte_perm(w[k - 1], w[k + 1], sel), __byte_perm(w[k + 3], w[k + 5], sel));
          sts64((a1 ^ (pp * 16)) + (ZB1 - ZA1), __byte_perm(b3[k], b3[k + 2], sel), __byte_perm(b3[k + 4], b3[k + 6], sel));
        }
      } else if (j >= 120) {
        sts128(zb + ZA1 + ((lane >> 2) & 1) * (ZB1 - ZA1) + (3 - q) * 16, 0, 0, 0, j == 127 ? w[8] << 16 : 0u);
      }
      if (qt < 3) {
        uint32_t e_[20], b5_[20];
        uint32_t *e = e_ + 8, *b5 = b5_ + 8;
#pragma unroll
        for (int i = -6; i <= -2; i++) o[i] = odd_pair(w[i], w[i + 1]);
#pragma unroll
        for (int i = -6; i <= -1; i++) d[i] = hadd(w[i], o[i]);
#pragma unroll
        for (int i = -5; i <= -1; i++) b3[i] = hadd(d[i], o[i - 1]);
#pragma unroll
        for (int i = -5; i <= 4; i++) e[i] = hadd(d[i - 1], d[i]);
#pragma unroll
        for (int i = -4; i <= 4; i++) b5[i] = hadd(e[i], w[i + 1]);
        const uint32_t a2 = zb + ((j >> 3) * 16 + (j & 7)) * 16;
        sts128(a2 + ZA2, b3[-2], b3[-1], b3[0], b3[1]);
        sts128(a2 + ZA2 + 128, b3[2], b3[3], b3[4], b3[5]);
        sts128(a2 + ZB2, b5[-4], b5[-3], b5[-2], b5[-1]);
        sts128(a2 + ZB2 + 128, b5[0], b5[1], b5[2], b5[3]);
        if (qt < 2) {
          sts128(a2 + ZS, d[-2], d[-1], d[0], d[1]);
          sts128(a2 + ZS + 128, d[2], d[3], d[4], d[5]);
          uint32_t b7[8], b9[8];
#pragma unroll
          for (int i = -4; i <= 3; i++) { b7[i + 4] = hadd(b3[i - 1], e[i + 1]); b9[i + 4] = hadd(e[i - 1], b5[i + 1]); }
          const uint32_t a3 = zb + ((j >> 4) * 32 + (j & 15)) * 16;
          sts128(a3 + ZA3, b7[0], b7[1], b7[2], b7[3]);
          sts128(a3 + ZA3 + 256, b7[4], b7[5], b7[6], b7[7]);
          sts128(a3 + ZB3 + 256, b9[0], b9[1], b9[2], b9[3]);
          if (j < 63) sts128(a3 + ZB3 + ((j & 15) == 15 ? 272 : 16), b9[4], b9[5], b9[6], b9[7]);
          else sts128(zb + ZB3, 0, 0, 0, 0);
        }
      }
    }
    __syncwarp();
    if (lane == 0) mbar_arrive(bar + 8 * B_ZRDY);
  }

  if ((warp >> 2) != 1) {
    const int wg = warp >> 2, role = warp & 3;
    mbar_wait(bar + 8 * B_ZRDY, 0);
    mbar_wait(bar + 8 * (B_DRAIN + 3), 0);
    const uint32_t nz = lds32(sb + OFF_ZERO) | 0x80000000u;
#pragma unroll 1
    for (int ch = (wg == 0 ? 2 : wg - 2); ch < 5; ch += 3) {
      const uint32_t ub = sb + OFF_U + ch * 32, zb = sb + OFF_Z + ch * ZSZ, pb = sb + OFF_P + ch * 3072;
      const uint2 chc = lds64(sb + OFF_CHC + ch * 8);
      const uint32_t pa = pb + (g - 2 * q) * 4;
      if (role < 2) {
        float acc[8][4];
#pragma unroll
        for (int r = 0; r < 8; r++) { acc[r][0] = acc[r][1] = acc[r][2] = acc[r][3] = 0.f; }
        float fix = 0.f;
        if (role == 1 && lane == 28) {
          const uint32_t k = lds32(pb + PB1 * 4), u0 = lds32(ub);
          fix = __low2float(*reinterpret_cast<const __half2*>(&k)) * __low2float(*reinterpret_cast<const __half2*>(&u0));
        }
        uint32_t ga[3][2];
#pragma unroll
        for (int gm = 0; gm < 3; gm++) {
          const int hb = 2 * (lane & 7) + role - 2 + gm, l3 = ((lane >> 3) ^ (hb >> 1)) & 7;
          ga[gm][0] = hb < 0 ? sb + OFF_ZERO + ((l3 * 16 + ch * 32) & 127) : ub + hb * 1280 + uoff(l3);
          ga[gm][1] = hb < 0 ? ga[gm][0] ^ 64 : ub + hb * 1280 + uoff(l3 ^ 4);
        }
        uint32_t b[12][4], A[17][4];
#pragma unroll
        for (int i = 11; i >= 8; i--) ldsm4(b[i], (ga[2][i & 1] ^ (((i >> 1) & 1) * 16)) + ((i >> 1) & 1) * 640);
        A[0][0] = lds32(pa + P0 * 4); A[0][1] = lds32(pa + P0 * 4 + 32); A[0][2] = dup(0, nz);
#pragma unroll
        for (int m = 0; m <= 16; m++) {
          if (m < 16) {
            A[m + 1][0] = lds32(pa + P0 * 4 + (2 * m + 2) * 32);
            A[m + 1][1] = m < 15 ? lds32(pa + P0 * 4 + (2 * m + 3) * 32) : dup(0, nz);
          }
          if ((m & 1) == 0 && m < 16) {
            const int i = 7 - (m >> 1);
            ldsm4(b[i], (ga[i >> 2][i & 1] ^ (((i >> 1) & 1) * 16)) + ((i >> 1) & 1) * 640);
          }
          A[m][3] = dup(A[m][0], nz);
          if (m < 16) A[m + 1][2] = dup(A[m][1], nz);
#pragma unroll
          for (int r = 7; r >= 0; r--) {
            const int f = 16 + r - m;
            hmma(acc[r], A[m][0], A[m][1], A[m][2], A[m][3], b[f >> 1][(f & 1) * 2], b[f >> 1][(f & 1) * 2 + 1]);
          }
        }
        acc[7][2] += fix;
        bar_sync(7 + wg, 64);
#pragma unroll
        for (int i = 3; i >= 0; i--)
          stsm4t((ga[2][i & 1] ^ (((i >> 1) & 1) * 16)) + ((i >> 1) & 1) * 640, pack_bf(acc[2 * i][0], acc[2 * i][1]), pack_bf(acc[2 * i][2], acc[2 * i][3]),
                 pack_bf(acc[2 * i + 1][0], acc[2 * i + 1][1]), pack_bf(acc[2 * i + 1][2], acc[2 * i + 1][3]));
      } else if (role == 2) {
        float acc[14][4];
#pragma unroll
        for (int r = 0; r < 14; r++) { acc[r][0] = acc[r][1] = acc[r][2] = acc[r][3] = 0.f; }
        const int mi = lane >> 3, hf = (lane >> 2) & 1;
        const uint32_t ze = zb + ZA1 + 128 - 512 + hf * 1792 + (mi ^ hf) * 64 + ((q ^ (mi >> 1) ^ (hf * 2)) << 4);
        const uint32_t zo = ze ^ 96;
#pragma unroll
        for (int arr = 0; arr < 2; arr++) {
          uint32_t A[5][4];
#pragma unroll
          for (int m = 0; m < 5; m++) {
            A[m][0] = lds32(pa + (arr ? PB1 : PA1) * 4 + m * 64);
            A[m][1] = m < 4 ? lds32(pa + (arr ? PB1 : PA1) * 4 + m * 64 + 32) : dup(0, nz);
          }
#pragma unroll
          for (int m = 4; m >= 0; m--) { A[m][2] = dup(m ? A[m - 1][1] : 0, nz); A[m][3] = dup(A[m][0], nz); }
#pragma unroll
          for (int ip = 0; ip < 9; ip++) {
            uint32_t b[4];
            uint32_t ad = ((ip & 1) ? zo : ze) + ip * 256 + arr * (ZB1 - ZA1);
            if (ip < 2 && hf == 0 && (ip == 0 || mi != 3)) ad = sb + OFF_ZERO + (ad & 127);
            ldsm4(b, ad);
#pragma unroll
            for (int hh = 0; hh < 2; hh++)
#pragma unroll
              for (int m = 0; m < 5; m++) {
                const int i = 2 * ip + hh - 4 + m;
                if (i >= 0 && i < 14) hmma(acc[i], A[m][0], A[m][1], A[m][2], A[m][3], b[2 * hh], b[2 * hh + 1]);
              }
          }
        }
        const uint32_t a = zb + ZA1 + (q >> 1) * (14 * 128 + 64) + (2 * g + (q & 1)) * 4;
#pragma unroll
        for (int r = 0; r < 14; r++) { sts32(a + r * 128, pack_bf(acc[r][0], acc[r][1])); sts32(a + r * 128 + 64, pack_bf(acc[r][2], acc[r][3])); }
      } else {
        float acc[12][4];
        const uint32_t za = zb + lane * 16;
        {
          float d[4][2][4];
#pragma unroll
          for (int r = 0; r < 8; r++) { d[r >> 1][r & 1][0] = d[r >> 1][r & 1][1] = d[r >> 1][r & 1][2] = d[r >> 1][r & 1][3] = 0.f; }
#pragma unroll
          for (int arr = 0; arr < 2; arr++) {
            uint32_t A[4][4];
#pragma unroll
            for (int m = 0; m < 4; m++) { A[m][0] = lds32(pa + (arr ? PB3 : PA3) * 4 + m * 64); A[m][1] = lds32(pa + (arr ? PB3 : PA3) * 4 + m * 64 + 32); }
#pragma unroll
            for (int m = 0; m < 4; m++) { A[m][2] = dup(m ? A[m - 1][1] : 0, nz); A[m][3] = dup(A[m][0], nz); }
#pragma unroll
            for (int io = 0; io < 4; io++) {
              uint32_t b[4];
              ldsm4t(b, za + (arr ? ZB3 : ZA3) + io * 512);
#pragma unroll
              for (int m = 0; m + io < 4; m++) {
                hmma(d[io + m][0], A[m][0], A[m][1], A[m][2], A[m][3], b[0], b[1]);
                hmma(d[io + m][1], A[m][0], A[m][1], A[m][2], A[m][3], b[2], b[3]);
              }
            }
          }
#pragma unroll
          for (int r = 0; r < 4; r++) {
            acc[r][0] = acc[r][1] = acc[r][2] = acc[r][3] = 0.f;
            acc[4 + 2 * r][0] = d[r][0][0]; acc[4 + 2 * r][1] = d[r][0][1]; acc[4 + 2 * r][2] = d[r][1][0]; acc[4 + 2 * r][3] = d[r][1][1];
            acc[5 + 2 * r][0] = d[r][0][2]; acc[5 + 2 * r][1] = d[r][0][3]; acc[5 + 2 * r][2] = d[r][1][2]; acc[5 + 2 * r][3] = d[r][1][3];
          }
        }
        {
          const uint32_t k0 = (g >> 1) == q ? (chc.y & ((g & 1) ? 0xffff0000u : 0xffffu)) : 0u;
          const uint32_t k1 = dup(0, nz), k2 = dup(0, nz), k3 = dup(k0, nz);
#pragma unroll
          for (int ip = 0; ip < 4; ip++) {
            uint32_t b[4];
            ldsm4t(b, za + ZS + ip * 512);
            hmma(acc[4 + 2 * ip], k0, k1, k2, k3, b[0], b[1]);
            hmma(acc[5 + 2 * ip], k0, k1, k2, k3, b[2], b[3]);
          }
        }
        const uint32_t pa2 = pb + (2 * g - 4 * q) * 4;
#pragma unroll
        for (int arr = 0; arr < 2; arr++) {
          uint32_t A[5][4];
#pragma unroll
          for (int m = 0; m < 5; m++) {
            const uint2 v = lds64(pa2 + (arr ? PB2 : PA2) * 4 + m * 64);
            A[m][0] = v.x; A[m][1] = v.y; A[m][2] = lds32(pa2 + (arr ? PB2 : PA2) * 4 + m * 64 - 4);
          }
#pragma unroll
          for (int m = 0; m < 5; m++) A[m][3] = dup(A[m][0], nz);
#pragma unroll
          for (int ip = 0; ip < 6; ip++) {
            uint32_t b[4];
            ldsm4t(b, za + (arr ? ZB2 : ZA2) + ip * 512);
#pragma unroll
            for (int hh = 0; hh < 2; hh++)
#pragma unroll
              for (int m = 0; m < 5; m++) {
                const int i = 2 * ip + hh + m;
                if (i < 12) hmma(acc[i], A[m][0], A[m][1], A[m][2], A[m][3], b[2 * hh], b[2 * hh + 1]);
              }
          }
        }
        const uint32_t a = zb + ZA2 + ((lane ^ ((lane >> 1) & 4)) << 4);
#pragma unroll
        for (int i = 0; i < 6; i++)
          stsm4(a + i * 512, pack_bf(acc[2 * i][0], acc[2 * i][1]), pack_bf(acc[2 * i][2], acc[2 * i][3]),
                pack_bf(acc[2 * i + 1][0], acc[2 * i + 1][1]), pack_bf(acc[2 * i + 1][2], acc[2 * i + 1][3]));
        fence_async_smem();
      }
      bar_sync(3 + wg, 128);
      if (lane == 0) mbar_arrive(bar + 8 * (B_MMA + ch));
      {
        const int row = (wid & 15) * 5 + ch;
        const int c = tid & 127;
        const uint32_t a0 = ub + uoff(upos(c)), a1 = zb + ZA1 + (c - 32) * 16;
        const uint32_t a2 = zb + ZA2 + ((c & ~15) - 64 + ((((c >> 1) & 7) + (c & 1) * 8) ^ ((c & 1) * 4))) * 16;
        uint4 v = lds128(a0), u = lds128(ub + uoff(upos(c) ^ 4) + 64 * 160);
        const uint4 u1 = lds128(a1 + 2048 + (c >= 16 ? 64 : 0)), u2 = lds128(a2 + 2048);
        if (role >= 1) { const uint4 y = lds128(a1); v.x = badd(v.x, y.x); v.y = badd(v.y, y.y); v.z = badd(v.z, y.z); v.w = badd(v.w, y.w); }
        if (role >= 2) { const uint4 y = lds128(a2); v.x = badd(v.x, y.x); v.y = badd(v.y, y.y); v.z = badd(v.z, y.z); v.w = badd(v.w, y.w); }
        uint4* dst = p.scr->sT + (((wid >> 4) * 16 + (c >> 4)) * 80 + row) * 16 + ((c & 15) ^ (row & 7));
        u = make_uint4(bmul(badd(badd(u1.x, u2.x), u.x), chc.x), bmul(badd(badd(u1.y, u2.y), u.y), chc.x),
                       bmul(badd(badd(u1.z, u2.z), u.z), chc.x), bmul(badd(badd(u1.w, u2.w), u.w), chc.x));
        fence_async_smem();
        dst[0] = make_uint4(bmul(v.x, chc.x), bmul(v.y, chc.x), bmul(v.z, chc.x), bmul(v.w, chc.x));
        dst[8 * 1280] = u;
      }
      __syncwarp();
      if (lane == 0) mbar_arrive(bar + 8 * (B_FREE + ch));
    }
  }

  if (warp < 8) {
    const int go = (rg2 * 128 + warp * 16 + g) * DM + j2 * 80;
    load_x(xv, p.x + go, 8 * DM, q);
    float acc[40];
    mbar_wait(bar + 8 * (B_MMA + 2), 0);
    mbar_wait(bar + 8 * (B_MMA + 3), 0);
    mbar_wait(bar + 8 * (B_MMA + 4), 0);
    if (warp < 4) gemm2_loop<0>(acc); else gemm2_loop<1>(acc);
    mbar_wait(bar + 8 * B_SFULL, 0);
    uint32_t sv[5][4];
    {
      const int i = lane & 7, mi = lane >> 3;
      const uint32_t a = sb + OFF_U + ((mi >> 1) * 8 + i) * 256 + (((2 * warp + (mi & 1)) ^ i) << 4);
#pragma unroll
      for (int k = 0; k < 5; k++) ldsm4t(sv[k], a + k * 4096);
    }
    wg_wait<0>();
#pragma unroll
    for (int hh = 0; hh < 2; hh++) {
      uint32_t o[10];
#pragma unroll
      for (int tl = 0; tl < 10; tl++) {
        const uint32_t xw = xv[hh][tl];
        const uint32_t sw = sv[tl >> 1][(tl & 1) * 2 + hh];
        const float a = acc[4 * tl + 2 * hh], b = acc[4 * tl + 2 * hh + 1];
        o[tl] = pack_bf(fmaf(bflo(sw), fmaf(a, tanha(a), a), bflo(xw)), fmaf(bfhi(sw), fmaf(b, tanha(b), b), bfhi(xw)));
      }
      __nv_bfloat16* op = p.out + go + hh * 8 * DM;
      ((uint4*)op)[q] = make_uint4(o[0], o[1], o[2], o[3]);
      ((uint4*)op)[4 + q] = make_uint4(o[4], o[5], o[6], o[7]);
      ((uint2*)(op + 64))[q] = make_uint2(o[8], o[9]);
    }
  } else if (warp == 8) {
    if (elect1()) {
      const uint4* srcA = p.scr->h + rg2 * 24 * 1024;
      const uint4* srcB = p.scr->w2p + j2 * 24 * 640;
      mbar_wait(bar + 8 * (B_FULL2 + 4), 0);
      mbar_wait(bar + 8 * (B_FREE + 2), 0);
      asm volatile("fence.proxy.async.global;" ::: "memory");
      int slot = 5, ph = 1;
#pragma unroll 1
      for (int s = 5; s < 24; s++) {
        mbar_wait(bar + 8 * (B_EMPTY2 + slot), ph);
        const uint32_t mb = bar + 8 * (B_FULL2 + slot), d = sb + slot * SLOT2;
        mbar_expect(mb, SLOT2);
        bulk_g2s(d, srcA + s * 1024, 16384, mb);
        bulk_g2s(d + 16384, srcB + s * 640, 10240, mb);
        if (++slot == NS2) { slot = 0; ph ^= 1; }
      }
    }
    __syncwarp();
  } else if (warp == 13) {
    if (elect1()) {
#pragma unroll 1
      for (int c = 0; c < 5; c++) mbar_wait(bar + 8 * (B_FREE + c), 0);
      publish(cnt + (C_S + (wid >> 4)) * 32);
      poll_cnt(cnt + (C_S + j2) * 32, ep * 16);
      mbar_expect(bar + 8 * B_SFULL, 20480);
      bulk_g2s(sb + OFF_U, p.scr->sT + (j2 * 16 + rg2) * 1280, 20480, bar + 8 * B_SFULL);
    }
    __syncwarp();
  }
}

typedef CUresult (*EncodeFn)(CUtensorMap*, CUtensorMapDataType, cuuint32_t, void*, const cuuint64_t*, const cuuint64_t*,
                             const cuuint32_t*, const cuuint32_t*, CUtensorMapInterleave, CUtensorMapSwizzle,
                             CUtensorMapL2promotion, CUtensorMapFloatOOBfill);

}

extern "C" void kernel_launch(void* const* d_in, const int* in_sizes, int n_in, void* d_out, int out_size) {
  static EncodeFn enc = nullptr;
  static int nsm = 0;
  static void* scr = nullptr;
  if (!enc) {
    void* fn = nullptr;
    cudaDriverEntryPointQueryResult qr;
    cudaGetDriverEntryPoint("cuTensorMapEncodeTiled", &fn, cudaEnableDefault, &qr);
    enc = (EncodeFn)fn;
    int dev = 0;
    cudaGetDevice(&dev);
    cudaDeviceGetAttribute(&nsm, cudaDevAttrMultiProcessorCount, dev);
    cudaFuncSetAttribute(fused_s4_ffn_kernel<true>, cudaFuncAttributeMaxDynamicSharedMemorySize, SMEM_BYTES);
    cudaFuncSetAttribute(fused_s4_ffn_kernel<false>, cudaFuncAttributeMaxDynamicSharedMemorySize, SMEM_BYTES);
    cudaGetSymbolAddress(&scr, g_scr);
  }
  Params p;
  p.x = (const __nv_bfloat16*)d_in[0];
  p.are = (const __nv_bfloat16*)d_in[1]; p.aim = (const __nv_bfloat16*)d_in[2];
  p.bre = (const __nv_bfloat16*)d_in[3]; p.bim = (const __nv_bfloat16*)d_in[4];
  p.cre = (const __nv_bfloat16*)d_in[5]; p.cim = (const __nv_bfloat16*)d_in[6];
  p.logdt = (const __nv_bfloat16*)d_in[7]; p.dskip = (const __nv_bfloat16*)d_in[8];
  p.w1 = (const __nv_bfloat16*)d_in[10]; p.w2 = (const __nv_bfloat16*)d_in[11];
  p.out = (__nv_bfloat16*)d_out;
  p.scr = (Scratch*)scr;
  CUtensorMap tmX, tmW1, tmU;
  const cuuint32_t es[3] = {1, 1, 1};
  {
    const cuuint64_t gd[2] = {16 * DM, 128}, gs[1] = {DM * 32};
    const cuuint32_t bx[2] = {80, 128};
    enc(&tmU, CU_TENSOR_MAP_DATA_TYPE_FLOAT16, 2, p.scr->uT, gd, gs, bx, es, CU_TENSOR_MAP_INTERLEAVE_NONE,
        CU_TENSOR_MAP_SWIZZLE_NONE, CU_TENSOR_MAP_L2_PROMOTION_NONE, CU_TENSOR_MAP_FLOAT_OOB_FILL_NONE);
  }
  {
    const cuuint64_t gd[2] = {DM, SEQ}, gs[1] = {DM * 2};
    const cuuint32_t bx[2] = {64, 128};
    enc(&tmX, CU_TENSOR_MAP_DATA_TYPE_BFLOAT16, 2, d_in[0], gd, gs, bx, es, CU_TENSOR_MAP_INTERLEAVE_NONE,
        CU_TENSOR_MAP_SWIZZLE_128B, CU_TENSOR_MAP_L2_PROMOTION_L2_128B, CU_TENSOR_MAP_FLOAT_OOB_FILL_NONE);
  }
  {
    const cuuint64_t gd[3] = {64, DM, FF / 64}, gs[2] = {FF * 2, 128};
    const cuuint32_t bx[3] = {64, 64, 3};
    enc(&tmW1, CU_TENSOR_MAP_DATA_TYPE_BFLOAT16, 3, d_in[10], gd, gs, bx, es, CU_TENSOR_MAP_INTERLEAVE_NONE,
        CU_TENSOR_MAP_SWIZZLE_128B, CU_TENSOR_MAP_L2_PROMOTION_L2_128B, CU_TENSOR_MAP_FLOAT_OOB_FILL_NONE);
  }
  if (nsm == 132) fused_s4_ffn_kernel<true><<<132, 512, SMEM_BYTES>>>(p, tmX, tmW1, tmU);
  else fused_s4_ffn_kernel<false><<<132, 512, SMEM_BYTES>>>(p, tmX, tmW1, tmU);
}
```

```cpp
#include <cuda_runtime.h>
#include <cuda_bf16.h>
#include <cuda_fp16.h>
#include <cuda.h>
#include <stdint.h>

namespace {

constexpr int SEQ = 2048, DM = 640, NMODE = 192, FF = 1536;

constexpr int SLOT1 = 40960;
constexpr int SLOT2 = 26624;
constexpr int NS2 = 6;
#define PACE_NS 0
constexpr int ZA3 = 0, ZB3 = 2048, ZS = 4096, ZA2 = 6144, ZB2 = 9216, ZA1 = 12288, ZB1 = 16000;
constexpr int OFF_Z2 = 179456;
constexpr int OFF_U = 199168;
constexpr int OFF_KS = 163840;
constexpr int OFF_MISC = 229376;
constexpr int OFF_ZERO = OFF_MISC + 128;
constexpr int OFF_CHC = OFF_MISC + 16;
constexpr int OFF_EP = OFF_MISC + 64;
constexpr int OFF_K0 = OFF_MISC + 256;
constexpr int OFF_BAR = OFF_MISC + 384;
constexpr int OFF_STAT = OFF_MISC + 1024;
constexpr int OFF_CS = OFF_MISC + 2048;
constexpr int SMEM_BYTES = OFF_MISC + 3072;
constexpr int P0 = 8, PA1 = 280, PB1 = 360, PA2 = 448, PB2 = 544, PA3 = 632, PB3 = 704;
enum { B_FULL1 = 0, B_EMPTY1 = 4, B_DRAIN = 8, B_UFULL = 12, B_EPI = 13, B_ZRDY = 14, B_SFULL = 15,
       B_MMA = 16, B_W2 = 17, B_FREE = 21, B_FULL2 = 26, B_EMPTY2 = 32, B_NUM = 38 };
enum { C_LN = 0, C_CS = 1, C_H0 = 2, C_H1 = 18, C_S = 34, C_W2 = 42, C_NUM = 43 };

struct Scratch {
  unsigned cnt[64 * 32];
  unsigned epoch[256];
  float2 stats[SEQ];
  float cs[FF];
  uint4 uT[DM * 256];
  uint4 w2p[8 * 24 * 640];
  uint4 sT[8 * 16 * 1280];
  uint4 h[16 * 24 * 1024];
};
__device__ __align__(1024) Scratch g_scr;
constexpr uint32_t sb = 1024;
constexpr uint32_t bar = sb + OFF_BAR;
__host__ __device__ constexpr uint32_t slot1(int s) { return sb + ((s + 2) & 3) * SLOT1; }
__host__ __device__ constexpr uint32_t slot2(int i) { return sb + 39424 + ((0x501432 >> (4 * i)) & 7) * SLOT2; }
__device__ __forceinline__ uint32_t zbase(int ch) { return sb + (ch == 2 ? OFF_Z2 : ch < 2 ? 40960 + ch * 19712 : (ch - 3) * 19712); }
__device__ __forceinline__ uint32_t pbase(int ch) { return sb + 170240 + ch * 3072 + (ch >= 3 ? 40192 : 0); }
__device__ __forceinline__ uint32_t kscr(int w) { return sb + OFF_KS + (w < 10 ? (w ? w + 3 : 0) : (w < 13 ? w - 9 : w)) * 4096; }

struct Params {
  const __nv_bfloat16 *are, *aim, *bre, *bim, *cre, *cim, *logdt, *dskip, *x, *w1, *w2;
  __nv_bfloat16* out;
  Scratch* scr;
};

__device__ __forceinline__ void mbar_init(uint32_t a, int c) { asm volatile("mbarrier.init.shared::cta.b64 [%0], %1;" ::"r"(a), "r"(c)); }
__device__ __forceinline__ void mbar_expect(uint32_t a, int b) { asm volatile("mbarrier.arrive.expect_tx.shared::cta.b64 _, [%0], %1;" ::"r"(a), "r"(b) : "memory"); }
__device__ __forceinline__ void mbar_arrive(uint32_t a) { asm volatile("mbarrier.arrive.shared::cta.b64 _, [%0];" ::"r"(a) : "memory"); }
__device__ __forceinline__ void mbar_wait(uint32_t a, int ph) {
  asm volatile(
      "{\n.reg .pred p;\n.reg .u32 n;\n"
      "mbarrier.try_wait.parity.shared::cta.b64 p, [%0], %1;\n@p bra LD;\nmov.u32 n, 0;\n"
      "LW:\nmbarrier.try_wait.parity.shared::cta.b64 p, [%0], %1, 20000;\n@p bra LD;\n"
      "add.u32 n, n, 1;\nsetp.lt.u32 p, n, 100000;\n@p bra LW;\ntrap;\nLD:\n}\n" ::"r"(a), "r"(ph) : "memory");
}
__device__ __forceinline__ void poll_cnt(const unsigned* p, unsigned target) {
  asm volatile(
      "{\n.reg .pred p;\n.reg .u32 n;\n.reg .s32 v;\nmov.u32 n, 0;\n"
      "LW:\nld.relaxed.gpu.global.u32 v, [%0];\nsub.s32 v, v, %1;\nsetp.ge.s32 p, v, 0;\n@p bra LD;\n"
      "add.u32 n, n, 1;\nsetp.lt.u32 p, n, 4000000;\n@p bra LW;\ntrap;\n"
      "LD:\nfence.acquire.gpu;\nfence.proxy.async.global;\n}\n" ::"l"(p), "r"(target) : "memory");
}
__device__ __forceinline__ void publish(unsigned* p) {
  asm volatile("fence.proxy.async.global;\nfence.release.gpu;\nred.relaxed.gpu.global.add.u32 [%0], 1;" ::"l"(p) : "memory");
}
__device__ __forceinline__ uint32_t movm(uint32_t v) { uint32_t r; asm volatile("movmatrix.sync.aligned.m8n8.trans.b16 %0, %1;" : "=r"(r) : "r"(v)); return r; }
__device__ __forceinline__ void fence_async_smem() { asm volatile("fence.proxy.async.shared::cta;" ::: "memory"); }
__device__ __forceinline__ bool elect1() { uint32_t p; asm volatile("{\n.reg .pred P;\nelect.sync _|P, 0xffffffff;\nselp.u32 %0,1,0,P;\n}\n" : "=r"(p)); return p; }
__device__ __forceinline__ void bar_sync(int id, int n) { asm volatile("bar.sync %0, %1;" ::"r"(id), "r"(n) : "memory"); }
__device__ __forceinline__ void bar_arrive(int id, int n) { asm volatile("bar.arrive %0, %1;" ::"r"(id), "r"(n) : "memory"); }
__device__ __forceinline__ void bulk_g2s(uint32_t dst, const void* src, int bytes, uint32_t mb) {
  asm volatile("cp.async.bulk.shared::cluster.global.mbarrier::complete_tx::bytes [%0], [%1], %2, [%3];" ::"r"(dst), "l"(src), "r"(bytes), "r"(mb) : "memory");
}
__device__ __forceinline__ void bulk_prefetch(const void* src, int bytes) { asm volatile("cp.async.bulk.prefetch.L2.global [%0], %1;" ::"l"(src), "r"(bytes) : "memory"); }
__device__ __forceinline__ void tma2d(uint32_t dst, const CUtensorMap* m, int c0, int c1, uint32_t mb) {
  asm volatile("cp.async.bulk.tensor.2d.shared::cluster.global.mbarrier::complete_tx::bytes [%0], [%1, {%3, %4}], [%2];" ::"r"(dst), "l"(m), "r"(mb), "r"(c0), "r"(c1) : "memory");
}
__device__ __forceinline__ void tma3d(uint32_t dst, const CUtensorMap* m, int c0, int c1, int c2, uint32_t mb) {
  asm volatile("cp.async.bulk.tensor.3d.shared::cluster.global.mbarrier::complete_tx::bytes [%0], [%1, {%3, %4, %5}], [%2];" ::"r"(dst), "l"(m), "r"(mb), "r"(c0), "r"(c1), "r"(c2) : "memory");
}
__device__ __forceinline__ int frag_col(int l) {
  const int tl = l >> 3, i = l & 7;
  return (tl < 8 ? 32 * (tl >> 2) + 8 * (i >> 1) + 2 * (tl & 3) : 48 + 4 * (i >> 1) + 2 * tl) + (i & 1);
}
__device__ __forceinline__ void tma5d(uint32_t dst, const CUtensorMap* m, int c0, int c4, uint32_t mb) {
  asm volatile("cp.async.bulk.tensor.5d.shared::cluster.global.mbarrier::complete_tx::bytes [%0], [%1, {%3, %5, %5, %5, %4}], [%2];" ::"r"(dst), "l"(m), "r"(mb), "r"(c0), "r"(c4), "r"(0) : "memory");
}
__device__ __forceinline__ uint64_t dsc(uint32_t lo, uint32_t hi) { return ((uint64_t)hi << 32) | lo; }
__device__ __forceinline__ void wg_fence() { asm volatile("wgmma.fence.sync.aligned;" ::: "memory"); }
__device__ __forceinline__ void wg_commit() { asm volatile("wgmma.commit_group.sync.aligned;" ::: "memory"); }
template <int N> __device__ __forceinline__ void wg_wait() { asm volatile("wgmma.wait_group.sync.aligned %0;" ::"n"(N) : "memory"); }
__device__ __forceinline__ void wgmma_n192(float (&d)[96], uint64_t da, uint64_t db, int scale_d) {
  asm volatile("{\n.reg .pred p;\nsetp.ne.b32 p, %98, 0;\n"
    "wgmma.mma_async.sync.aligned.m64n192k16.f32.bf16.bf16 "
    "{"
    "%0, %1, %2, %3, %4, %5, %6, %7, %8, %9, %10, %11, %12, %13, %14, %15, "
    "%16, %17, %18, %19, %20, %21, %22, %23, %24, %25, %26, %27, %28, %29, %30, %31, "
    "%32, %33, %34, %35, %36, %37, %38, %39, %40, %41, %42, %43, %44, %45, %46, %47, "
    "%48, %49, %50, %51, %52, %53, %54, %55, %56, %57, %58, %59, %60, %61, %62, %63, "
    "%64, %65, %66, %67, %68, %69, %70, %71, %72, %73, %74, %75, %76, %77, %78, %79, "
    "%80, %81, %82, %83, %84, %85, %86, %87, %88, %89, %90, %91, %92, %93, %94, %95"
    "}, "
    "%96, %97, p, 1, 1, 0, 1;\n}\n"
    : "+f"(d[0]), "+f"(d[1]), "+f"(d[2]), "+f"(d[3]), "+f"(d[4]), "+f"(d[5]), "+f"(d[6]), "+f"(d[7]),
      "+f"(d[8]), "+f"(d[9]), "+f"(d[10]), "+f"(d[11]), "+f"(d[12]), "+f"(d[13]), "+f"(d[14]), "+f"(d[15]),
      "+f"(d[16]), "+f"(d[17]), "+f"(d[18]), "+f"(d[19]), "+f"(d[20]), "+f"(d[21]), "+f"(d[22]), "+f"(d[23]),
      "+f"(d[24]), "+f"(d[25]), "+f"(d[26]), "+f"(d[27]), "+f"(d[28]), "+f"(d[29]), "+f"(d[30]), "+f"(d[31]),
      "+f"(d[32]), "+f"(d[33]), "+f"(d[34]), "+f"(d[35]), "+f"(d[36]), "+f"(d[37]), "+f"(d[38]), "+f"(d[39]),
      "+f"(d[40]), "+f"(d[41]), "+f"(d[42]), "+f"(d[43]), "+f"(d[44]), "+f"(d[45]), "+f"(d[46]), "+f"(d[47]),
      "+f"(d[48]), "+f"(d[49]), "+f"(d[50]), "+f"(d[51]), "+f"(d[52]), "+f"(d[53]), "+f"(d[54]), "+f"(d[55]),
      "+f"(d[56]), "+f"(d[57]), "+f"(d[58]), "+f"(d[59]), "+f"(d[60]), "+f"(d[61]), "+f"(d[62]), "+f"(d[63]),
      "+f"(d[64]), "+f"(d[65]), "+f"(d[66]), "+f"(d[67]), "+f"(d[68]), "+f"(d[69]), "+f"(d[70]), "+f"(d[71]),
      "+f"(d[72]), "+f"(d[73]), "+f"(d[74]), "+f"(d[75]), "+f"(d[76]), "+f"(d[77]), "+f"(d[78]), "+f"(d[79]),
      "+f"(d[80]), "+f"(d[81]), "+f"(d[82]), "+f"(d[83]), "+f"(d[84]), "+f"(d[85]), "+f"(d[86]), "+f"(d[87]),
      "+f"(d[88]), "+f"(d[89]), "+f"(d[90]), "+f"(d[91]), "+f"(d[92]), "+f"(d[93]), "+f"(d[94]), "+f"(d[95])
    : "l"(da), "l"(db), "r"(scale_d));
}

__device__ __forceinline__ void wgmma_n80(float (&d)[40], uint64_t da, uint64_t db, int scale_d) {
  asm volatile("{\n.reg .pred p;\nsetp.ne.b32 p, %42, 0;\n"
    "wgmma.mma_async.sync.aligned.m64n80k16.f32.bf16.bf16 "
    "{"
    "%0, %1, %2, %3, %4, %5, %6, %7, %8, %9, %10, %11, %12, %13, %14, %15, "
    "%16, %17, %18, %19, %20, %21, %22, %23, %24, %25, %26, %27, %28, %29, %30, %31, "
    "%32, %33, %34, %35, %36, %37, %38, %39"
    "}, "
    "%40, %41, p, 1, 1, 0, 1;\n}\n"
    : "+f"(d[0]), "+f"(d[1]), "+f"(d[2]), "+f"(d[3]), "+f"(d[4]), "+f"(d[5]), "+f"(d[6]), "+f"(d[7]),
      "+f"(d[8]), "+f"(d[9]), "+f"(d[10]), "+f"(d[11]), "+f"(d[12]), "+f"(d[13]), "+f"(d[14]), "+f"(d[15]),
      "+f"(d[16]), "+f"(d[17]), "+f"(d[18]), "+f"(d[19]), "+f"(d[20]), "+f"(d[21]), "+f"(d[22]), "+f"(d[23]),
      "+f"(d[24]), "+f"(d[25]), "+f"(d[26]), "+f"(d[27]), "+f"(d[28]), "+f"(d[29]), "+f"(d[30]), "+f"(d[31]),
      "+f"(d[32]), "+f"(d[33]), "+f"(d[34]), "+f"(d[35]), "+f"(d[36]), "+f"(d[37]), "+f"(d[38]), "+f"(d[39])
    : "l"(da), "l"(db), "r"(scale_d));
}

__device__ __forceinline__ void hmma(float* c, uint32_t a0, uint32_t a1, uint32_t a2, uint32_t a3, uint32_t b0, uint32_t b1) {
  asm volatile("mma.sync.aligned.m16n8k16.row.col.f32.f16.f16.f32 {%0,%1,%2,%3}, {%4,%5,%6,%7}, {%8,%9}, {%0,%1,%2,%3};"
      : "+f"(c[0]), "+f"(c[1]), "+f"(c[2]), "+f"(c[3]) : "r"(a0), "r"(a1), "r"(a2), "r"(a3), "r"(b0), "r"(b1));
}
__device__ __forceinline__ void ldsm4(uint32_t* r, uint32_t a) { asm volatile("ldmatrix.sync.aligned.m8n8.x4.shared.b16 {%0,%1,%2,%3}, [%4];" : "=r"(r[0]), "=r"(r[1]), "=r"(r[2]), "=r"(r[3]) : "r"(a) : "memory"); }
__device__ __forceinline__ void ldsm4t(uint32_t* r, uint32_t a) { asm volatile("ldmatrix.sync.aligned.m8n8.x4.trans.shared.b16 {%0,%1,%2,%3}, [%4];" : "=r"(r[0]), "=r"(r[1]), "=r"(r[2]), "=r"(r[3]) : "r"(a) : "memory"); }
__device__ __forceinline__ void stsm4(uint32_t a, uint32_t r0, uint32_t r1, uint32_t r2, uint32_t r3) { asm volatile("stmatrix.sync.aligned.m8n8.x4.shared.b16 [%0], {%1,%2,%3,%4};" ::"r"(a), "r"(r0), "r"(r1), "r"(r2), "r"(r3) : "memory"); }
__device__ __forceinline__ void stsm4t(uint32_t a, uint32_t r0, uint32_t r1, uint32_t r2, uint32_t r3) { asm volatile("stmatrix.sync.aligned.m8n8.x4.trans.shared.b16 [%0], {%1,%2,%3,%4};" ::"r"(a), "r"(r0), "r"(r1), "r"(r2), "r"(r3) : "memory"); }
__device__ __forceinline__ uint32_t lds32(uint32_t a) { uint32_t v; asm volatile("ld.shared.u32 %0, [%1];" : "=r"(v) : "r"(a) : "memory"); return v; }
__device__ __forceinline__ uint2 lds64(uint32_t a) { uint2 v; asm volatile("ld.shared.v2.u32 {%0,%1}, [%2];" : "=r"(v.x), "=r"(v.y) : "r"(a) : "memory"); return v; }
__device__ __forceinline__ uint4 lds128(uint32_t a) { uint4 v; asm volatile("ld.shared.v4.u32 {%0,%1,%2,%3}, [%4];" : "=r"(v.x), "=r"(v.y), "=r"(v.z), "=r"(v.w) : "r"(a) : "memory"); return v; }
__device__ __forceinline__ void sts16(uint32_t a, uint32_t v) { asm volatile("st.shared.u16 [%0], %1;" ::"r"(a), "h"((unsigned short)v) : "memory"); }
__device__ __forceinline__ void sts32(uint32_t a, uint32_t v) { asm volatile("st.shared.u32 [%0], %1;" ::"r"(a), "r"(v) : "memory"); }
__device__ __forceinline__ void sts64(uint32_t a, uint32_t x, uint32_t y) { asm volatile("st.shared.v2.u32 [%0], {%1,%2};" ::"r"(a), "r"(x), "r"(y) : "memory"); }
__device__ __forceinline__ void sts128(uint32_t a, uint32_t x, uint32_t y, uint32_t z, uint32_t w) { asm volatile("st.shared.v4.u32 [%0], {%1,%2,%3,%4};" ::"r"(a), "r"(x), "r"(y), "r"(z), "r"(w) : "memory"); }
__device__ __forceinline__ float bflo(uint32_t v) { return __uint_as_float(v << 16); }
__device__ __forceinline__ float bfhi(uint32_t v) { return __uint_as_float(v & 0xffff0000u); }
__device__ __forceinline__ uint32_t pack_bf(float lo, float hi) { uint32_t r; asm("cvt.rn.bf16x2.f32 %0, %1, %2;" : "=r"(r) : "f"(hi), "f"(lo)); return r; }
__device__ __forceinline__ uint32_t pack_h(float lo, float hi) { uint32_t r; asm("cvt.rn.f16x2.f32 %0, %1, %2;" : "=r"(r) : "f"(hi), "f"(lo)); return r; }
__device__ __forceinline__ float rnd_bf(float v) { return __bfloat162float(__float2bfloat16_rn(v)); }
__device__ __forceinline__ float ex2a(float v) { float r; asm("ex2.approx.ftz.f32 %0, %1;" : "=f"(r) : "f"(v)); return r; }
__device__ __forceinline__ float tanha(float v) { float r; asm("tanh.approx.f32 %0, %1;" : "=f"(r) : "f"(v)); return r; }
__device__ __forceinline__ uint32_t hadd(uint32_t a, uint32_t b) { uint32_t r; asm("add.rn.f16x2 %0, %1, %2;" : "=r"(r) : "r"(a), "r"(b)); return r; }
__device__ __forceinline__ uint32_t badd(uint32_t a, uint32_t b) { uint32_t r; asm("add.rn.bf16x2 %0, %1, %2;" : "=r"(r) : "r"(a), "r"(b)); return r; }
__device__ __forceinline__ uint32_t bmul(uint32_t a, uint32_t b) { uint32_t r; asm("mul.rn.bf16x2 %0, %1, %2;" : "=r"(r) : "r"(a), "r"(b)); return r; }
__device__ __forceinline__ uint32_t bsub(uint32_t a, uint32_t b) { uint32_t r; asm("sub.rn.bf16x2 %0, %1, %2;" : "=r"(r) : "r"(a), "r"(b)); return r; }
__device__ __forceinline__ uint32_t dup(uint32_t v, uint32_t nz) { uint32_t r; asm volatile("add.rn.f32 %0, %1, %2;" : "=r"(r) : "r"(v), "r"(nz)); return r; }
__device__ __forceinline__ void bmma(float* c, uint32_t a0, uint32_t a1, uint32_t a2, uint32_t a3, uint32_t b0, uint32_t b1) {
  asm("mma.sync.aligned.m16n8k16.row.col.f32.bf16.bf16.f32 {%0,%1,%2,%3}, {%4,%5,%6,%7}, {%8,%9}, {%0,%1,%2,%3};"
      : "+f"(c[0]), "+f"(c[1]), "+f"(c[2]), "+f"(c[3]) : "r"(a0), "r"(a1), "r"(a2), "r"(a3), "r"(b0), "r"(b1));
}
__device__ __forceinline__ uint32_t odd_pair(uint32_t a, uint32_t b) { return __byte_perm(a, b, 0x5432); }
__device__ __forceinline__ int upos(int c) { return c ^ (c >> 5) ^ ((c >> 3) & 1); }
__device__ __forceinline__ int uoff(int pos) { return (pos >> 1) * 160 + (pos & 1) * 16; }

struct cf { float r, i; };
__device__ __forceinline__ cf cmul(cf a, cf b) { cf o; o.r = fmaf(a.r, b.r, -a.i * b.i); o.i = fmaf(a.r, b.i, a.i * b.r); return o; }
__device__ __forceinline__ cf csq(cf a) { cf o; o.r = fmaf(a.r, a.r, -a.i * a.i); o.i = (a.r + a.r) * a.i; return o; }
struct hp { uint32_t r, i; };
__device__ __forceinline__ hp hpack(cf a, cf b) { hp o; o.r = pack_h(a.r, b.r); o.i = pack_h(a.i, b.i); return o; }
__device__ __forceinline__ hp hmulc(hp a, uint32_t c) {
  __half2 ar = *reinterpret_cast<__half2*>(&a.r), ai = *reinterpret_cast<__half2*>(&a.i), cc = *reinterpret_cast<__half2*>(&c);
  __half2 orr = __hfma2(ar, __low2half2(cc), __hneg2(__hmul2(ai, __high2half2(cc))));
  __half2 oi = __hfma2(ar, __high2half2(cc), __hmul2(ai, __low2half2(cc)));
  hp o; o.r = *reinterpret_cast<uint32_t*>(&orr); o.i = *reinterpret_cast<uint32_t*>(&oi); return o;
}
__device__ __forceinline__ void sts_tile(uint32_t a, const hp* t) {
  sts128(a, t[0].r, t[1].r, t[2].r, t[3].r);
  sts128(a + 512, t[0].i, t[1].i, t[2].i, t[3].i);
}
template <int STEP> __device__ __forceinline__ void put2(uint32_t a0, uint32_t a1, uint32_t h, uint32_t sel) {
  const uint32_t x = __byte_perm(h, h, sel), y = x >> 16;
  sts16(a0, x); sts16(a0 + STEP * 4 + 2, x);
  sts16(a1, y); sts16(a1 + STEP * 4 + 2, y);
}

__device__ __forceinline__ void spare_work(const Params& p, const CUtensorMap* tmW1, int k, int tid) {
  const int lane = tid & 31;
  unsigned ep = 0;
  if (tid == 480) {
    ep = p.scr->epoch[128 + k] + 1;
    for (int i = 0; i < 8; i++) mbar_init(bar + 8 * i, i < 4 ? 1 : 12);
    asm volatile("fence.mbarrier_init.release.cluster;" ::: "memory");
    fence_async_smem();
  }
  __syncthreads();
  float a[2][4] = {{0.f, 0.f, 0.f, 0.f}, {0.f, 0.f, 0.f, 0.f}};
  if (tid >= 480) {
    if (elect1()) {
#pragma unroll 1
      for (int s = 0; s < 10; s++) {
        mbar_wait(bar + 8 * (4 + (s & 3)), ((s >> 2) & 1) ^ 1);
        mbar_expect(bar + 8 * (s & 3), 49152);
#pragma unroll 1
        for (int b = 0; b < 2; b++) tma3d(sb + (s & 3) * 49152 + b * 24576, tmW1, 0, s * 64, k * 6 + b * 3, bar + 8 * (s & 3));
      }
    }
    __syncwarp();
  } else if (tid < 384) {
    const uint32_t idn = (lane >> 3) == (lane & 3) ? ((lane & 4) ? 0x3f800000u : 0x3f80u) : 0u;
#pragma unroll 1
    for (int s = 0; s < 10; s++) {
      mbar_wait(bar + 8 * (s & 3), (s >> 2) & 1);
      const uint32_t ad = sb + (s & 3) * 49152 + (tid >> 6) * 8192 + (tid & 63) * 16;
#pragma unroll
      for (int i = 0; i < 8; i += 2) {
        const uint4 v = lds128(ad + i * 1024), w = lds128(ad + i * 1024 + 1024);
        bmma(a[0], v.x, v.y, w.x, w.y, idn, idn);
        bmma(a[1], v.z, v.w, w.z, w.w, idn, idn);
      }
      __syncwarp();
      if (lane == 0) mbar_arrive(bar + 8 * (4 + (s & 3)));
    }
    const int rho = (tid >> 3) & 7;
    const uint32_t ad = sb + 196608 + rho * 1536 + ((tid >> 6) * 8 + ((tid & 7) ^ rho)) * 32;
    sts128(ad, __float_as_uint(a[0][0]), __float_as_uint(a[0][1]), __float_as_uint(a[0][2]), __float_as_uint(a[0][3]));
    sts128(ad + 16, __float_as_uint(a[1][0]), __float_as_uint(a[1][1]), __float_as_uint(a[1][2]), __float_as_uint(a[1][3]));
  }
  __syncthreads();
  if (tid < 384) {
    float s = 0.f;
#pragma unroll
    for (int r = 0; r < 8; r++) s += __uint_as_float(lds32(sb + 196608 + r * 1536 + tid * 4));
    p.scr->cs[k * 384 + tid] = s;
  }
  __syncthreads();
  if (tid == 480) {
    publish(p.scr->cnt + C_CS * 32);
    p.scr->epoch[128 + k] = ep;
    poll_cnt(p.scr->cnt + C_LN * 32, ep * 128);
  }
}

__device__ __forceinline__ void load1(int s, const CUtensorMap* tmX, const CUtensorMap* tmW1, int rg1, int j1) {
  const uint32_t d = slot1(s), mb = bar + 8 * (B_FULL1 + (s & 3));
  mbar_expect(mb, SLOT1);
  tma2d(d, tmX, s * 64, rg1 * 128, mb);
  tma3d(d + 16384, tmW1, 0, s * 64, j1 * 3, mb);
}
template <int WG> __device__ __forceinline__ void gemm2_loop(float (&acc)[40]) {
#pragma unroll 1
  for (int o = 0; o < 24 / NS2; o++) {
#pragma unroll
    for (int s = 0; s < NS2; s++) {
      mbar_wait(bar + 8 * (B_FULL2 + s), o & 1);
      wg_fence();
#pragma unroll
      for (int kk = 0; kk < 4; kk++)
        wgmma_n80(acc, dsc(((slot2(s) + WG * 8192 + kk * 256) >> 4) | (8 << 16), 64),
                  dsc(((slot2(s) + 16384 + kk * 2560) >> 4) | (80 << 16), 8), (s | kk) ? 1 : o);
      wg_commit();
      wg_wait<1>();
      if ((s > 0 || o > 0) && elect1()) mbar_arrive(bar + 8 * (B_EMPTY2 + (s + NS2 - 1) % NS2));
    }
  }
}

__device__ __forceinline__ void load_x(uint32_t (&xv)[2][10], const __nv_bfloat16* xc, int rstep, int q) {
#pragma unroll
  for (int r = 0; r < 2; r++) {
    const uint4 a = __ldg((const uint4*)(xc + r * rstep) + q), b = __ldg((const uint4*)(xc + r * rstep) + 4 + q);
    const uint2 c = __ldg((const uint2*)(xc + r * rstep + 64) + q);
    xv[r][0] = a.x; xv[r][1] = a.y; xv[r][2] = a.z; xv[r][3] = a.w; xv[r][4] = b.x; xv[r][5] = b.y; xv[r][6] = b.z; xv[r][7] = b.w;
    xv[r][8] = c.x; xv[r][9] = c.y;
  }
}

template <bool USE_SMID>
__global__ void __launch_bounds__(512, 1)
fused_s4_ffn_kernel(const Params p, const __grid_constant__ CUtensorMap tmX, const __grid_constant__ CUtensorMap tmW1,
                    const __grid_constant__ CUtensorMap tmU, const __grid_constant__ CUtensorMap tmW2) {
  extern __shared__ __align__(1024) unsigned char smem_raw[];
  const int tid = threadIdx.x, lane = tid & 31;
  const int warp = __shfl_sync(0xffffffffu, tid >> 5, 0);
  const int g = lane >> 2, q = lane & 3;
  uint32_t sid;
  if (USE_SMID) asm("mov.u32 %0, %smid;" : "=r"(sid)); else sid = blockIdx.x;
  if (sid - 120u < 4u) { spare_work(p, &tmW1, sid - 120, tid); return; }
  const int wid = sid < 120 ? sid : sid - 4;
  unsigned* const cnt = p.scr->cnt;

  float kacc[5][4];
  const int kch = warp % 5, kpart = warp / 5;
  float k0n = 0.f;
  uint32_t xv[2][10];
  const __nv_bfloat16* const xln = p.x + (wid * 16 + ((g >> 1) << 2) + (g & 1)) * DM + (warp - 8) * 80;
  int kex = 0;
  uint32_t pa[6], pld, pds;
  if (warp < 15) {
    const int ch = (wid >> 4) * 80 + frag_col((wid & 15) * 5 + kch);
    const int o = (ch * NMODE + kpart * 64) / 2 + lane;
    pa[0] = __ldg((const uint32_t*)p.are + o); pa[1] = __ldg((const uint32_t*)p.aim + o);
    pa[2] = __ldg((const uint32_t*)p.bre + o); pa[3] = __ldg((const uint32_t*)p.bim + o);
    pa[4] = __ldg((const uint32_t*)p.cre + o); pa[5] = __ldg((const uint32_t*)p.cim + o);
    pld = __ldg((const unsigned short*)p.logdt + ch);
    pds = __ldg((const unsigned short*)p.dskip + ch);
  }
  int gpc, qi;
  {
    int i;
    if (sid < 64) { gpc = (sid & 15) >> 1; i = sid >> 4; }
    else if (sid < 120) { const int t = sid - 64; i = t / 14; gpc = 1 + ((t - i * 14) >> 1); i += 4; }
    else { gpc = 0; i = 4 + ((sid - 124) >> 1); }
    qi = ((0x52741630 >> (4 * i)) & 7) * 2 + (sid & 1);
  }
  const int rg1 = 4 * (gpc >> 1) + (qi >> 2), j1 = 4 * (gpc & 1) + (qi & 3);
  const int rg2 = rg1, j2 = j1;
  {
#pragma unroll
    for (int j = 0; j < 5; j++) { kacc[j][0] = kacc[j][1] = kacc[j][2] = kacc[j][3] = 0.f; }
    if (warp < 15) {
      const float dt = rnd_bf(expf(bflo(pld)));
      cf c0 = cmul(cf{bflo(pa[4]), bflo(pa[5])}, cf{bflo(pa[2]), bflo(pa[3])});
      cf c1 = cmul(cf{bfhi(pa[4]), bfhi(pa[5])}, cf{bfhi(pa[2]), bfhi(pa[3])});
      const float mx = fmaxf(fmaxf(fmaxf(fabsf(c0.r), fabsf(c0.i)), fmaxf(fabsf(c1.r), fabsf(c1.i))) * dt, fabsf(bflo(pds)) * (1.f / 256.f));
      const uint32_t mw = __reduce_max_sync(0xffffffffu, __float_as_uint(mx));
      float k0 = c0.r + c1.r;
#pragma unroll
      for (int o = 16; o; o >>= 1) k0 += __shfl_xor_sync(0xffffffffu, k0, o);
      if (lane == 0) sts64(sb + OFF_K0 + warp * 8, __float_as_uint(k0), mw);
      bar_sync(3 + kch, 96);
      const uint2 e0 = lds64(sb + OFF_K0 + kch * 8), e1 = lds64(sb + OFF_K0 + kch * 8 + 40), e2 = lds64(sb + OFF_K0 + kch * 8 + 80);
      kex = min(max((int)(max(max(e0.y, e1.y), e2.y) >> 23), 20), 240);
      const float s2 = __uint_as_float((259 - kex) << 23), sc = s2 * dt;
      k0n = fmaf(__uint_as_float(e0.x) + __uint_as_float(e1.x) + __uint_as_float(e2.x), sc, bflo(pds) * s2);
      const float dl2 = dt * 1.4426950408889634f;
      float zr = bflo(pa[0]) * dl2, th = bflo(pa[1]) * dt;
      cf c = cf{c0.r * sc, c0.i * sc};
      if (warp >= 8) load_x(xv, xln, 2 * DM, q);
      const uint32_t ks = kscr(warp);
      const uint32_t ka = ks + (lane >> 3) * 512 + (lane & 7) * 16;
      const uint32_t kb = ks + ((lane >> 3) & 1) * 512 + ((lane >> 4) * 8 + (lane & 7)) * 16;
#pragma unroll 1
      for (int it = 0; it < 2; it++) {
        float m = ex2a(zr);
        const cf w1 = cf{m * __cosf(th), m * __sinf(th)};
        m = ex2a(zr * 8.f);
        const cf w8 = cf{m * __cosf(th * 8.f), m * __sinf(th * 8.f)};
        const cf w16 = csq(w8), w32 = csq(w16), w64 = csq(w32), w128 = csq(w64), w256 = csq(w128), w512 = csq(w256), w1024 = csq(w512);
        hp lo[8];
        lo[0] = hpack(cf{1.f, 0.f}, cf{w8.r, -w8.i});
        lo[1] = hmulc(lo[0], pack_h(w16.r, -w16.i));
        { const uint32_t k = pack_h(w32.r, -w32.i); lo[2] = hmulc(lo[0], k); lo[3] = hmulc(lo[1], k); }
        { const uint32_t k = pack_h(w64.r, -w64.i);
#pragma unroll
          for (int i = 0; i < 4; i++) lo[4 + i] = hmulc(lo[i], k); }
        const uint32_t st = ks + lane * 16;
        sts128(st, lo[0].r, lo[1].r, lo[2].r, lo[3].r);
        sts128(st + 512, lo[4].r, lo[5].r, lo[6].r, lo[7].r);
        sts128(st + 1024, lo[0].i, lo[1].i, lo[2].i, lo[3].i);
        sts128(st + 1536, lo[4].i, lo[5].i, lo[6].i, lo[7].i);
        const cf t1 = cmul(c, w1), t2 = cmul(t1, w1), t3 = cmul(t2, w1), t4 = cmul(t3, w1);
        const cf t5 = cmul(t4, w1), t6 = cmul(t5, w1), t7 = cmul(t6, w1), t8 = cmul(c, w8);
        hp T0[4], T1[4], T2[4], T3[4], T4[4];
        T0[0] = hpack(t4, t8); T0[1] = hpack(t2, t6); T0[2] = hpack(t1, t5); T0[3] = hpack(t3, t7);
        const uint32_t k128 = pack_h(w128.r, w128.i), k256 = pack_h(w256.r, w256.i), k512 = pack_h(w512.r, w512.i);
#pragma unroll
        for (int i = 0; i < 4; i++) T1[i] = hmulc(T0[i], k128);
        sts_tile(st + 2048, T0);
        sts_tile(st + 3072, T1);
        __syncwarp();
        uint32_t af[4][4];
#pragma unroll
        for (int mg = 0; mg < 4; mg++) ldsm4t(af[mg], ka + mg * 128);
#pragma unroll
        for (int j = 0; j < 2; j++)
#pragma unroll
          for (int mg = 0; mg < 4; mg += 2) {
            uint32_t b[4];
            ldsm4t(b, kb + 2048 + j * 1024 + mg * 128);
            hmma(kacc[j], af[mg][0], af[mg][1], af[mg][2], af[mg][3], b[0], b[1]);
            hmma(kacc[j], af[mg + 1][0], af[mg + 1][1], af[mg + 1][2], af[mg + 1][3], b[2], b[3]);
          }
        T2[0] = hmulc(T0[0], k256); T2[1] = hmulc(T0[1], k256); T2[2] = hmulc(T1[0], k256); T2[3] = hmulc(T1[1], k256);
        T3[0] = hmulc(T0[0], k512); T3[1] = hmulc(T1[0], k512); T3[2] = hmulc(T2[0], k512); T3[3] = hmulc(T2[2], k512);
        { const cf u0 = cmul(t8, w1024), u1 = cmul(u0, w128);
          T4[0] = hpack(u0, u1); T4[1] = hmulc(T4[0], k256); T4[2] = hmulc(T4[0], k512); T4[3] = hmulc(T4[1], k512); }
        __syncwarp();
        sts_tile(st, T2);
        sts_tile(st + 1024, T3);
        sts_tile(st + 2048, T4);
        __syncwarp();
#pragma unroll
        for (int j = 0; j < 3; j++)
#pragma unroll
          for (int mg = 0; mg < 4; mg += 2) {
            uint32_t b[4];
            ldsm4t(b, kb + j * 1024 + mg * 128);
            hmma(kacc[2 + j], af[mg][0], af[mg][1], af[mg][2], af[mg][3], b[0], b[1]);
            hmma(kacc[2 + j], af[mg + 1][0], af[mg + 1][1], af[mg + 1][2], af[mg + 1][3], b[2], b[3]);
          }
        __syncwarp();
        zr = bfhi(pa[0]) * dl2; th = bfhi(pa[1]) * dt;
        c = cf{c1.r * sc, c1.i * sc};
      }
#pragma unroll
      for (int j = 0; j < 5; j++) {
        if (warp < 10) sts128(ks + j * 512 + lane * 16, __float_as_uint(kacc[j][0]), __float_as_uint(kacc[j][1]), __float_as_uint(kacc[j][2]), __float_as_uint(kacc[j][3]));
      }
    } else {
      const unsigned ep0 = p.scr->epoch[wid];
      if (elect1()) {
        if ((uint32_t)__cvta_generic_to_shared(smem_raw) != sb) __trap();
        for (int i = 0; i < B_NUM; i++) {
          int c = 1;
          if ((i >= B_EMPTY1 && i < B_UFULL) || i == B_ZRDY || i >= B_EMPTY2) c = 8;
          if (i >= B_FREE && i < B_FULL2) c = 4;
          if (i == B_MMA) c = 3;
          mbar_init(bar + 8 * i, c);
        }
        asm volatile("fence.mbarrier_init.release.cluster;" ::: "memory");
        bulk_prefetch(p.x + wid * 16 * DM, 16 * DM * 2);
#pragma unroll 1
        for (int s = 0; s < 4; s++) load1(s, &tmX, &tmW1, rg1, j1);
        bulk_prefetch(p.w1 + wid * 5 * FF, 5 * FF * 2);
        bulk_prefetch(p.w2 + wid * 12 * DM, 12 * DM * 2);
        asm volatile("prefetch.tensormap [%0];\nprefetch.tensormap [%1];" ::"l"(&tmU), "l"(&tmW2) : "memory");
      }
      sts64(sb + OFF_ZERO + (lane & 15) * 8 + (lane >> 4) * 640, 0, 0);
      const uint4* xr = (const uint4*)(p.x + (wid * 16 + ((g >> 1) << 2) + (g & 1)) * DM) + q;
      uint32_t sh[2];
      float sm[4], g0[2][4], g1[2][4];
#pragma unroll
      for (int i = 0; i < 8; i++) sm[i & 3] = g0[i >> 2][i & 3] = g1[i >> 2][i & 3] = 0.f;
      uint4 v[2][10];
#pragma unroll
      for (int i = 0; i < 10; i++) { v[0][i] = __ldg(xr + i * 4); v[1][i] = __ldg(xr + 160 + i * 4); }
      if (lane == 0) { p.scr->epoch[wid] = ep0 + 1; sts32(sb + OFF_EP, ep0 + 1); }
#pragma unroll
      for (int r = 0; r < 2; r++) {
        const uint32_t w = __shfl_sync(0xffffffffu, v[r][0].x, lane & 28);
        sh[r] = fabsf(bflo(w) - bfhi(w)) * 8.f < fabsf(bflo(w)) ? __byte_perm(w, 0, 0x1010) : 0u;
      }
#pragma unroll 1
      for (int b = 0; b < 2; b++) {
#pragma unroll
        for (int i = 0; i < 10; i++) {
#pragma unroll
          for (int e = 0; e < 2; e++) {
            const uint32_t x0 = (&v[0][i].x)[2 * e], x1 = (&v[1][i].x)[2 * e], x2 = (&v[0][i].x)[2 * e + 1], x3 = (&v[1][i].x)[2 * e + 1];
            const uint32_t a0 = bsub(x0, sh[0]), a1 = bsub(x1, sh[1]), a2 = bsub(x2, sh[0]), a3 = bsub(x3, sh[1]);
            bmma(sm, a0, a1, a2, a3, 0x3f803f80u, 0x3f803f80u);
            bmma(g0[e], a0, a1, a2, a3, x0, x2);
            bmma(g1[e], a0, a1, a2, a3, x1, x3);
          }
          if (b == 0) { v[0][i] = __ldg(xr + 40 + i * 4); v[1][i] = __ldg(xr + 200 + i * 4); }
        }
      }
      load_x(xv, xln, 2 * DM, q);
      if (q == (g >> 1)) {
#pragma unroll
        for (int r = 0; r < 2; r++) {
          const float md = sm[2 * r] * (1.f / DM), mean = bflo(sh[r]) + md;
          const float s2 = r ? ((g & 1) ? g1[0][3] + g1[1][3] : g1[0][2] + g1[1][2]) : ((g & 1) ? g0[0][1] + g0[1][1] : g0[0][0] + g0[1][0]);
          const float var = fmaxf(fmaf(-md, mean, s2 * (1.f / DM)), 0.f);
          const float m = rnd_bf(mean);
          const float ri = 1.f / rnd_bf(sqrtf(rnd_bf(rnd_bf(var) + 1e-5f)));
          p.scr->stats[wid * 16 + ((g >> 1) << 2) + (g & 1) + 2 * r] = make_float2(-m, 0.5f * ri);
          sts64(sb + OFF_STAT + g * 16 + r * 8, __float_as_uint(-m * ri), __float_as_uint(ri));
        }
      }
      __syncwarp();
    }
  }
  __syncthreads();
  const unsigned ep = lds32(sb + OFF_EP);

  if (warp < 8) {
    float acc[96];
    const uint32_t alo = ((sb >> 4) | (1 << 16)) + (warp >> 2) * 512;
#pragma unroll 1
    for (int s = 0; s < 10; s++) {
      const uint32_t so = ((s + 2) & 3) * (SLOT1 >> 4);
      mbar_wait(bar + 8 * (B_FULL1 + (s & 3)), (s >> 2) & 1);
      wg_fence();
#pragma unroll
      for (int kk = 0; kk < 4; kk++)
        wgmma_n192(acc, dsc(alo + so + kk * 2, 0x40000040u), dsc((((sb + 16384) >> 4) | (512 << 16)) + so + kk * 128, 0x40000040u), (s | kk) != 0);
      wg_commit();
      if (s > 0) {
        wg_wait<1>();
        const int sp = s - 1;
        if (elect1()) mbar_arrive(bar + 8 * (sp < 6 ? B_EMPTY1 + (sp & 3) : B_DRAIN + sp - 6));
      }
    }
    wg_wait<0>();
    if (lane == 0) mbar_arrive(bar + 8 * (B_DRAIN + 3));
    mbar_wait(bar + 8 * B_EPI, 0);
    const uint2 s0 = lds64(sb + OFF_STAT + (warp * 16 + g) * 8), s1 = lds64(sb + OFF_STAT + (warp * 16 + g + 8) * 8);
    const float nm0 = __uint_as_float(s0.x), r0 = __uint_as_float(s0.y), nm1 = __uint_as_float(s1.x), r1 = __uint_as_float(s1.y);
    uint4* hd = p.scr->h + (rg1 * 24 + j1) * 1024 + warp * 128 + q * 8 + g;
#pragma unroll
    for (int grp = 0; grp < 6; grp++) {
      uint32_t o0[4], o1[4];
#pragma unroll
      for (int tl = 0; tl < 4; tl++) {
        const int nt = grp * 4 + tl;
        const uint2 cs = lds64(sb + OFF_CS + (nt * 8 + 2 * q) * 4);
        const float ca = __uint_as_float(cs.x), cb = __uint_as_float(cs.y);
        const float a = fmaf(nm0, ca, acc[4 * nt]) * r0, b = fmaf(nm0, cb, acc[4 * nt + 1]) * r0;
        const float c = fmaf(nm1, ca, acc[4 * nt + 2]) * r1, d = fmaf(nm1, cb, acc[4 * nt + 3]) * r1;
        o0[tl] = pack_bf(fmaf(a, tanha(a), a), fmaf(b, tanha(b), b));
        o1[tl] = pack_bf(fmaf(c, tanha(c), c), fmaf(d, tanha(d), d));
      }
      uint4* dst = hd + (grp >> 1) * 8192 + (grp & 1) * 32;
      dst[0] = make_uint4(o0[0], o0[1], o0[2], o0[3]);
      dst[64] = make_uint4(o1[0], o1[1], o1[2], o1[3]);
      if (PACE_NS) __nanosleep(PACE_NS);
      if (grp == 1) {
        if (warp == 7) {
          bar_sync(2, 256);
          mbar_wait(bar + 8 * B_ZRDY, 0);
          if (lane == 0) publish(cnt + C_H0 * 32);
          __syncwarp();
        }
        else bar_arrive(2, 256);
      }
    }
    if (warp == 6) { bar_sync(11, 256); if (lane == 0) publish(cnt + (C_H1 + rg1) * 32); __syncwarp(); }
    else bar_arrive(11, 256);
    if (warp == 4) {
      const uint4* srcA = p.scr->h + rg2 * 24 * 1024;
      const uint4* srcB = p.scr->w2p + j2 * 24 * 640;
      mbar_wait(bar + 8 * (B_DRAIN + 3), 0);
      if (elect1()) {
        poll_cnt(cnt + C_H0 * 32, ep * 128);
#pragma unroll 1
        for (int s = 0; s < NS2; s++) {
          if (s >= 2) mbar_wait(bar + 8 * (B_FREE + ((s - 1) >> 1)), 0);
          mbar_expect(bar + 8 * (B_FULL2 + s), SLOT2);
          bulk_g2s(slot2(s), srcA + s * 1024, 16384, bar + 8 * (B_FULL2 + s));
          bulk_g2s(slot2(s) + 16384, srcB + s * 640, 10240, bar + 8 * (B_FULL2 + s));
        }
        poll_cnt(cnt + (C_H1 + rg2) * 32, ep * 8);
      }
      __syncwarp();
    }
  } else {
    const int cw = warp - 8;
    {
      const uint4 st = lds128(sb + OFF_STAT + g * 16);
      const float n0 = __uint_as_float(st.x), r0 = __uint_as_float(st.y), n1 = __uint_as_float(st.z), r1 = __uint_as_float(st.w);
      const int up = upos(2 * wid);
      uint2* dst = (uint2*)p.scr->uT + ((up >> 1) * DM + cw * 80) * 4 + (lane ^ ((up & 1) << 1));
#pragma unroll
      for (int i = 0; i < 10; i++) {
        const uint32_t a = movm(pack_h(fmaf(bflo(xv[0][i]), r0, n0), fmaf(bfhi(xv[0][i]), r0, n0)));
        const uint32_t b = movm(pack_h(fmaf(bflo(xv[1][i]), r1, n1), fmaf(bfhi(xv[1][i]), r1, n1)));
        dst[i * 32] = make_uint2(a, b);
      }
    }
    if (warp == 9) {
      bar_sync(12, 256);
      if (elect1()) {
        publish(cnt + C_LN * 32);
        poll_cnt(cnt + C_CS * 32, ep * 4);
        bulk_g2s(sb + OFF_CS, p.scr->cs + j1 * 192, 768, bar + 8 * B_EPI);
      }
      __syncwarp();
    } else bar_arrive(12, 256);
    if (warp == 15) {
      if (elect1()) {
#pragma unroll 1
        for (int s = 4; s < 7; s++) {
          mbar_wait(bar + 8 * (B_EMPTY1 + (s & 3)), ((s >> 2) & 1) ^ 1);
          load1(s, &tmX, &tmW1, rg1, j1);
        }
      }
      __syncwarp();
    }
    if (warp >= 10 && warp < 15) {
      const uint32_t pb = pbase(kch);
      uint32_t h[5][2];
#pragma unroll
      for (int j = 0; j < 5; j++) {
        const uint4 a = lds128(kscr(kch) + j * 512 + lane * 16), b = lds128(sb + OFF_KS + (kch + 8) * 4096 + j * 512 + lane * 16);
#pragma unroll
        for (int e = 0; e < 4; e++) kacc[j][e] += __uint_as_float((&a.x)[e]) + __uint_as_float((&b.x)[e]);
        if (j == 1) {
          const float k256 = __shfl_sync(0xffffffffu, kacc[1][3], 28);
          if (lane == 31) kacc[1][3] -= k256;
        }
        if (j == 2 || j == 3) { h[j][0] = pack_h(kacc[j][0], kacc[j][2]); h[j][1] = pack_h(kacc[j][1], kacc[j][3]); }
        else { h[j][0] = pack_h(kacc[j][0], kacc[j][1]); h[j][1] = pack_h(kacc[j][2], kacc[j][3]); }
      }
      fence_async_smem();
      bar_arrive(13, 192);
#pragma unroll
      for (int i = 0; i < 6; i++) sts128(pb + i * 512 + lane * 16, 0, 0, 0, 0);
      __syncwarp();
      {
        const int sw = g >> 2;
        const uint32_t sel = sw ? 0x1032 : 0x3210;
        const uint32_t a = pb + (P0 + 8 * g + ((0x3124 >> (4 * q)) & 7)) * 4, a0 = a + sw * 16, a1 = a + 16 - sw * 16;
        put2<1>(a0, a1, h[0][0], sel);
        put2<1>(a0 + 256, a1 + 256, h[0][1], sel);
        put2<1>(a0 + 512, a1 + 512, h[1][0], sel);
        put2<1>(lane == 28 ? pb + PB1 * 4 : a0 + 768, a1 + 768, h[1][1], sel);
      }
      {
        const int sw = q >> 1;
        const uint32_t sel = sw ? 0x1032 : 0x3210;
        uint32_t a = pb + (((q & 1) ? PA1 : PB1 + 1) + 32 * sw + 2 * g) * 4;
        put2<1>(a + sw * 64, a + 64 - sw * 64, h[2][0], sel);
        put2<1>(a + 4 + sw * 64, a + 68 - sw * 64, h[2][1], sel);
        a = pb + (PA2 + g + 16 * q) * 4;
        put2<2>(a + sw * 32, a + 32 - sw * 32, h[3][0], sel);
        put2<2>(a + (PB2 - PA2) * 4 + sw * 32, a + (PB2 - PA2) * 4 + 32 - sw * 32, h[3][1], sel);
        a = pb + (((g & 1) ? PB3 : PA3) + (g >> 1) + 16 * q) * 4;
        const uint32_t hx = sw ? h[4][1] : h[4][0], hy = sw ? h[4][0] : h[4][1];
        put2<1>(a + sw * 16, a + 32 + sw * 16, hx, 0x3210);
        put2<1>(a + 16 - sw * 16, a + 48 - sw * 16, hy, 0x3210);
      }
      if (lane == 30) put2<1>(pb + P0 * 4, pb + (PA1 + 64) * 4, pack_h(k0n, kacc[2][3]), 0x3210);
      if (lane == 31) sts64(sb + OFF_CHC + kch * 8, (kex - 5) * 0x00800080u, __byte_perm(h[3][1], 0, 0x3232));
    }
    if (warp == 8) {
      bar_sync(13, 192);
      if (elect1()) {
        mbar_expect(bar + 8 * B_W2, 96 * 176);
        tma5d(sb + OFF_Z2 + 128, &tmW2, (wid & 7) * 80, (wid >> 3) * 3, bar + 8 * B_W2);
      }
      __syncwarp();
    }
    {
      const int ct = min(tid - 256, 239), uu = ct / 80, ur = ct - uu * 80, kp = ur < 64 ? (ur & 31) : (ur - 64);
      const int grp = (wid >> 3) * 3 + uu, jj = grp / 6, rem = grp - jj * 6;
      const uint32_t a = sb + OFF_Z2 + 128 + (uu * 32 + kp) * 176 + (ur >> 5) * 64, a2 = a + (ur < 64 ? 32 : 16 * 176);
      uint4* dst = p.scr->w2p + ((wid & 7) * 24 + 8 * (rem >> 1) + jj) * 640 + ((rem & 1) * 4 + (kp >> 3)) * 80 + (kp & 7) + (ur >> 5) * 32;
      mbar_wait(bar + 8 * B_W2, 0);
      const uint4 wv[4] = {lds128(a), lds128(a + 16), lds128(a2), lds128(a2 + 16)};
      uint32_t w[16];
#pragma unroll
      for (int i = 0; i < 16; i++) w[i] = bmul((&wv[i >> 2].x)[i & 3], 0x3f003f00u);
      if (warp == 8) {
        if (elect1()) {
          mbar_expect(bar + 8 * B_UFULL, 20480);
          mbar_expect(bar + 8 * B_EPI, 1024 + 768);
          poll_cnt(cnt + C_LN * 32, ep * 128);
          tma2d(sb + OFF_U, &tmU, wid * 80, 0, bar + 8 * B_UFULL);
          bulk_g2s(sb + OFF_STAT, p.scr->stats + rg1 * 128, 1024, bar + 8 * B_EPI);
        }
        __syncwarp();
      }
      if (warp == 15) {
        bar_arrive(1, 256);
        if (elect1()) {
#pragma unroll 1
          for (int s = 7; s < 10; s++) {
            mbar_wait(bar + 8 * (B_EMPTY1 + (s & 3)), ((s >> 2) & 1) ^ 1);
            load1(s, &tmX, &tmW1, rg1, j1);
          }
        }
        __syncwarp();
      } else bar_sync(1, 256);
      if (ur < 64) {
#pragma unroll
        for (int i = 0; i < 4; i++) dst[8 * i] = make_uint4(w[i], w[4 + i], w[8 + i], w[12 + i]);
      } else {
        dst[0] = make_uint4(w[0], w[2], w[4], w[6]);
        dst[8] = make_uint4(w[1], w[3], w[5], w[7]);
        dst[160] = make_uint4(w[8], w[10], w[12], w[14]);
        dst[168] = make_uint4(w[9], w[11], w[13], w[15]);
      }
    }
    mbar_wait(bar + 8 * B_UFULL, 0);
#pragma unroll 1
    for (int rnd = -(cw >> 2); rnd < 2; rnd++) {
      if (rnd >= 0) mbar_wait(bar + 8 * (B_DRAIN + rnd), 0);
      const int ch = rnd < 0 ? 2 : (cw >> 2) + 3 - 3 * rnd, qt = (cw + (cw >> 2) * 2 + rnd) & 3, j = qt * 32 + lane;
      const uint32_t ub = sb + OFF_U + ch * 32, zb = zbase(ch);
      uint32_t w_[20], o_[20], d_[20], b3_[20];
      uint32_t *w = w_ + 8, *o = o_ + 8, *d = d_ + 8, *b3 = b3_ + 8;
      {
        const uint32_t am = j > 0 ? ub + uoff(upos(2 * j - 2)) : sb + OFF_ZERO, a0 = ub + uoff(upos(2 * j));
        const uint2 a = lds64(am + 8);
        const uint4 b = lds128(am ^ 16), c = lds128(a0), e = lds128(a0 ^ 16);
        w[8] = lds32(ub + uoff(upos((2 * j + 2) & 255)));
        w[-6] = a.x; w[-5] = a.y; w[-4] = b.x; w[-3] = b.y; w[-2] = b.z; w[-1] = b.w;
        w[0] = c.x; w[1] = c.y; w[2] = c.z; w[3] = c.w; w[4] = e.x; w[5] = e.y; w[6] = e.z; w[7] = e.w;
      }
#pragma unroll
      for (int i = -1; i <= 7; i++) o[i] = odd_pair(w[i], w[i + 1]);
#pragma unroll
      for (int i = 0; i <= 7; i++) { d[i] = hadd(w[i], o[i]); b3[i] = hadd(d[i], o[i - 1]); }
      if (j < 112) {
        const int gr = j >> 1;
        const uint32_t a1 = zb + ZA1 + 128 + (gr ^ ((gr >> 2) & 1)) * 64 + ((gr >> 1) & 3) * 16 + (j & 1) * 8;
#pragma unroll
        for (int pp = 0; pp < 4; pp++) {
          const uint32_t sel = (pp & 1) ? 0x7632 : 0x5410;
          const int k = pp >> 1;
          sts64(a1 ^ (pp * 16), __byte_perm(w[k - 1], w[k + 1], sel), __byte_perm(w[k + 3], w[k + 5], sel));
          sts64((a1 ^ (pp * 16)) + (ZB1 - ZA1), __byte_perm(b3[k], b3[k + 2], sel), __byte_perm(b3[k + 4], b3[k + 6], sel));
        }
      } else if (j >= 120) {
        sts128(zb + ZA1 + ((lane >> 2) & 1) * (ZB1 - ZA1) + (3 - q) * 16, 0, 0, 0, j == 127 ? w[8] << 16 : 0u);
      }
      if (qt < 3) {
        uint32_t e_[20], b5_[20];
        uint32_t *e = e_ + 8, *b5 = b5_ + 8;
#pragma unroll
        for (int i = -6; i <= -2; i++) o[i] = odd_pair(w[i], w[i + 1]);
#pragma unroll
        for (int i = -6; i <= -1; i++) d[i] = hadd(w[i], o[i]);
#pragma unroll
        for (int i = -5; i <= -1; i++) b3[i] = hadd(d[i], o[i - 1]);
#pragma unroll
        for (int i = -5; i <= 4; i++) e[i] = hadd(d[i - 1], d[i]);
#pragma unroll
        for (int i = -4; i <= 4; i++) b5[i] = hadd(e[i], w[i + 1]);
        const uint32_t a2 = zb + ((j >> 3) * 16 + (j & 7)) * 16;
        sts128(a2 + ZA2, b3[-2], b3[-1], b3[0], b3[1]);
        sts128(a2 + ZA2 + 128, b3[2], b3[3], b3[4], b3[5]);
        sts128(a2 + ZB2, b5[-4], b5[-3], b5[-2], b5[-1]);
        sts128(a2 + ZB2 + 128, b5[0], b5[1], b5[2], b5[3]);
        if (qt < 2) {
          sts128(a2 + ZS, d[-2], d[-1], d[0], d[1]);
          sts128(a2 + ZS + 128, d[2], d[3], d[4], d[5]);
          uint32_t b7[8], b9[8];
#pragma unroll
          for (int i = -4; i <= 3; i++) { b7[i + 4] = hadd(b3[i - 1], e[i + 1]); b9[i + 4] = hadd(e[i - 1], b5[i + 1]); }
          const uint32_t a3 = zb + ((j >> 4) * 32 + (j & 15)) * 16;
          sts128(a3 + ZA3, b7[0], b7[1], b7[2], b7[3]);
          sts128(a3 + ZA3 + 256, b7[4], b7[5], b7[6], b7[7]);
          sts128(a3 + ZB3 + 256, b9[0], b9[1], b9[2], b9[3]);
          if (j < 63) sts128(a3 + ZB3 + ((j & 15) == 15 ? 272 : 16), b9[4], b9[5], b9[6], b9[7]);
          else sts128(zb + ZB3, 0, 0, 0, 0);
        }
      }
    }
    __syncwarp();
    if (lane == 0) mbar_arrive(bar + 8 * B_ZRDY);
  }

  if ((warp >> 2) != 1) {
    const int wg = warp >> 2, role = (warp + (wg ? 2 * wg : 1)) & 3;
    mbar_wait(bar + 8 * B_ZRDY, 0);
    mbar_wait(bar + 8 * (B_DRAIN + 3), 0);
    const uint32_t nz = lds32(sb + OFF_ZERO) | 0x80000000u;
#pragma unroll 1
    for (int ch = (wg == 0 ? 2 : wg - 2); ch < 5; ch += 3) {
      const uint32_t ub = sb + OFF_U + ch * 32, zb = zbase(ch), pb = pbase(ch);
      const uint2 chc = lds64(sb + OFF_CHC + ch * 8);
      const int tid = lds32(sb + OFF_ZERO + 20) + threadIdx.x;
      const int lane = tid & 31, g = lane >> 2, q = lane & 3;
      const uint32_t pa = pb + (g - 2 * q) * 4;
      if (role < 2) {
        float acc[8][4];
#pragma unroll
        for (int r = 0; r < 8; r++) { acc[r][0] = acc[r][1] = acc[r][2] = acc[r][3] = 0.f; }
        float fix = 0.f;
        if (role == 1 && lane == 28) {
          const uint32_t k = lds32(pb + PB1 * 4), u0 = lds32(ub);
          fix = __low2float(*reinterpret_cast<const __half2*>(&k)) * __low2float(*reinterpret_cast<const __half2*>(&u0));
        }
        uint32_t ga[3][2];
#pragma unroll
        for (int gm = 0; gm < 3; gm++) {
          const int hb = 2 * (lane & 7) + role - 2 + gm, l3 = ((lane >> 3) ^ (hb >> 1)) & 7;
          ga[gm][0] = hb < 0 ? sb + OFF_ZERO + ((l3 * 16 + ch * 32) & 127) : ub + hb * 1280 + uoff(l3);
          ga[gm][1] = hb < 0 ? ga[gm][0] ^ 64 : ub + hb * 1280 + uoff(l3 ^ 4);
        }
        uint32_t b[12][4], A[17][4];
#pragma unroll
        for (int i = 11; i >= 8; i--) ldsm4(b[i], (ga[2][i & 1] ^ (((i >> 1) & 1) * 16)) + ((i >> 1) & 1) * 640);
        A[0][0] = lds32(pa + P0 * 4); A[0][1] = lds32(pa + P0 * 4 + 32); A[0][2] = lds32(sb + OFF_ZERO + 4);
#pragma unroll
        for (int m = 0; m <= 16; m++) {
          if (m < 16) {
            A[m + 1][0] = lds32(pa + P0 * 4 + (2 * m + 2) * 32);
            A[m + 1][1] = m < 15 ? lds32(pa + P0 * 4 + (2 * m + 3) * 32) : lds32(sb + OFF_ZERO + 8);
          }
          if ((m & 1) == 0 && m < 16) {
            const int i = 7 - (m >> 1);
            ldsm4(b[i], (ga[i >> 2][i & 1] ^ (((i >> 1) & 1) * 16)) + ((i >> 1) & 1) * 640);
          }
          A[m][3] = dup(A[m][0], nz);
          if (m < 16) A[m + 1][2] = dup(A[m][1], nz);
#pragma unroll
          for (int r = 7; r >= 0; r--) {
            const int f = 16 + r - m;
            hmma(acc[r], A[m][0], A[m][1], A[m][2], A[m][3], b[f >> 1][(f & 1) * 2], b[f >> 1][(f & 1) * 2 + 1]);
          }
        }
        acc[7][2] += fix;
        bar_sync(7 + wg, 64);
#pragma unroll
        for (int i = 3; i >= 0; i--)
          stsm4t((ga[2][i & 1] ^ (((i >> 1) & 1) * 16)) + ((i >> 1) & 1) * 640, pack_bf(acc[2 * i][0], acc[2 * i][1]), pack_bf(acc[2 * i][2], acc[2 * i][3]),
                 pack_bf(acc[2 * i + 1][0], acc[2 * i + 1][1]), pack_bf(acc[2 * i + 1][2], acc[2 * i + 1][3]));
      } else if (role == 2) {
        float acc[14][4];
#pragma unroll
        for (int r = 0; r < 14; r++) { acc[r][0] = acc[r][1] = acc[r][2] = acc[r][3] = 0.f; }
        const int mi = lane >> 3, hf = (lane >> 2) & 1;
        const uint32_t ze = zb + ZA1 + 128 - 512 + hf * 1792 + (mi ^ hf) * 64 + ((q ^ (mi >> 1) ^ (hf * 2)) << 4);
        const uint32_t zo = ze ^ 96;
#pragma unroll
        for (int arr = 0; arr < 2; arr++) {
          uint32_t A[5][4];
#pragma unroll
          for (int m = 0; m < 5; m++) {
            A[m][0] = lds32(pa + (arr ? PB1 : PA1) * 4 + m * 64);
            A[m][1] = m < 4 ? lds32(pa + (arr ? PB1 : PA1) * 4 + m * 64 + 32) : lds32(sb + OFF_ZERO + 4 + arr * 8);
          }
#pragma unroll
          for (int m = 4; m >= 1; m--) { A[m][2] = dup(A[m - 1][1], nz); A[m][3] = dup(A[m][0], nz); }
          A[0][2] = lds32(sb + OFF_ZERO + 8 + arr * 8); A[0][3] = dup(A[0][0], nz);
#pragma unroll
          for (int ip = 0; ip < 9; ip++) {
            uint32_t b[4];
            uint32_t ad = ((ip & 1) ? zo : ze) + ip * 256 + arr * (ZB1 - ZA1);
            if (ip < 2 && hf == 0 && (ip == 0 || mi != 3)) ad = sb + OFF_ZERO + (ad & 127);
            ldsm4(b, ad);
#pragma unroll
            for (int hh = 0; hh < 2; hh++)
#pragma unroll
              for (int m = 0; m < 5; m++) {
                const int i = 2 * ip + hh - 4 + m;
                if (i >= 0 && i < 14) hmma(acc[i], A[m][0], A[m][1], A[m][2], A[m][3], b[2 * hh], b[2 * hh + 1]);
              }
          }
        }
        const uint32_t a = zb + ZA1 + ((lane ^ (mi & 1)) << 4);
#pragma unroll
        for (int i = 0; i < 7; i++)
          stsm4(a + i * 512, pack_bf(acc[2 * i][0], acc[2 * i][1]), pack_bf(acc[2 * i][2], acc[2 * i][3]),
                pack_bf(acc[2 * i + 1][0], acc[2 * i + 1][1]), pack_bf(acc[2 * i + 1][2], acc[2 * i + 1][3]));
      } else {
        float acc[12][4];
        const uint32_t za = zb + lane * 16;
        {
          float d[4][2][4];
#pragma unroll
          for (int r = 0; r < 8; r++) { d[r >> 1][r & 1][0] = d[r >> 1][r & 1][1] = d[r >> 1][r & 1][2] = d[r >> 1][r & 1][3] = 0.f; }
#pragma unroll
          for (int arr = 0; arr < 2; arr++) {
            uint32_t A[4][4];
#pragma unroll
            for (int m = 0; m < 4; m++) { A[m][0] = lds32(pa + (arr ? PB3 : PA3) * 4 + m * 64); A[m][1] = lds32(pa + (arr ? PB3 : PA3) * 4 + m * 64 + 32); }
#pragma unroll
            for (int m = 0; m < 4; m++) { A[m][2] = m ? dup(A[m - 1][1], nz) : lds32(sb + OFF_ZERO + 4 + arr * 4); A[m][3] = dup(A[m][0], nz); }
#pragma unroll
            for (int io = 0; io < 4; io++) {
              uint32_t b[4];
              ldsm4t(b, za + (arr ? ZB3 : ZA3) + io * 512);
#pragma unroll
              for (int m = 0; m + io < 4; m++) {
                hmma(d[io + m][0], A[m][0], A[m][1], A[m][2], A[m][3], b[0], b[1]);
                hmma(d[io + m][1], A[m][0], A[m][1], A[m][2], A[m][3], b[2], b[3]);
              }
            }
          }
#pragma unroll
          for (int r = 0; r < 4; r++) {
            acc[r][0] = acc[r][1] = acc[r][2] = acc[r][3] = 0.f;
            acc[4 + 2 * r][0] = d[r][0][0]; acc[4 + 2 * r][1] = d[r][0][1]; acc[4 + 2 * r][2] = d[r][1][0]; acc[4 + 2 * r][3] = d[r][1][1];
            acc[5 + 2 * r][0] = d[r][0][2]; acc[5 + 2 * r][1] = d[r][0][3]; acc[5 + 2 * r][2] = d[r][1][2]; acc[5 + 2 * r][3] = d[r][1][3];
          }
        }
        {
          const uint32_t k0 = (g >> 1) == q ? (chc.y & ((g & 1) ? 0xffff0000u : 0xffffu)) : 0u;
          const uint32_t k1 = lds32(sb + OFF_ZERO + 12), k2 = lds32(sb + OFF_ZERO + 16), k3 = dup(k0, nz);
#pragma unroll
          for (int ip = 0; ip < 4; ip++) {
            uint32_t b[4];
            ldsm4t(b, za + ZS + ip * 512);
            hmma(acc[4 + 2 * ip], k0, k1, k2, k3, b[0], b[1]);
            hmma(acc[5 + 2 * ip], k0, k1, k2, k3, b[2], b[3]);
          }
        }
        const uint32_t pa2 = pb + (2 * g - 4 * q) * 4;
#pragma unroll
        for (int arr = 0; arr < 2; arr++) {
          uint32_t A[5][4];
#pragma unroll
          for (int m = 0; m < 5; m++) {
            const uint2 v = lds64(pa2 + (arr ? PB2 : PA2) * 4 + m * 64);
            A[m][0] = v.x; A[m][1] = v.y; A[m][2] = lds32(pa2 + (arr ? PB2 : PA2) * 4 + m * 64 - 4);
          }
#pragma unroll
          for (int m = 0; m < 5; m++) A[m][3] = dup(A[m][0], nz);
#pragma unroll
          for (int ip = 0; ip < 6; ip++) {
            uint32_t b[4];
            ldsm4t(b, za + (arr ? ZB2 : ZA2) + ip * 512);
#pragma unroll
            for (int hh = 0; hh < 2; hh++)
#pragma unroll
              for (int m = 0; m < 5; m++) {
                const int i = 2 * ip + hh + m;
                if (i < 12) hmma(acc[i], A[m][0], A[m][1], A[m][2], A[m][3], b[2 * hh], b[2 * hh + 1]);
              }
          }
        }
        const uint32_t a = zb + ZA2 + ((lane ^ ((lane >> 1) & 4)) << 4);
#pragma unroll
        for (int i = 0; i < 6; i++)
          stsm4(a + i * 512, pack_bf(acc[2 * i][0], acc[2 * i][1]), pack_bf(acc[2 * i][2], acc[2 * i][3]),
                pack_bf(acc[2 * i + 1][0], acc[2 * i + 1][1]), pack_bf(acc[2 * i + 1][2], acc[2 * i + 1][3]));
      }
      bar_sync(3 + wg, 128);
      if (ch >= 2 && (tid & 127) == 0) mbar_arrive(bar + 8 * B_MMA);
      {
        const int row = (wid & 15) * 5 + ch;
        const int c = tid & 127, c1 = c < 112 ? c + 32 : c - 112, c2 = c < 112 ? c + 144 : c - 96;
        const uint32_t zr = sb + OFF_ZERO + (lane & 7) * 16;
        const uint32_t a1 = c < 112 ? zb + ZA1 + ((2 * c) ^ ((c >> 2) & 1)) * 16 : zr;
        const uint32_t a2 = zb + ZA2 + ((c & ~15) - 32 + ((((c >> 1) & 7) + (c & 1) * 8) ^ ((c & 1) * 4))) * 16;
        const uint4 v0 = lds128(ub + uoff(upos(c1))), u0 = lds128(ub + uoff(upos(c2)));
        const uint4 y0 = lds128(a1), y1 = lds128(a1 ^ 16);
        const uint4 v2 = lds128(c1 >= 64 ? a2 : zr), u2 = lds128(c < 112 ? a2 + 112 * 16 : zr);
        uint4* dst = p.scr->sT + ((wid >> 4) * 16 * 80 + row) * 16 + ((c & 15) ^ (row & 7));
        const uint4 v = make_uint4(bmul(badd(badd(y0.x, v2.x), v0.x), chc.x), bmul(badd(badd(y0.y, v2.y), v0.y), chc.x),
                                   bmul(badd(badd(y1.x, v2.z), v0.z), chc.x), bmul(badd(badd(y1.y, v2.w), v0.w), chc.x));
        const uint4 u = make_uint4(bmul(badd(badd(y0.z, u2.x), u0.x), chc.x), bmul(badd(badd(y0.w, u2.y), u0.y), chc.x),
                                   bmul(badd(badd(y1.z, u2.z), u0.z), chc.x), bmul(badd(badd(y1.w, u2.w), u0.w), chc.x));
        fence_async_smem();
        dst[(c1 >> 4) * 1280] = v;
        dst[(c2 >> 4) * 1280] = u;
      }
      __syncwarp();
      if (lane == 0) mbar_arrive(bar + 8 * (B_FREE + ch));
    }
  }

  if (warp < 8) {
    const int go = (rg2 * 128 + warp * 16 + g) * DM + j2 * 80;
    load_x(xv, p.x + go, 8 * DM, q);
    float acc[40];
    mbar_wait(bar + 8 * B_MMA, 0);
    if (warp < 4) gemm2_loop<0>(acc); else gemm2_loop<1>(acc);
    mbar_wait(bar + 8 * B_SFULL, 0);
    uint32_t sv[5][4];
    {
      const int i = lane & 7, mi = lane >> 3;
      const uint32_t a = sb + OFF_U + ((mi >> 1) * 8 + i) * 256 + (((2 * warp + (mi & 1)) ^ i) << 4);
#pragma unroll
      for (int k = 0; k < 5; k++) ldsm4t(sv[k], a + k * 4096);
    }
    wg_wait<0>();
#pragma unroll
    for (int hh = 0; hh < 2; hh++) {
      uint32_t o[10];
#pragma unroll
      for (int tl = 0; tl < 10; tl++) {
        const uint32_t xw = xv[hh][tl];
        const uint32_t sw = sv[tl >> 1][(tl & 1) * 2 + hh];
        const float a = acc[4 * tl + 2 * hh], b = acc[4 * tl + 2 * hh + 1];
        o[tl] = pack_bf(fmaf(bflo(sw), fmaf(a, tanha(a), a), bflo(xw)), fmaf(bfhi(sw), fmaf(b, tanha(b), b), bfhi(xw)));
      }
      __nv_bfloat16* op = p.out + go + hh * 8 * DM;
      ((uint4*)op)[q] = make_uint4(o[0], o[1], o[2], o[3]);
      ((uint4*)op)[4 + q] = make_uint4(o[4], o[5], o[6], o[7]);
      ((uint2*)(op + 64))[q] = make_uint2(o[8], o[9]);
    }
  } else if (warp == 8) {
    if (elect1()) {
      const uint4* srcA = p.scr->h + rg2 * 24 * 1024;
      const uint4* srcB = p.scr->w2p + j2 * 24 * 640;
#pragma unroll 1
      for (int o = 1; o < 4; o++) {
        srcA += NS2 * 1024; srcB += NS2 * 640;
#pragma unroll
        for (int i = 0; i < NS2; i++) {
          mbar_wait(bar + 8 * (B_EMPTY2 + i), (o & 1) ^ 1);
          if (i == 0) asm volatile("fence.proxy.async.global;" ::: "memory");
          mbar_expect(bar + 8 * (B_FULL2 + i), SLOT2);
          bulk_g2s(slot2(i), srcA + i * 1024, 16384, bar + 8 * (B_FULL2 + i));
          bulk_g2s(slot2(i) + 16384, srcB + i * 640, 10240, bar + 8 * (B_FULL2 + i));
        }
      }
    }
    __syncwarp();
  } else if (warp == 13) {
    if (elect1()) {
#pragma unroll 1
      for (int c = 0; c < 5; c++) mbar_wait(bar + 8 * (B_FREE + c), 0);
      publish(cnt + (C_S + (wid >> 4)) * 32);
      poll_cnt(cnt + (C_S + j2) * 32, ep * 16);
      mbar_expect(bar + 8 * B_SFULL, 20480);
      bulk_g2s(sb + OFF_U, p.scr->sT + (j2 * 16 + rg2) * 1280, 20480, bar + 8 * B_SFULL);
    }
    __syncwarp();
  }
}

typedef CUresult (*EncodeFn)(CUtensorMap*, CUtensorMapDataType, cuuint32_t, void*, const cuuint64_t*, const cuuint64_t*,
                             const cuuint32_t*, const cuuint32_t*, CUtensorMapInterleave, CUtensorMapSwizzle,
                             CUtensorMapL2promotion, CUtensorMapFloatOOBfill);

}

extern "C" void kernel_launch(void* const* d_in, const int* in_sizes, int n_in, void* d_out, int out_size) {
  static EncodeFn enc = nullptr;
  static int nsm = 0;
  static void* scr = nullptr;
  if (!enc) {
    void* fn = nullptr;
    cudaDriverEntryPointQueryResult qr;
    cudaGetDriverEntryPoint("cuTensorMapEncodeTiled", &fn, cudaEnableDefault, &qr);
    enc = (EncodeFn)fn;
    int dev = 0;
    cudaGetDevice(&dev);
    cudaDeviceGetAttribute(&nsm, cudaDevAttrMultiProcessorCount, dev);
    cudaFuncSetAttribute(fused_s4_ffn_kernel<true>, cudaFuncAttributeMaxDynamicSharedMemorySize, SMEM_BYTES);
    cudaFuncSetAttribute(fused_s4_ffn_kernel<false>, cudaFuncAttributeMaxDynamicSharedMemorySize, SMEM_BYTES);
    cudaGetSymbolAddress(&scr, g_scr);
  }
  Params p;
  p.x = (const __nv_bfloat16*)d_in[0];
  p.are = (const __nv_bfloat16*)d_in[1]; p.aim = (const __nv_bfloat16*)d_in[2];
  p.bre = (const __nv_bfloat16*)d_in[3]; p.bim = (const __nv_bfloat16*)d_in[4];
  p.cre = (const __nv_bfloat16*)d_in[5]; p.cim = (const __nv_bfloat16*)d_in[6];
  p.logdt = (const __nv_bfloat16*)d_in[7]; p.dskip = (const __nv_bfloat16*)d_in[8];
  p.w1 = (const __nv_bfloat16*)d_in[10]; p.w2 = (const __nv_bfloat16*)d_in[11];
  p.out = (__nv_bfloat16*)d_out;
  p.scr = (Scratch*)scr;
  CUtensorMap tmX, tmW1, tmU, tmW2;
  const cuuint32_t es[5] = {1, 1, 1, 1, 1};
  {
    const cuuint64_t gd[5] = {DM, 2, 4, 4, FF / 32}, gs[4] = {DM * 2, DM * 16, DM * 4, DM * 64};
    const cuuint32_t bx[5] = {88, 2, 4, 4, 3};
    enc(&tmW2, CU_TENSOR_MAP_DATA_TYPE_BFLOAT16, 5, d_in[11], gd, gs, bx, es, CU_TENSOR_MAP_INTERLEAVE_NONE,
        CU_TENSOR_MAP_SWIZZLE_NONE, CU_TENSOR_MAP_L2_PROMOTION_NONE, CU_TENSOR_MAP_FLOAT_OOB_FILL_NONE);
  }
  {
    const cuuint64_t gd[2] = {16 * DM, 128}, gs[1] = {DM * 32};
    const cuuint32_t bx[2] = {80, 128};
    enc(&tmU, CU_TENSOR_MAP_DATA_TYPE_FLOAT16, 2, p.scr->uT, gd, gs, bx, es, CU_TENSOR_MAP_INTERLEAVE_NONE,
        CU_TENSOR_MAP_SWIZZLE_NONE, CU_TENSOR_MAP_L2_PROMOTION_NONE, CU_TENSOR_MAP_FLOAT_OOB_FILL_NONE);
  }
  {
    const cuuint64_t gd[2] = {DM, SEQ}, gs[1] = {DM * 2};
    const cuuint32_t bx[2] = {64, 128};
    enc(&tmX, CU_TENSOR_MAP_DATA_TYPE_BFLOAT16, 2, d_in[0], gd, gs, bx, es, CU_TENSOR_MAP_INTERLEAVE_NONE,
        CU_TENSOR_MAP_SWIZZLE_128B, CU_TENSOR_MAP_L2_PROMOTION_L2_128B, CU_TENSOR_MAP_FLOAT_OOB_FILL_NONE);
  }
  {
    const cuuint64_t gd[3] = {64, DM, FF / 64}, gs[2] = {FF * 2, 128};
    const cuuint32_t bx[3] = {64, 64, 3};
    enc(&tmW1, CU_TENSOR_MAP_DATA_TYPE_BFLOAT16, 3, d_in[10], gd, gs, bx, es, CU_TENSOR_MAP_INTERLEAVE_NONE,
        CU_TENSOR_MAP_SWIZZLE_128B, CU_TENSOR_MAP_L2_PROMOTION_L2_128B, CU_TENSOR_MAP_FLOAT_OOB_FILL_NONE);
  }
  if (nsm == 132) fused_s4_ffn_kernel<true><<<132, 512, SMEM_BYTES>>>(p, tmX, tmW1, tmU, tmW2);
  else fused_s4_ffn_kernel<false><<<132, 512, SMEM_BYTES>>>(p, tmX, tmW1, tmU, tmW2);
}
```

```cpp
#include <cuda_runtime.h>
#include <cuda_bf16.h>
#include <cuda_fp16.h>
#include <cuda.h>
#include <stdint.h>

namespace {

constexpr int SEQ = 2048, DM = 640, FF = 1536;

constexpr int SLOT1 = 40960;
constexpr int SLOT2 = 26624;
constexpr int NS2 = 6;
#define PACE_NS 0
constexpr int OFF_Z = 91904, ZSZ = 19712;
constexpr int ZA3 = 0, ZB3 = 2048, ZS = 4096, ZA2 = 6144, ZB2 = 9216, ZA1 = 12288, ZB1 = 16000;
constexpr int OFF_W2S = OFF_Z + 4 * ZSZ;
constexpr int OFF_U = 190464;
constexpr int OFF_P = 210944;
constexpr int OFF_KS = 163840;
constexpr int OFF_LNP = 225280;
constexpr int OFF_MISC = 226304;
constexpr int OFF_CHC = OFF_MISC + 16;
constexpr int OFF_EP = OFF_MISC + 64;
constexpr int OFF_ZERO = OFF_MISC + 128;
constexpr int OFF_STAT = OFF_MISC + 1024;
constexpr int OFF_CS = OFF_MISC + 2048;
constexpr int OFF_BAR = OFF_MISC + 2816;
constexpr int SMEM_BYTES = OFF_MISC + 6144;
constexpr int P0 = 8, PA1 = 280, PB1 = 360, PA2 = 448, PB2 = 544, PA3 = 632, PB3 = 704;
enum { B_FULL1 = 0, B_FULL2 = 10, B_UFULL = 34, B_EPI = 35, B_SFULL = 36, B_W2 = 37, B_MMA = 38,
       B_FREE = 39, B_ZRDY = 44,
       B_REL1 = 45, B_REL2 = 55, B_NUM = 79 };
enum { C_LN = 0, C_CS = 1, C_H0 = 2, C_H1 = 18, C_S = 34, C_W2 = 42, C_NUM = 43 };

struct Scratch {
  unsigned cnt[64 * 32];
  unsigned epoch[256];
  float2 stats[SEQ];
  float cs[FF];
  uint4 uT[DM * 256];
  uint4 w2p[8 * 24 * 640];
  uint4 sT[8 * 16 * 1280];
  uint4 h[16 * 24 * 1024];
};
__device__ __align__(1024) Scratch g_scr;
constexpr uint32_t sb = 1024;
constexpr uint32_t bar = sb + OFF_BAR;

struct Params {
  const __nv_bfloat16 *are, *aim, *bre, *bim, *cre, *cim, *logdt, *dskip, *x, *w1, *w2;
  __nv_bfloat16* out;
  Scratch* scr;
};

__device__ __forceinline__ void mbar_init(uint32_t a, int c) { asm volatile("mbarrier.init.shared::cta.b64 [%0], %1;" ::"r"(a), "r"(c)); }
__device__ __forceinline__ void mbar_expect(uint32_t a, int b) { asm volatile("mbarrier.arrive.expect_tx.shared::cta.b64 _, [%0], %1;" ::"r"(a), "r"(b) : "memory"); }
__device__ __forceinline__ void mbar_arrive(uint32_t a) { asm volatile("mbarrier.arrive.shared::cta.b64 _, [%0];" ::"r"(a) : "memory"); }
__device__ __forceinline__ void mbar_wait(uint32_t a, int ph) {
  asm volatile(
      "{\n.reg .pred p;\n.reg .u32 n;\n"
      "mbarrier.try_wait.parity.shared::cta.b64 p, [%0], %1;\n@p bra LD;\nmov.u32 n, 0;\n"
      "LW:\nmbarrier.try_wait.parity.shared::cta.b64 p, [%0], %1, 20000;\n@p bra LD;\n"
      "add.u32 n, n, 1;\nsetp.lt.u32 p, n, 100000;\n@p bra LW;\ntrap;\nLD:\n}\n" ::"r"(a), "r"(ph) : "memory");
}
__device__ __forceinline__ void poll_cnt(const unsigned* p, unsigned target) {
  asm volatile(
      "{\n.reg .pred p;\n.reg .u32 n;\n.reg .s32 v;\nmov.u32 n, 0;\n"
      "LW:\nld.relaxed.gpu.global.u32 v, [%0];\nsub.s32 v, v, %1;\nsetp.ge.s32 p, v, 0;\n@p bra LD;\n"
      "add.u32 n, n, 1;\nsetp.lt.u32 p, n, 4000000;\n@p bra LW;\ntrap;\n"
      "LD:\nfence.acquire.gpu;\nfence.proxy.async.global;\n}\n" ::"l"(p), "r"(target) : "memory");
}
__device__ __forceinline__ void publish(unsigned* p) {
  asm volatile("fence.proxy.async.global;\nfence.release.gpu;\nred.relaxed.gpu.global.add.u32 [%0], 1;" ::"l"(p) : "memory");
}
__device__ __forceinline__ uint32_t movm(uint32_t v) { uint32_t r; asm volatile("movmatrix.sync.aligned.m8n8.trans.b16 %0, %1;" : "=r"(r) : "r"(v)); return r; }
__device__ __forceinline__ void fence_async_smem() { asm volatile("fence.proxy.async.shared::cta;" ::: "memory"); }
__device__ __forceinline__ bool elect1() { uint32_t p; asm volatile("{\n.reg .pred P;\nelect.sync _|P, 0xffffffff;\nselp.u32 %0,1,0,P;\n}\n" : "=r"(p)); return p; }
__device__ __forceinline__ void bar_sync(int id, int n) { asm volatile("bar.sync %0, %1;" ::"r"(id), "r"(n) : "memory"); }
__device__ __forceinline__ void bar_arrive(int id, int n) { asm volatile("bar.arrive %0, %1;" ::"r"(id), "r"(n) : "memory"); }
__device__ __forceinline__ void bulk_g2s(uint32_t dst, const void* src, int bytes, uint32_t mb) {
  asm volatile("cp.async.bulk.shared::cluster.global.mbarrier::complete_tx::bytes [%0], [%1], %2, [%3];" ::"r"(dst), "l"(src), "r"(bytes), "r"(mb) : "memory");
}
__device__ __forceinline__ void bulk_prefetch(const void* src, int bytes) { asm volatile("cp.async.bulk.prefetch.L2.global [%0], %1;" ::"l"(src), "r"(bytes) : "memory"); }
__device__ __forceinline__ void tma2d(uint32_t dst, const CUtensorMap* m, int c0, int c1, uint32_t mb) {
  asm volatile("cp.async.bulk.tensor.2d.shared::cluster.global.mbarrier::complete_tx::bytes [%0], [%1, {%3, %4}], [%2];" ::"r"(dst), "l"(m), "r"(mb), "r"(c0), "r"(c1) : "memory");
}
__device__ __forceinline__ void tma3d(uint32_t dst, const CUtensorMap* m, int c0, int c1, int c2, uint32_t mb) {
  asm volatile("cp.async.bulk.tensor.3d.shared::cluster.global.mbarrier::complete_tx::bytes [%0], [%1, {%3, %4, %5}], [%2];" ::"r"(dst), "l"(m), "r"(mb), "r"(c0), "r"(c1), "r"(c2) : "memory");
}
__device__ __forceinline__ int frag_col(int l) {
  const int tl = l >> 3, i = l & 7;
  return (tl < 8 ? 32 * (tl >> 2) + 8 * (i >> 1) + 2 * (tl & 3) : 48 + 4 * (i >> 1) + 2 * tl) + (i & 1);
}
__device__ __forceinline__ void tma5d(uint32_t dst, const CUtensorMap* m, int c0, int c4, uint32_t mb) {
  asm volatile("cp.async.bulk.tensor.5d.shared::cluster.global.mbarrier::complete_tx::bytes [%0], [%1, {%3, %5, %5, %5, %4}], [%2];" ::"r"(dst), "l"(m), "r"(mb), "r"(c0), "r"(c4), "r"(0) : "memory");
}
__device__ __forceinline__ uint64_t dsc(uint32_t lo, uint32_t hi) { return ((uint64_t)hi << 32) | lo; }
__device__ __forceinline__ void wg_fence() { asm volatile("wgmma.fence.sync.aligned;" ::: "memory"); }
__device__ __forceinline__ void wg_commit() { asm volatile("wgmma.commit_group.sync.aligned;" ::: "memory"); }
template <int N> __device__ __forceinline__ void wg_wait() { asm volatile("wgmma.wait_group.sync.aligned %0;" ::"n"(N) : "memory"); }
__device__ __forceinline__ void wgmma_n192(float (&d)[96], uint64_t da, uint64_t db, int scale_d) {
  asm volatile("{\n.reg .pred p;\nsetp.ne.b32 p, %98, 0;\n"
    "wgmma.mma_async.sync.aligned.m64n192k16.f32.bf16.bf16 "
    "{"
    "%0, %1, %2, %3, %4, %5, %6, %7, %8, %9, %10, %11, %12, %13, %14, %15, "
    "%16, %17, %18, %19, %20, %21, %22, %23, %24, %25, %26, %27, %28, %29, %30, %31, "
    "%32, %33, %34, %35, %36, %37, %38, %39, %40, %41, %42, %43, %44, %45, %46, %47, "
    "%48, %49, %50, %51, %52, %53, %54, %55, %56, %57, %58, %59, %60, %61, %62, %63, "
    "%64, %65, %66, %67, %68, %69, %70, %71, %72, %73, %74, %75, %76, %77, %78, %79, "
    "%80, %81, %82, %83, %84, %85, %86, %87, %88, %89, %90, %91, %92, %93, %94, %95"
    "}, "
    "%96, %97, p, 1, 1, 0, 1;\n}\n"
    : "+f"(d[0]), "+f"(d[1]), "+f"(d[2]), "+f"(d[3]), "+f"(d[4]), "+f"(d[5]), "+f"(d[6]), "+f"(d[7]),
      "+f"(d[8]), "+f"(d[9]), "+f"(d[10]), "+f"(d[11]), "+f"(d[12]), "+f"(d[13]), "+f"(d[14]), "+f"(d[15]),
      "+f"(d[16]), "+f"(d[17]), "+f"(d[18]), "+f"(d[19]), "+f"(d[20]), "+f"(d[21]), "+f"(d[22]), "+f"(d[23]),
      "+f"(d[24]), "+f"(d[25]), "+f"(d[26]), "+f"(d[27]), "+f"(d[28]), "+f"(d[29]), "+f"(d[30]), "+f"(d[31]),
      "+f"(d[32]), "+f"(d[33]), "+f"(d[34]), "+f"(d[35]), "+f"(d[36]), "+f"(d[37]), "+f"(d[38]), "+f"(d[39]),
      "+f"(d[40]), "+f"(d[41]), "+f"(d[42]), "+f"(d[43]), "+f"(d[44]), "+f"(d[45]), "+f"(d[46]), "+f"(d[47]),
      "+f"(d[48]), "+f"(d[49]), "+f"(d[50]), "+f"(d[51]), "+f"(d[52]), "+f"(d[53]), "+f"(d[54]), "+f"(d[55]),
      "+f"(d[56]), "+f"(d[57]), "+f"(d[58]), "+f"(d[59]), "+f"(d[60]), "+f"(d[61]), "+f"(d[62]), "+f"(d[63]),
      "+f"(d[64]), "+f"(d[65]), "+f"(d[66]), "+f"(d[67]), "+f"(d[68]), "+f"(d[69]), "+f"(d[70]), "+f"(d[71]),
      "+f"(d[72]), "+f"(d[73]), "+f"(d[74]), "+f"(d[75]), "+f"(d[76]), "+f"(d[77]), "+f"(d[78]), "+f"(d[79]),
      "+f"(d[80]), "+f"(d[81]), "+f"(d[82]), "+f"(d[83]), "+f"(d[84]), "+f"(d[85]), "+f"(d[86]), "+f"(d[87]),
      "+f"(d[88]), "+f"(d[89]), "+f"(d[90]), "+f"(d[91]), "+f"(d[92]), "+f"(d[93]), "+f"(d[94]), "+f"(d[95])
    : "l"(da), "l"(db), "r"(scale_d));
}

__device__ __forceinline__ void wgmma_n80(float (&d)[40], uint64_t da, uint64_t db, int scale_d) {
  asm volatile("{\n.reg .pred p;\nsetp.ne.b32 p, %42, 0;\n"
    "wgmma.mma_async.sync.aligned.m64n80k16.f32.bf16.bf16 "
    "{"
    "%0, %1, %2, %3, %4, %5, %6, %7, %8, %9, %10, %11, %12, %13, %14, %15, "
    "%16, %17, %18, %19, %20, %21, %22, %23, %24, %25, %26, %27, %28, %29, %30, %31, "
    "%32, %33, %34, %35, %36, %37, %38, %39"
    "}, "
    "%40, %41, p, 1, 1, 0, 1;\n}\n"
    : "+f"(d[0]), "+f"(d[1]), "+f"(d[2]), "+f"(d[3]), "+f"(d[4]), "+f"(d[5]), "+f"(d[6]), "+f"(d[7]),
      "+f"(d[8]), "+f"(d[9]), "+f"(d[10]), "+f"(d[11]), "+f"(d[12]), "+f"(d[13]), "+f"(d[14]), "+f"(d[15]),
      "+f"(d[16]), "+f"(d[17]), "+f"(d[18]), "+f"(d[19]), "+f"(d[20]), "+f"(d[21]), "+f"(d[22]), "+f"(d[23]),
      "+f"(d[24]), "+f"(d[25]), "+f"(d[26]), "+f"(d[27]), "+f"(d[28]), "+f"(d[29]), "+f"(d[30]), "+f"(d[31]),
      "+f"(d[32]), "+f"(d[33]), "+f"(d[34]), "+f"(d[35]), "+f"(d[36]), "+f"(d[37]), "+f"(d[38]), "+f"(d[39])
    : "l"(da), "l"(db), "r"(scale_d));
}

__device__ __forceinline__ void hmma(float* c, uint32_t a0, uint32_t a1, uint32_t a2, uint32_t a3, uint32_t b0, uint32_t b1) {
  asm volatile("mma.sync.aligned.m16n8k16.row.col.f32.f16.f16.f32 {%0,%1,%2,%3}, {%4,%5,%6,%7}, {%8,%9}, {%0,%1,%2,%3};"
      : "+f"(c[0]), "+f"(c[1]), "+f"(c[2]), "+f"(c[3]) : "r"(a0), "r"(a1), "r"(a2), "r"(a3), "r"(b0), "r"(b1));
}
__device__ __forceinline__ void ldsm4(uint32_t* r, uint32_t a) { asm volatile("ldmatrix.sync.aligned.m8n8.x4.shared.b16 {%0,%1,%2,%3}, [%4];" : "=r"(r[0]), "=r"(r[1]), "=r"(r[2]), "=r"(r[3]) : "r"(a) : "memory"); }
__device__ __forceinline__ void ldsm4t(uint32_t* r, uint32_t a) { asm volatile("ldmatrix.sync.aligned.m8n8.x4.trans.shared.b16 {%0,%1,%2,%3}, [%4];" : "=r"(r[0]), "=r"(r[1]), "=r"(r[2]), "=r"(r[3]) : "r"(a) : "memory"); }
__device__ __forceinline__ void stsm4(uint32_t a, uint32_t r0, uint32_t r1, uint32_t r2, uint32_t r3) { asm volatile("stmatrix.sync.aligned.m8n8.x4.shared.b16 [%0], {%1,%2,%3,%4};" ::"r"(a), "r"(r0), "r"(r1), "r"(r2), "r"(r3) : "memory"); }
__device__ __forceinline__ void stsm4t(uint32_t a, uint32_t r0, uint32_t r1, uint32_t r2, uint32_t r3) { asm volatile("stmatrix.sync.aligned.m8n8.x4.trans.shared.b16 [%0], {%1,%2,%3,%4};" ::"r"(a), "r"(r0), "r"(r1), "r"(r2), "r"(r3) : "memory"); }
__device__ __forceinline__ uint32_t lds32(uint32_t a) { uint32_t v; asm volatile("ld.shared.u32 %0, [%1];" : "=r"(v) : "r"(a) : "memory"); return v; }
__device__ __forceinline__ uint2 lds64(uint32_t a) { uint2 v; asm volatile("ld.shared.v2.u32 {%0,%1}, [%2];" : "=r"(v.x), "=r"(v.y) : "r"(a) : "memory"); return v; }
__device__ __forceinline__ uint4 lds128(uint32_t a) { uint4 v; asm volatile("ld.shared.v4.u32 {%0,%1,%2,%3}, [%4];" : "=r"(v.x), "=r"(v.y), "=r"(v.z), "=r"(v.w) : "r"(a) : "memory"); return v; }
__device__ __forceinline__ void sts16(uint32_t a, uint32_t v) { asm volatile("st.shared.u16 [%0], %1;" ::"r"(a), "h"((unsigned short)v) : "memory"); }
__device__ __forceinline__ void sts32(uint32_t a, uint32_t v) { asm volatile("st.shared.u32 [%0], %1;" ::"r"(a), "r"(v) : "memory"); }
__device__ __forceinline__ void sts64(uint32_t a, uint32_t x, uint32_t y) { asm volatile("st.shared.v2.u32 [%0], {%1,%2};" ::"r"(a), "r"(x), "r"(y) : "memory"); }
__device__ __forceinline__ void sts128(uint32_t a, uint32_t x, uint32_t y, uint32_t z, uint32_t w) { asm volatile("st.shared.v4.u32 [%0], {%1,%2,%3,%4};" ::"r"(a), "r"(x), "r"(y), "r"(z), "r"(w) : "memory"); }
__device__ __forceinline__ float bflo(uint32_t v) { return __uint_as_float(v << 16); }
__device__ __forceinline__ float bfhi(uint32_t v) { return __uint_as_float(v & 0xffff0000u); }
__device__ __forceinline__ uint32_t pack_bf(float lo, float hi) { uint32_t r; asm("cvt.rn.bf16x2.f32 %0, %1, %2;" : "=r"(r) : "f"(hi), "f"(lo)); return r; }
__device__ __forceinline__ uint32_t pack_h(float lo, float hi) { uint32_t r; asm("cvt.rn.f16x2.f32 %0, %1, %2;" : "=r"(r) : "f"(hi), "f"(lo)); return r; }
__device__ __forceinline__ float rnd_bf(float v) { return __bfloat162float(__float2bfloat16_rn(v)); }
__device__ __forceinline__ float ex2a(float v) { float r; asm("ex2.approx.ftz.f32 %0, %1;" : "=f"(r) : "f"(v)); return r; }
__device__ __forceinline__ float tanha(float v) { float r; asm("tanh.approx.f32 %0, %1;" : "=f"(r) : "f"(v)); return r; }
__device__ __forceinline__ uint32_t hadd(uint32_t a, uint32_t b) { uint32_t r; asm("add.rn.f16x2 %0, %1, %2;" : "=r"(r) : "r"(a), "r"(b)); return r; }
__device__ __forceinline__ uint32_t badd(uint32_t a, uint32_t b) { uint32_t r; asm("add.rn.bf16x2 %0, %1, %2;" : "=r"(r) : "r"(a), "r"(b)); return r; }
__device__ __forceinline__ uint32_t bmul(uint32_t a, uint32_t b) { uint32_t r; asm("mul.rn.bf16x2 %0, %1, %2;" : "=r"(r) : "r"(a), "r"(b)); return r; }
__device__ __forceinline__ uint32_t bsub(uint32_t a, uint32_t b) { uint32_t r; asm("sub.rn.bf16x2 %0, %1, %2;" : "=r"(r) : "r"(a), "r"(b)); return r; }
__device__ __forceinline__ uint32_t dup(uint32_t v, uint32_t nz) { uint32_t r; asm volatile("add.rn.f32 %0, %1, %2;" : "=r"(r) : "r"(v), "r"(nz)); return r; }
__device__ __forceinline__ void bmma(float* c, uint32_t a0, uint32_t a1, uint32_t a2, uint32_t a3, uint32_t b0, uint32_t b1) {
  asm("mma.sync.aligned.m16n8k16.row.col.f32.bf16.bf16.f32 {%0,%1,%2,%3}, {%4,%5,%6,%7}, {%8,%9}, {%0,%1,%2,%3};"
      : "+f"(c[0]), "+f"(c[1]), "+f"(c[2]), "+f"(c[3]) : "r"(a0), "r"(a1), "r"(a2), "r"(a3), "r"(b0), "r"(b1));
}
__device__ __forceinline__ uint32_t odd_pair(uint32_t a, uint32_t b) { return __byte_perm(a, b, 0x5432); }
__device__ __forceinline__ int upos(int c) { return c ^ (c >> 5) ^ ((c >> 3) & 1); }
__device__ __forceinline__ int uoff(int pos) { return (pos >> 1) * 160 + (pos & 1) * 16; }

struct cf { float r, i; };
__device__ __forceinline__ cf cmul(cf a, cf b) { cf o; o.r = fmaf(a.r, b.r, -a.i * b.i); o.i = fmaf(a.r, b.i, a.i * b.r); return o; }
__device__ __forceinline__ cf csq(cf a) { cf o; o.r = fmaf(a.r, a.r, -a.i * a.i); o.i = (a.r + a.r) * a.i; return o; }
struct hp { uint32_t r, i; };
__device__ __forceinline__ hp hpack(cf a, cf b) { hp o; o.r = pack_h(a.r, b.r); o.i = pack_h(a.i, b.i); return o; }
__device__ __forceinline__ hp hmulc(hp a, uint32_t c) {
  __half2 ar = *reinterpret_cast<__half2*>(&a.r), ai = *reinterpret_cast<__half2*>(&a.i), cc = *reinterpret_cast<__half2*>(&c);
  __half2 orr = __hfma2(ar, __low2half2(cc), __hneg2(__hmul2(ai, __high2half2(cc))));
  __half2 oi = __hfma2(ar, __high2half2(cc), __hmul2(ai, __low2half2(cc)));
  hp o; o.r = *reinterpret_cast<uint32_t*>(&orr); o.i = *reinterpret_cast<uint32_t*>(&oi); return o;
}
__device__ __forceinline__ void sts_tile(uint32_t a, const hp* t) {
  sts128(a, t[0].r, t[1].r, t[2].r, t[3].r);
  sts128(a + 512, t[0].i, t[1].i, t[2].i, t[3].i);
}
template <int STEP> __device__ __forceinline__ void put2(uint32_t a0, uint32_t a1, uint32_t h, uint32_t sel) {
  const uint32_t x = __byte_perm(h, h, sel), y = x >> 16;
  sts16(a0, x); sts16(a0 + STEP * 4 + 2, x);
  sts16(a1, y); sts16(a1 + STEP * 4 + 2, y);
}

__device__ __forceinline__ void spare_work(const Params& p, const CUtensorMap* tmW1, int k, int tid) {
  const int lane = tid & 31;
  unsigned ep = 0;
  if (tid == 480) {
    ep = p.scr->epoch[128 + k] + 1;
    for (int i = 0; i < 8; i++) mbar_init(bar + 8 * i, i < 4 ? 1 : 12);
    asm volatile("fence.mbarrier_init.release.cluster;" ::: "memory");
    fence_async_smem();
  }
  __syncthreads();
  float a[2][4] = {{0.f, 0.f, 0.f, 0.f}, {0.f, 0.f, 0.f, 0.f}};
  if (tid >= 480) {
    if (elect1()) {
#pragma unroll 1
      for (int s = 0; s < 10; s++) {
        mbar_wait(bar + 8 * (4 + (s & 3)), ((s >> 2) & 1) ^ 1);
        mbar_expect(bar + 8 * (s & 3), 49152);
#pragma unroll 1
        for (int b = 0; b < 2; b++) tma3d(sb + (s & 3) * 49152 + b * 24576, tmW1, 0, s * 64, k * 6 + b * 3, bar + 8 * (s & 3));
      }
    }
    __syncwarp();
  } else if (tid < 384) {
    const uint32_t idn = (lane >> 3) == (lane & 3) ? ((lane & 4) ? 0x3f800000u : 0x3f80u) : 0u;
#pragma unroll 1
    for (int s = 0; s < 10; s++) {
      mbar_wait(bar + 8 * (s & 3), (s >> 2) & 1);
      const uint32_t ad = sb + (s & 3) * 49152 + (tid >> 6) * 8192 + (tid & 63) * 16;
#pragma unroll
      for (int i = 0; i < 8; i += 2) {
        const uint4 v = lds128(ad + i * 1024), w = lds128(ad + i * 1024 + 1024);
        bmma(a[0], v.x, v.y, w.x, w.y, idn, idn);
        bmma(a[1], v.z, v.w, w.z, w.w, idn, idn);
      }
      __syncwarp();
      if (lane == 0) mbar_arrive(bar + 8 * (4 + (s & 3)));
    }
    const int rho = (tid >> 3) & 7;
    const uint32_t ad = sb + 196608 + rho * 1536 + ((tid >> 6) * 8 + ((tid & 7) ^ rho)) * 32;
    sts128(ad, __float_as_uint(a[0][0]), __float_as_uint(a[0][1]), __float_as_uint(a[0][2]), __float_as_uint(a[0][3]));
    sts128(ad + 16, __float_as_uint(a[1][0]), __float_as_uint(a[1][1]), __float_as_uint(a[1][2]), __float_as_uint(a[1][3]));
  }
  __syncthreads();
  if (tid < 384) {
    float s = 0.f;
#pragma unroll
    for (int r = 0; r < 8; r++) s += __uint_as_float(lds32(sb + 196608 + r * 1536 + tid * 4));
    p.scr->cs[k * 384 + tid] = s;
  }
  __syncthreads();
  if (tid == 480) {
    publish(p.scr->cnt + C_CS * 32);
    p.scr->epoch[128 + k] = ep;
    poll_cnt(p.scr->cnt + C_LN * 32, ep * 128);
  }
}

__device__ __forceinline__ void load1(int s, const CUtensorMap* tmX, const CUtensorMap* tmW1, int rg1, int j1) {
  const uint32_t d = sb + (s & 3) * SLOT1, mb = bar + 8 * (B_FULL1 + s);
  mbar_expect(mb, SLOT1);
  tma2d(d, tmX, s * 64, rg1 * 128, mb);
  tma3d(d + 16384, tmW1, 0, s * 64, j1 * 3, mb);
}
__device__ __forceinline__ void load_x(uint32_t (&xv)[2][10], const __nv_bfloat16* xc, int rstep, int q) {
#pragma unroll
  for (int r = 0; r < 2; r++) {
    const uint4 a = __ldg((const uint4*)(xc + r * rstep) + q), b = __ldg((const uint4*)(xc + r * rstep) + 4 + q);
    const uint2 c = __ldg((const uint2*)(xc + r * rstep + 64) + q);
    xv[r][0] = a.x; xv[r][1] = a.y; xv[r][2] = a.z; xv[r][3] = a.w; xv[r][4] = b.x; xv[r][5] = b.y; xv[r][6] = b.z; xv[r][7] = b.w;
    xv[r][8] = c.x; xv[r][9] = c.y;
  }
}

template <bool USE_SMID>
__global__ void __launch_bounds__(512, 1)
fused_s4_ffn_kernel(const Params p, const __grid_constant__ CUtensorMap tmX, const __grid_constant__ CUtensorMap tmW1,
                    const __grid_constant__ CUtensorMap tmU, const __grid_constant__ CUtensorMap tmW2) {
  extern __shared__ __align__(1024) unsigned char smem_raw[];
  const int tid = threadIdx.x, lane = tid & 31;
  const int warp = __shfl_sync(0xffffffffu, tid >> 5, 0);
  const int g = lane >> 2, q = lane & 3;
  uint32_t sid;
  if (USE_SMID) asm("mov.u32 %0, %smid;" : "=r"(sid)); else sid = blockIdx.x;
  if (sid - 120u < 4u) { spare_work(p, &tmW1, sid - 120, tid); return; }
  const int wid = sid < 120 ? sid : sid - 4;
  unsigned* const cnt = p.scr->cnt;

  float kacc[5][4];
  const int kpart = (warp >= 5) + (warp >= 10), kch = warp - 5 * kpart;
  float dt, k0;
  uint32_t xv[2][10], xs[2], mw, pds;
  {
    uint32_t pa[6], pld;
    unsigned ep0;
    if (warp < 15) {
      const int ch = (wid >> 4) * 80 + frag_col((wid & 15) * 5 + kch);
      const int o = (ch * 3 + kpart) * 32 + lane;
      pa[0] = __ldg((const uint32_t*)p.are + o); pa[1] = __ldg((const uint32_t*)p.aim + o);
      pa[2] = __ldg((const uint32_t*)p.bre + o); pa[3] = __ldg((const uint32_t*)p.bim + o);
      pa[4] = __ldg((const uint32_t*)p.cre + o); pa[5] = __ldg((const uint32_t*)p.cim + o);
      pld = __ldg((const unsigned short*)p.logdt + ch);
      pds = __ldg((const unsigned short*)p.dskip + ch);
    } else {
      ep0 = p.scr->epoch[wid];
      if ((uint32_t)__cvta_generic_to_shared(smem_raw) != sb) __trap();
#pragma unroll 1
      for (int i = lane; i < B_NUM; i += 32) mbar_init(bar + 8 * i, i < B_FREE ? 1 : i < B_REL1 ? 4 : 8);
      asm volatile("fence.mbarrier_init.release.cluster;" ::: "memory");
      sts64(sb + OFF_ZERO + (lane & 15) * 8 + (lane >> 4) * 640, 0, 0);
      int gpc, i;
      if (sid < 64) { gpc = (sid & 15) >> 1; i = sid >> 4; }
      else if (sid < 120) { const int t = sid - 64; i = t / 14; gpc = 1 + ((t - i * 14) >> 1); i += 4; }
      else { gpc = 0; i = 4 + ((sid - 124) >> 1); }
      const int qi = ((0x52741630 >> (4 * i)) & 7) * 2 + (sid & 1);
      const int rg = 4 * (gpc >> 1) + (qi >> 2), jc = 4 * (gpc & 1) + (qi & 3);
      sts64(sb + OFF_EP + 8, rg, jc);
      __syncwarp();
      if (elect1()) {
#pragma unroll 1
        for (int s = 0; s < 4; s++) load1(s, &tmX, &tmW1, rg, jc);
        bulk_prefetch(p.w1 + wid * 5 * FF, 5 * FF * 2);
        bulk_prefetch(p.w2 + wid * 12 * DM, 12 * DM * 2);
        asm volatile("prefetch.tensormap [%0];\nprefetch.tensormap [%1];" ::"l"(&tmU), "l"(&tmW2) : "memory");
      }
    }
    if (warp >= 8) {
      const __nv_bfloat16* xr = p.x + (wid * 16 + ((g >> 1) << 2) + (g & 1)) * DM;
      load_x(xv, xr + (warp - 8) * 80, 2 * DM, q);
      xs[0] = __ldg((const uint32_t*)xr); xs[1] = __ldg((const uint32_t*)(xr + 2 * DM));
    }
#pragma unroll
    for (int j = 0; j < 5; j++) { kacc[j][0] = kacc[j][1] = kacc[j][2] = kacc[j][3] = 0.f; }
    float zr, th, zr1, th1;
    cf c, c1;
    const uint32_t ks = sb + OFF_KS + warp * 4096;
    if (warp < 15) {
      dt = rnd_bf(expf(bflo(pld)));
      c = cmul(cf{bflo(pa[4]), bflo(pa[5])}, cf{bflo(pa[2]), bflo(pa[3])});
      c1 = cmul(cf{bfhi(pa[4]), bfhi(pa[5])}, cf{bfhi(pa[2]), bfhi(pa[3])});
      mw = __reduce_max_sync(0xffffffffu, __float_as_uint(fmaxf(fmaxf(fabsf(c.r), fabsf(c.i)), fmaxf(fabsf(c1.r), fabsf(c1.i)))));
      mw = min(max(mw & 0x7f800000u, 20u << 23), 240u << 23);
      const float sc = __uint_as_float((259u << 23) - mw), dl2 = dt * 1.4426950408889634f;
      k0 = c.r + c1.r;
      zr = bflo(pa[0]) * dl2; th = bflo(pa[1]) * dt; zr1 = bfhi(pa[0]) * dl2; th1 = bfhi(pa[1]) * dt;
      c.r *= sc; c.i *= sc; c1.r *= sc; c1.i *= sc;
    }
    {
      const uint32_t ka = ks + (lane >> 3) * 512 + (lane & 7) * 16;
      const uint32_t kb = ks + ((lane >> 3) & 1) * 512 + ((lane >> 4) * 8 + (lane & 7)) * 16;
#pragma unroll 1
      for (int it = 0; it < 2; it++) {
        if (it == 1 && warp >= 8) {
          float sm[4] = {0.f, 0.f, 0.f, 0.f}, g0[4] = {0.f, 0.f, 0.f, 0.f}, g1[4] = {0.f, 0.f, 0.f, 0.f};
#pragma unroll
          for (int r = 0; r < 2; r++)
            xs[r] = fabsf(bflo(xs[r]) - bfhi(xs[r])) * 8.f < fabsf(bflo(xs[r])) ? __byte_perm(xs[r], 0, 0x1010) : 0u;
#pragma unroll
          for (int i = 0; i < 10; i += 2) {
            const uint32_t a0 = bsub(xv[0][i], xs[0]), a1 = bsub(xv[1][i], xs[1]), a2 = bsub(xv[0][i + 1], xs[0]), a3 = bsub(xv[1][i + 1], xs[1]);
            bmma(sm, a0, a1, a2, a3, 0x3f803f80u, 0x3f803f80u);
            bmma(g0, a0, a1, a2, a3, xv[0][i], xv[0][i + 1]);
            bmma(g1, a0, a1, a2, a3, xv[1][i], xv[1][i + 1]);
          }
          if (q == (g >> 1))
            sts128(sb + OFF_LNP + (warp - 8) * 128 + g * 16, __float_as_uint(sm[0]), __float_as_uint((g & 1) ? g0[1] : g0[0]),
                   __float_as_uint(sm[2]), __float_as_uint((g & 1) ? g1[3] : g1[2]));
          if (warp < 15) bar_arrive(1, 256);
        }
        if (warp == 15) continue;
        float m = ex2a(zr);
        const cf w1 = cf{m * __cosf(th), m * __sinf(th)};
        m = ex2a(zr * 8.f);
        const cf w8 = cf{m * __cosf(th * 8.f), m * __sinf(th * 8.f)};
        const cf w16 = csq(w8), w32 = csq(w16), w64 = csq(w32), w128 = csq(w64), w256 = csq(w128), w512 = csq(w256), w1024 = csq(w512);
        hp lo[8];
        lo[0] = hpack(cf{1.f, 0.f}, cf{w8.r, -w8.i});
        lo[1] = hmulc(lo[0], pack_h(w16.r, -w16.i));
        { const uint32_t k = pack_h(w32.r, -w32.i); lo[2] = hmulc(lo[0], k); lo[3] = hmulc(lo[1], k); }
        { const uint32_t k = pack_h(w64.r, -w64.i);
#pragma unroll
          for (int i = 0; i < 4; i++) lo[4 + i] = hmulc(lo[i], k); }
        const uint32_t st = ks + lane * 16;
        sts128(st, lo[0].r, lo[1].r, lo[2].r, lo[3].r);
        sts128(st + 512, lo[4].r, lo[5].r, lo[6].r, lo[7].r);
        sts128(st + 1024, lo[0].i, lo[1].i, lo[2].i, lo[3].i);
        sts128(st + 1536, lo[4].i, lo[5].i, lo[6].i, lo[7].i);
        const cf t1 = cmul(c, w1), t2 = cmul(t1, w1), t3 = cmul(t2, w1), t4 = cmul(t3, w1);
        const cf t5 = cmul(t4, w1), t6 = cmul(t5, w1), t7 = cmul(t6, w1), t8 = cmul(c, w8);
        hp T0[4], T1[4], T2[4], T3[4], T4[4];
        T0[0] = hpack(t4, t8); T0[1] = hpack(t2, t6); T0[2] = hpack(t1, t5); T0[3] = hpack(t3, t7);
        const uint32_t k128 = pack_h(w128.r, w128.i), k256 = pack_h(w256.r, w256.i), k512 = pack_h(w512.r, w512.i);
#pragma unroll
        for (int i = 0; i < 4; i++) T1[i] = hmulc(T0[i], k128);
        sts_tile(st + 2048, T0);
        sts_tile(st + 3072, T1);
        __syncwarp();
        uint32_t af[4][4];
#pragma unroll
        for (int mg = 0; mg < 4; mg++) ldsm4t(af[mg], ka + mg * 128);
#pragma unroll
        for (int j = 0; j < 2; j++)
#pragma unroll
          for (int mg = 0; mg < 4; mg += 2) {
            uint32_t b[4];
            ldsm4t(b, kb + 2048 + j * 1024 + mg * 128);
            hmma(kacc[j], af[mg][0], af[mg][1], af[mg][2], af[mg][3], b[0], b[1]);
            hmma(kacc[j], af[mg + 1][0], af[mg + 1][1], af[mg + 1][2], af[mg + 1][3], b[2], b[3]);
          }
        T2[0] = hmulc(T0[0], k256); T2[1] = hmulc(T0[1], k256); T2[2] = hmulc(T1[0], k256); T2[3] = hmulc(T1[1], k256);
        T3[0] = hmulc(T0[0], k512); T3[1] = hmulc(T1[0], k512); T3[2] = hmulc(T2[0], k512); T3[3] = hmulc(T2[2], k512);
        { const cf u0 = cmul(t8, w1024), u1 = cmul(u0, w128);
          T4[0] = hpack(u0, u1); T4[1] = hmulc(T4[0], k256); T4[2] = hmulc(T4[0], k512); T4[3] = hmulc(T4[1], k512); }
        __syncwarp();
        sts_tile(st, T2);
        sts_tile(st + 1024, T3);
        sts_tile(st + 2048, T4);
        __syncwarp();
#pragma unroll
        for (int j = 0; j < 3; j++)
#pragma unroll
          for (int mg = 0; mg < 4; mg += 2) {
            uint32_t b[4];
            ldsm4t(b, kb + j * 1024 + mg * 128);
            hmma(kacc[2 + j], af[mg][0], af[mg][1], af[mg][2], af[mg][3], b[0], b[1]);
            hmma(kacc[2 + j], af[mg + 1][0], af[mg + 1][1], af[mg + 1][2], af[mg + 1][3], b[2], b[3]);
          }
        __syncwarp();
        zr = zr1; th = th1; c = c1;
      }
    }
    if (warp < 10) {
#pragma unroll
      for (int j = 0; j < 5; j++)
        sts128(ks + j * 512 + lane * 16, __float_as_uint(kacc[j][0]), __float_as_uint(kacc[j][1]), __float_as_uint(kacc[j][2]), __float_as_uint(kacc[j][3]));
      sts64(ks + 2560 + lane * 8, __float_as_uint(k0), mw);
    } else if (warp == 15) {
      if (lane == 0) { p.scr->epoch[wid] = ep0 + 1; sts32(sb + OFF_EP, ep0 + 1); }
      bar_sync(1, 256);
      float s1 = 0.f, s2 = 0.f;
#pragma unroll
      for (int w = 0; w < 8; w++) {
        const uint2 v = lds64(sb + OFF_LNP + w * 128 + g * 16 + (q & 1) * 8);
        s1 += __uint_as_float(v.x); s2 += __uint_as_float(v.y);
      }
      const float md = s1 * (1.f / DM), mean = bflo((q & 1) ? xs[1] : xs[0]) + md;
      const float var = fmaxf(fmaf(-md, mean, s2 * (1.f / DM)), 0.f);
      const float m = rnd_bf(mean);
      float sd, ri;
      asm("sqrt.approx.f32 %0, %1;" : "=f"(sd) : "f"(rnd_bf(rnd_bf(var) + 1e-5f)));
      asm("rcp.approx.f32 %0, %1;" : "=f"(ri) : "f"(rnd_bf(sd)));
      if (q < 2) {
        p.scr->stats[wid * 16 + ((g >> 1) << 2) + (g & 1) + 2 * q] = make_float2(-m, 0.5f * ri);
        sts64(sb + OFF_STAT + g * 16 + q * 8, __float_as_uint(-m * ri), __float_as_uint(ri));
      }
    }
  }
  __syncthreads();

  if (warp < 8) {
    float acc[96];
    const uint32_t alo = ((sb >> 4) | (1 << 16)) + (warp >> 2) * 512;
#pragma unroll 1
    for (int s = 0; s < 10; s++) {
      const uint32_t so = (s & 3) * (SLOT1 >> 4);
      mbar_wait(bar + 8 * (B_FULL1 + s), 0);
      wg_fence();
#pragma unroll
      for (int kk = 0; kk < 4; kk++)
        wgmma_n192(acc, dsc(alo + so + kk * 2, 0x40000040u), dsc((((sb + 16384) >> 4) | (512 << 16)) + so + kk * 128, 0x40000040u), (s | kk) != 0);
      wg_commit();
      wg_wait<1>();
      if (lane == 0) mbar_arrive(bar + 8 * (B_REL1 + s));
    }
    wg_wait<0>();
    bar_arrive(14, 512);
    mbar_wait(bar + 8 * B_EPI, 0);
    const uint2 s0 = lds64(sb + OFF_STAT + (warp * 16 + g) * 8), s1 = lds64(sb + OFF_STAT + (warp * 16 + g + 8) * 8);
    const float nm0 = __uint_as_float(s0.x), r0 = __uint_as_float(s0.y), nm1 = __uint_as_float(s1.x), r1 = __uint_as_float(s1.y);
    const uint2 rj = lds64(sb + OFF_EP + 8);
    const int rg1 = rj.x, j1 = rj.y;
    uint4* hd = p.scr->h + (rg1 * 24 + j1) * 1024 + warp * 128 + q * 8 + g;
#pragma unroll
    for (int grp = 0; grp < 6; grp++) {
      uint32_t o0[4], o1[4];
#pragma unroll
      for (int tl = 0; tl < 4; tl++) {
        const int nt = grp * 4 + tl;
        const uint2 cs = lds64(sb + OFF_CS + (nt * 8 + 2 * q) * 4);
        const float ca = __uint_as_float(cs.x), cb = __uint_as_float(cs.y);
        const float a = fmaf(nm0, ca, acc[4 * nt]) * r0, b = fmaf(nm0, cb, acc[4 * nt + 1]) * r0;
        const float c = fmaf(nm1, ca, acc[4 * nt + 2]) * r1, d = fmaf(nm1, cb, acc[4 * nt + 3]) * r1;
        o0[tl] = pack_bf(fmaf(a, tanha(a), a), fmaf(b, tanha(b), b));
        o1[tl] = pack_bf(fmaf(c, tanha(c), c), fmaf(d, tanha(d), d));
      }
      uint4* dst = hd + (grp >> 1) * 8192 + (grp & 1) * 32;
      dst[0] = make_uint4(o0[0], o0[1], o0[2], o0[3]);
      dst[64] = make_uint4(o1[0], o1[1], o1[2], o1[3]);
      if (PACE_NS) __nanosleep(PACE_NS);
      if (grp == 1) {
        if (warp == 7) { bar_sync(2, 448); if (lane == 0) publish(cnt + C_H0 * 32); __syncwarp(); }
        else bar_arrive(2, 448);
      }
    }
    if (warp == 6) { bar_sync(11, 256); if (lane == 0) publish(cnt + (C_H1 + rg1) * 32); __syncwarp(); }
    else bar_arrive(11, 256);
    const int go = (rg1 * 128 + warp * 16 + g) * DM + j1 * 80;
    load_x(xv, p.x + go, 8 * DM, q);
    float acc2[40];
    mbar_wait(bar + 8 * B_MMA, 0);
    {
      const uint32_t al2 = ((sb >> 4) | (8 << 16)) + (warp >> 2) * 512;
      uint32_t so = 0;
#pragma unroll 1
      for (int s = 0; s < 24; s++) {
        mbar_wait(bar + 8 * (B_FULL2 + s), 0);
        wg_fence();
#pragma unroll
        for (int kk = 0; kk < 4; kk++)
          wgmma_n80(acc2, dsc(al2 + so + kk * 16, 64), dsc((((sb + 16384) >> 4) | (80 << 16)) + so + kk * 160, 8), (s | kk) != 0);
        wg_commit();
        so = so == (NS2 - 1) * (SLOT2 >> 4) ? 0 : so + (SLOT2 >> 4);
        wg_wait<1>();
        if (lane == 0) mbar_arrive(bar + 8 * (B_REL2 + s));
      }
    }
    mbar_wait(bar + 8 * B_SFULL, 0);
    uint32_t sv[5][4];
    {
      const int i = lane & 7, mi = lane >> 3;
      const uint32_t a = sb + OFF_U + ((mi >> 1) * 8 + i) * 256 + (((2 * warp + (mi & 1)) ^ i) << 4);
#pragma unroll
      for (int k = 0; k < 5; k++) ldsm4t(sv[k], a + k * 4096);
    }
    wg_wait<0>();
#pragma unroll
    for (int hh = 0; hh < 2; hh++) {
      uint32_t o[10];
#pragma unroll
      for (int tl = 0; tl < 10; tl++) {
        const uint32_t xw = xv[hh][tl];
        const uint32_t sw = sv[tl >> 1][(tl & 1) * 2 + hh];
        const float a = acc2[4 * tl + 2 * hh], b = acc2[4 * tl + 2 * hh + 1];
        o[tl] = pack_bf(fmaf(bflo(sw), fmaf(a, tanha(a), a), bflo(xw)), fmaf(bfhi(sw), fmaf(b, tanha(b), b), bfhi(xw)));
      }
      __nv_bfloat16* op = p.out + go + hh * 8 * DM;
      ((uint4*)op)[q] = make_uint4(o[0], o[1], o[2], o[3]);
      ((uint4*)op)[4 + q] = make_uint4(o[4], o[5], o[6], o[7]);
      ((uint2*)(op + 64))[q] = make_uint2(o[8], o[9]);
    }
  } else {
    const int cw = warp - 8;
    const uint4 erj = lds128(sb + OFF_EP);
    const unsigned ep = erj.x;
    const int rg1 = erj.z, j1 = erj.w;
    {
      const uint4 st = lds128(sb + OFF_STAT + g * 16);
      const float n0 = __uint_as_float(st.x), r0 = __uint_as_float(st.y), n1 = __uint_as_float(st.z), r1 = __uint_as_float(st.w);
      const int up = upos(2 * wid);
      uint2* dst = (uint2*)p.scr->uT + ((up >> 1) * DM + cw * 80) * 4 + (lane ^ ((up & 1) << 1));
#pragma unroll
      for (int i = 0; i < 10; i++) {
        const uint32_t a = movm(pack_h(fmaf(bflo(xv[0][i]), r0, n0), fmaf(bfhi(xv[0][i]), r0, n0)));
        const uint32_t b = movm(pack_h(fmaf(bflo(xv[1][i]), r1, n1), fmaf(bfhi(xv[1][i]), r1, n1)));
        dst[i * 32] = make_uint2(a, b);
      }
    }
    if (warp == 9) {
      bar_sync(12, 256);
      if (elect1()) {
        publish(cnt + C_LN * 32);
        poll_cnt(cnt + C_CS * 32, ep * 4);
        bulk_g2s(sb + OFF_CS, p.scr->cs + j1 * 192, 768, bar + 8 * B_EPI);
      }
      __syncwarp();
    } else bar_arrive(12, 256);
    if (warp == 15) {
      if (elect1()) {
#pragma unroll 1
        for (int s = 4; s < 10; s++) {
          mbar_wait(bar + 8 * (B_REL1 + s - 3), 0);
          load1(s, &tmX, &tmW1, rg1, j1);
        }
      }
      __syncwarp();
    }
    if (warp >= 10 && warp < 15) {
      const uint32_t pb = sb + OFF_P + kch * 3072, pk = sb + OFF_KS + kch * 4096;
      const uint2 e0 = lds64(pk + 2560 + lane * 8), e1 = lds64(pk + 5 * 4096 + 2560 + lane * 8);
      const float dsk = bflo(pds);
      uint32_t kex = __float_as_uint(fmaxf(__uint_as_float(max(max(e0.y, e1.y), mw)) * dt, fabsf(dsk) * (1.f / 256.f))) >> 23;
      kex = min(max(kex, 20u), 240u);
      const float s2 = __uint_as_float((258 - kex) << 23), sd = s2 * dt * (1.f / 32.f);
      const float f0 = __uint_as_float(e0.y) * sd, f1 = __uint_as_float(e1.y) * sd, f2 = __uint_as_float(mw) * sd;
      k0 += __uint_as_float(e0.x) + __uint_as_float(e1.x);
#pragma unroll
      for (int o = 16; o; o >>= 1) k0 += __shfl_xor_sync(0xffffffffu, k0, o);
      const float k0n = fmaf(k0, dt, dsk) * s2;
      uint32_t h[5][2];
#pragma unroll
      for (int j = 0; j < 5; j++) {
        const uint4 a = lds128(pk + j * 512 + lane * 16), b = lds128(pk + 5 * 4096 + j * 512 + lane * 16);
#pragma unroll
        for (int e = 0; e < 4; e++) kacc[j][e] = fmaf(__uint_as_float((&a.x)[e]), f0, fmaf(__uint_as_float((&b.x)[e]), f1, kacc[j][e] * f2));
        if (j == 1) {
          const float k256 = __shfl_sync(0xffffffffu, kacc[1][3], 28);
          if (lane == 31) kacc[1][3] -= k256;
        }
        if (j == 2 || j == 3) { h[j][0] = pack_h(kacc[j][0], kacc[j][2]); h[j][1] = pack_h(kacc[j][1], kacc[j][3]); }
        else { h[j][0] = pack_h(kacc[j][0], kacc[j][1]); h[j][1] = pack_h(kacc[j][2], kacc[j][3]); }
      }
      fence_async_smem();
      bar_arrive(13, 192);
#pragma unroll
      for (int i = 0; i < 6; i++) sts128(pb + i * 512 + lane * 16, 0, 0, 0, 0);
      __syncwarp();
      {
        const int sw = g >> 2;
        const uint32_t sel = sw ? 0x1032 : 0x3210;
        const uint32_t a = pb + (P0 + 8 * g + ((0x3124 >> (4 * q)) & 7)) * 4, a0 = a + sw * 16, a1 = a + 16 - sw * 16;
        put2<1>(a0, a1, h[0][0], sel);
        put2<1>(a0 + 256, a1 + 256, h[0][1], sel);
        put2<1>(a0 + 512, a1 + 512, h[1][0], sel);
        put2<1>(lane == 28 ? pb + PB1 * 4 : a0 + 768, a1 + 768, h[1][1], sel);
      }
      {
        const int sw = q >> 1;
        const uint32_t sel = sw ? 0x1032 : 0x3210;
        uint32_t a = pb + (((q & 1) ? PA1 : PB1 + 1) + 32 * sw + 2 * g) * 4;
        put2<1>(a + sw * 64, a + 64 - sw * 64, h[2][0], sel);
        put2<1>(a + 4 + sw * 64, a + 68 - sw * 64, h[2][1], sel);
        a = pb + (PA2 + g + 16 * q) * 4;
        put2<2>(a + sw * 32, a + 32 - sw * 32, h[3][0], sel);
        put2<2>(a + (PB2 - PA2) * 4 + sw * 32, a + (PB2 - PA2) * 4 + 32 - sw * 32, h[3][1], sel);
        a = pb + (((g & 1) ? PB3 : PA3) + (g >> 1) + 16 * q) * 4;
        const uint32_t hx = sw ? h[4][1] : h[4][0], hy = sw ? h[4][0] : h[4][1];
        put2<1>(a + sw * 16, a + 32 + sw * 16, hx, 0x3210);
        put2<1>(a + 16 - sw * 16, a + 48 - sw * 16, hy, 0x3210);
      }
      if (lane == 30) put2<1>(pb + P0 * 4, pb + (PA1 + 64) * 4, pack_h(k0n, kacc[2][3]), 0x3210);
      if (lane == 31) sts64(sb + OFF_CHC + kch * 8, (kex - 4) * 0x00800080u, __byte_perm(h[3][1], 0, 0x3232));
    }
    if (warp == 8) {
      bar_sync(13, 192);
      if (elect1()) {
        mbar_expect(bar + 8 * B_W2, 96 * 176);
        tma5d(sb + OFF_W2S, &tmW2, (wid & 7) * 80, (wid >> 3) * 3, bar + 8 * B_W2);
        mbar_expect(bar + 8 * B_UFULL, 20480);
        mbar_expect(bar + 8 * B_EPI, 1024 + 768);
        poll_cnt(cnt + C_LN * 32, ep * 128);
        tma2d(sb + OFF_U, &tmU, wid * 80, 0, bar + 8 * B_UFULL);
        bulk_g2s(sb + OFF_STAT, p.scr->stats + rg1 * 128, 1024, bar + 8 * B_EPI);
      }
      __syncwarp();
      bar_arrive(15, 224);
    }
    if (warp >= 9 && warp < 15) {
      const int uu = (warp - 9) >> 1, G = (warp - 9) & 1;
      const int grp = (wid >> 3) * 3 + uu, jj = grp / 6, rem = grp - jj * 6;
      const uint32_t a = sb + OFF_W2S + (uu * 32 + lane) * 176;
      uint4* dst = p.scr->w2p + ((wid & 7) * 24 + 8 * (rem >> 1) + jj) * 640 + ((rem & 1) * 4 + (lane >> 3)) * 80 + (lane & 7);
      mbar_wait(bar + 8 * B_W2, 0);
      const uint4 wv[4] = {lds128(a + G * 64), lds128(a + G * 64 + 16), lds128(a + G * 64 + 32), lds128(a + G * 64 + 48)};
      const uint4 t0 = lds128(a + 128), t1 = lds128(a + 144);
      uint32_t w[20];
#pragma unroll
      for (int i = 0; i < 16; i++) w[i] = bmul((&wv[i >> 2].x)[i & 3], 0x3f003f00u);
      w[16] = bmul(G ? t0.y : t0.x, 0x3f003f00u); w[17] = bmul(G ? t0.w : t0.z, 0x3f003f00u);
      w[18] = bmul(G ? t1.y : t1.x, 0x3f003f00u); w[19] = bmul(G ? t1.w : t1.z, 0x3f003f00u);
      bar_sync(15, 224);
#pragma unroll
      for (int i = 0; i < 4; i++) dst[G * 32 + 8 * i] = make_uint4(w[i], w[4 + i], w[8 + i], w[12 + i]);
      dst[64 + G * 8] = make_uint4(w[16], w[17], w[18], w[19]);
      bar_arrive(2, 448);
      if (warp == 12) bar_arrive(3, 64);
    } else if (warp == 15) bar_sync(3, 64);
    mbar_wait(bar + 8 * B_UFULL, 0);
#pragma unroll 1
    for (int ch = (cw >> 2) * 4; ch != 4 + (cw >> 2); ch = ch == 4 ? 1 : ch + 2) {
      if (ch < 4) mbar_wait(bar + 8 * (B_REL1 + (ch ? 8 : 7)), 0);
      const int qt = (cw + ch) & 3, j = qt * 32 + lane;
      const uint32_t ub = sb + OFF_U + ch * 32, zb = sb + OFF_Z + ch * ZSZ;
      uint32_t w_[20], o_[20], d_[20], b3_[20];
      uint32_t *w = w_ + 8, *o = o_ + 8, *d = d_ + 8, *b3 = b3_ + 8;
      {
        const uint32_t am = j > 0 ? ub + uoff(upos(2 * j - 2)) : sb + OFF_ZERO, a0 = ub + uoff(upos(2 * j));
        const uint2 a = lds64(am + 8);
        const uint4 b = lds128(am ^ 16), c = lds128(a0), e = lds128(a0 ^ 16);
        w[8] = lds32(ub + uoff(upos((2 * j + 2) & 255)));
        w[-6] = a.x; w[-5] = a.y; w[-4] = b.x; w[-3] = b.y; w[-2] = b.z; w[-1] = b.w;
        w[0] = c.x; w[1] = c.y; w[2] = c.z; w[3] = c.w; w[4] = e.x; w[5] = e.y; w[6] = e.z; w[7] = e.w;
      }
#pragma unroll
      for (int i = -1; i <= 7; i++) o[i] = odd_pair(w[i], w[i + 1]);
#pragma unroll
      for (int i = 0; i <= 7; i++) { d[i] = hadd(w[i], o[i]); b3[i] = hadd(d[i], o[i - 1]); }
      if (j < 112) {
        const int gr = j >> 1;
        const uint32_t a1 = zb + ZA1 + 128 + (gr ^ ((gr >> 2) & 1)) * 64 + ((gr >> 1) & 3) * 16 + (j & 1) * 8;
#pragma unroll
        for (int pp = 0; pp < 4; pp++) {
          const uint32_t sel = (pp & 1) ? 0x7632 : 0x5410;
          const int k = pp >> 1;
          sts64(a1 ^ (pp * 16), __byte_perm(w[k - 1], w[k + 1], sel), __byte_perm(w[k + 3], w[k + 5], sel));
          sts64((a1 ^ (pp * 16)) + (ZB1 - ZA1), __byte_perm(b3[k], b3[k + 2], sel), __byte_perm(b3[k + 4], b3[k + 6], sel));
        }
      } else if (j >= 120) {
        sts128(zb + ZA1 + ((lane >> 2) & 1) * (ZB1 - ZA1) + (3 - q) * 16, 0, 0, 0, j == 127 ? w[8] << 16 : 0u);
      }
      if (qt < 3) {
        uint32_t e_[20], b5_[20];
        uint32_t *e = e_ + 8, *b5 = b5_ + 8;
#pragma unroll
        for (int i = -6; i <= -2; i++) o[i] = odd_pair(w[i], w[i + 1]);
#pragma unroll
        for (int i = -6; i <= -1; i++) d[i] = hadd(w[i], o[i]);
#pragma unroll
        for (int i = -5; i <= -1; i++) b3[i] = hadd(d[i], o[i - 1]);
#pragma unroll
        for (int i = -5; i <= 4; i++) e[i] = hadd(d[i - 1], d[i]);
#pragma unroll
        for (int i = -4; i <= 4; i++) b5[i] = hadd(e[i], w[i + 1]);
        const uint32_t a2 = zb + ((j >> 3) * 16 + (j & 7)) * 16;
        sts128(a2 + ZA2, b3[-2], b3[-1], b3[0], b3[1]);
        sts128(a2 + ZA2 + 128, b3[2], b3[3], b3[4], b3[5]);
        sts128(a2 + ZB2, b5[-4], b5[-3], b5[-2], b5[-1]);
        sts128(a2 + ZB2 + 128, b5[0], b5[1], b5[2], b5[3]);
        if (qt < 2) {
          sts128(a2 + ZS, d[-2], d[-1], d[0], d[1]);
          sts128(a2 + ZS + 128, d[2], d[3], d[4], d[5]);
          uint32_t b7[8], b9[8];
#pragma unroll
          for (int i = -4; i <= 3; i++) { b7[i + 4] = hadd(b3[i - 1], e[i + 1]); b9[i + 4] = hadd(e[i - 1], b5[i + 1]); }
          const uint32_t a3 = zb + ((j >> 4) * 32 + (j & 15)) * 16;
          sts128(a3 + ZA3, b7[0], b7[1], b7[2], b7[3]);
          sts128(a3 + ZA3 + 256, b7[4], b7[5], b7[6], b7[7]);
          sts128(a3 + ZB3 + 256, b9[0], b9[1], b9[2], b9[3]);
          if (j < 63) sts128(a3 + ZB3 + ((j & 15) == 15 ? 272 : 16), b9[4], b9[5], b9[6], b9[7]);
          else sts128(zb + ZB3, 0, 0, 0, 0);
        }
      }
    }
    const int wg = warp >> 2, role = (warp + 2 * wg) & 3;
    bar_sync(14, 512);
    const uint32_t nz = lds32(sb + OFF_ZERO) | 0x80000000u;
#pragma unroll 1
    for (int ch = wg - 2; ch < 5; ch += 2) {
      const uint32_t ub = sb + OFF_U + ch * 32, zb = sb + OFF_Z + ch * ZSZ, pb = sb + OFF_P + ch * 3072;
      const uint2 chc = lds64(sb + OFF_CHC + ch * 8);
      const int tid = lds32(sb + OFF_ZERO + 20) + threadIdx.x;
      const int lane = tid & 31, g = lane >> 2, q = lane & 3;
      const uint32_t pa = pb + (g - 2 * q) * 4;
      if (role < 2) {
        float acc[8][4];
#pragma unroll
        for (int r = 0; r < 8; r++) { acc[r][0] = acc[r][1] = acc[r][2] = acc[r][3] = 0.f; }
        float fix = 0.f;
        if (role == 1 && lane == 28) {
          const uint32_t k = lds32(pb + PB1 * 4), u0 = lds32(ub);
          fix = __low2float(*reinterpret_cast<const __half2*>(&k)) * __low2float(*reinterpret_cast<const __half2*>(&u0));
        }
        uint32_t ga[3][2];
#pragma unroll
        for (int gm = 0; gm < 3; gm++) {
          const int hb = 2 * (lane & 7) + role - 2 + gm, l3 = ((lane >> 3) ^ (hb >> 1)) & 7;
          ga[gm][0] = hb < 0 ? sb + OFF_ZERO + ((l3 * 16 + ch * 32) & 127) : ub + hb * 1280 + uoff(l3);
          ga[gm][1] = hb < 0 ? ga[gm][0] ^ 64 : ub + hb * 1280 + uoff(l3 ^ 4);
        }
        uint32_t b[12][4], A[17][4];
#pragma unroll
        for (int i = 11; i >= 8; i--) ldsm4(b[i], (ga[2][i & 1] ^ (((i >> 1) & 1) * 16)) + ((i >> 1) & 1) * 640);
        A[0][0] = lds32(pa + P0 * 4); A[0][1] = lds32(pa + P0 * 4 + 32); A[0][2] = lds32(sb + OFF_ZERO + 4);
#pragma unroll
        for (int m = 0; m <= 16; m++) {
          if (m < 16) {
            A[m + 1][0] = lds32(pa + P0 * 4 + (2 * m + 2) * 32);
            A[m + 1][1] = m < 15 ? lds32(pa + P0 * 4 + (2 * m + 3) * 32) : lds32(sb + OFF_ZERO + 8);
          }
          if ((m & 1) == 0 && m < 16) {
            const int i = 7 - (m >> 1);
            ldsm4(b[i], (ga[i >> 2][i & 1] ^ (((i >> 1) & 1) * 16)) + ((i >> 1) & 1) * 640);
          }
          A[m][3] = dup(A[m][0], nz);
          if (m < 16) A[m + 1][2] = dup(A[m][1], nz);
#pragma unroll
          for (int r = 7; r >= 0; r--) {
            const int f = 16 + r - m;
            hmma(acc[r], A[m][0], A[m][1], A[m][2], A[m][3], b[f >> 1][(f & 1) * 2], b[f >> 1][(f & 1) * 2 + 1]);
          }
        }
        acc[7][2] += fix;
        bar_sync(7 + wg, 64);
#pragma unroll
        for (int i = 3; i >= 0; i--)
          stsm4t((ga[2][i & 1] ^ (((i >> 1) & 1) * 16)) + ((i >> 1) & 1) * 640, pack_bf(acc[2 * i][0], acc[2 * i][1]), pack_bf(acc[2 * i][2], acc[2 * i][3]),
                 pack_bf(acc[2 * i + 1][0], acc[2 * i + 1][1]), pack_bf(acc[2 * i + 1][2], acc[2 * i + 1][3]));
      } else if (role == 2) {
        float acc[14][4];
#pragma unroll
        for (int r = 0; r < 14; r++) { acc[r][0] = acc[r][1] = acc[r][2] = acc[r][3] = 0.f; }
        const int mi = lane >> 3, hf = (lane >> 2) & 1;
        const uint32_t ze = zb + ZA1 + 128 - 512 + hf * 1792 + (mi ^ hf) * 64 + ((q ^ (mi >> 1) ^ (hf * 2)) << 4);
        const uint32_t zo = ze ^ 96;
#pragma unroll
        for (int arr = 0; arr < 2; arr++) {
          uint32_t A[5][4];
#pragma unroll
          for (int m = 0; m < 5; m++) {
            A[m][0] = lds32(pa + (arr ? PB1 : PA1) * 4 + m * 64);
            A[m][1] = m < 4 ? lds32(pa + (arr ? PB1 : PA1) * 4 + m * 64 + 32) : lds32(sb + OFF_ZERO + 4 + arr * 8);
          }
#pragma unroll
          for (int m = 4; m >= 1; m--) { A[m][2] = dup(A[m - 1][1], nz); A[m][3] = dup(A[m][0], nz); }
          A[0][2] = lds32(sb + OFF_ZERO + 8 + arr * 8); A[0][3] = dup(A[0][0], nz);
#pragma unroll
          for (int ip = 0; ip < 9; ip++) {
            uint32_t b[4];
            uint32_t ad = ((ip & 1) ? zo : ze) + ip * 256 + arr * (ZB1 - ZA1);
            if (ip < 2 && hf == 0 && (ip == 0 || mi != 3)) ad = sb + OFF_ZERO + (ad & 127);
            ldsm4(b, ad);
#pragma unroll
            for (int hh = 0; hh < 2; hh++)
#pragma unroll
              for (int m = 0; m < 5; m++) {
                const int i = 2 * ip + hh - 4 + m;
                if (i >= 0 && i < 14) hmma(acc[i], A[m][0], A[m][1], A[m][2], A[m][3], b[2 * hh], b[2 * hh + 1]);
              }
          }
        }
        const uint32_t a = zb + ZA1 + ((lane ^ (mi & 1)) << 4);
#pragma unroll
        for (int i = 0; i < 7; i++)
          stsm4(a + i * 512, pack_bf(acc[2 * i][0], acc[2 * i][1]), pack_bf(acc[2 * i][2], acc[2 * i][3]),
                pack_bf(acc[2 * i + 1][0], acc[2 * i + 1][1]), pack_bf(acc[2 * i + 1][2], acc[2 * i + 1][3]));
      } else {
        float acc[12][4];
        const uint32_t za = zb + lane * 16;
        {
          float d[4][2][4];
#pragma unroll
          for (int r = 0; r < 8; r++) { d[r >> 1][r & 1][0] = d[r >> 1][r & 1][1] = d[r >> 1][r & 1][2] = d[r >> 1][r & 1][3] = 0.f; }
#pragma unroll
          for (int arr = 0; arr < 2; arr++) {
            uint32_t A[4][4];
#pragma unroll
            for (int m = 0; m < 4; m++) { A[m][0] = lds32(pa + (arr ? PB3 : PA3) * 4 + m * 64); A[m][1] = lds32(pa + (arr ? PB3 : PA3) * 4 + m * 64 + 32); }
#pragma unroll
            for (int m = 0; m < 4; m++) { A[m][2] = m ? dup(A[m - 1][1], nz) : lds32(sb + OFF_ZERO + 4 + arr * 4); A[m][3] = dup(A[m][0], nz); }
#pragma unroll
            for (int io = 0; io < 4; io++) {
              uint32_t b[4];
              ldsm4t(b, za + (arr ? ZB3 : ZA3) + io * 512);
#pragma unroll
              for (int m = 0; m + io < 4; m++) {
                hmma(d[io + m][0], A[m][0], A[m][1], A[m][2], A[m][3], b[0], b[1]);
                hmma(d[io + m][1], A[m][0], A[m][1], A[m][2], A[m][3], b[2], b[3]);
              }
            }
          }
#pragma unroll
          for (int r = 0; r < 4; r++) {
            acc[r][0] = acc[r][1] = acc[r][2] = acc[r][3] = 0.f;
            acc[4 + 2 * r][0] = d[r][0][0]; acc[4 + 2 * r][1] = d[r][0][1]; acc[4 + 2 * r][2] = d[r][1][0]; acc[4 + 2 * r][3] = d[r][1][1];
            acc[5 + 2 * r][0] = d[r][0][2]; acc[5 + 2 * r][1] = d[r][0][3]; acc[5 + 2 * r][2] = d[r][1][2]; acc[5 + 2 * r][3] = d[r][1][3];
          }
        }
        {
          const uint32_t k0 = (g >> 1) == q ? (chc.y & ((g & 1) ? 0xffff0000u : 0xffffu)) : 0u;
          const uint32_t k1 = lds32(sb + OFF_ZERO + 12), k2 = lds32(sb + OFF_ZERO + 16), k3 = dup(k0, nz);
#pragma unroll
          for (int ip = 0; ip < 4; ip++) {
            uint32_t b[4];
            ldsm4t(b, za + ZS + ip * 512);
            hmma(acc[4 + 2 * ip], k0, k1, k2, k3, b[0], b[1]);
            hmma(acc[5 + 2 * ip], k0, k1, k2, k3, b[2], b[3]);
          }
        }
        const uint32_t pa2 = pb + (2 * g - 4 * q) * 4;
#pragma unroll
        for (int arr = 0; arr < 2; arr++) {
          uint32_t A[5][4];
#pragma unroll
          for (int m = 0; m < 5; m++) {
            const uint2 v = lds64(pa2 + (arr ? PB2 : PA2) * 4 + m * 64);
            A[m][0] = v.x; A[m][1] = v.y; A[m][2] = lds32(pa2 + (arr ? PB2 : PA2) * 4 + m * 64 - 4);
          }
#pragma unroll
          for (int m = 0; m < 5; m++) A[m][3] = dup(A[m][0], nz);
#pragma unroll
          for (int ip = 0; ip < 6; ip++) {
            uint32_t b[4];
            ldsm4t(b, za + (arr ? ZB2 : ZA2) + ip * 512);
#pragma unroll
            for (int hh = 0; hh < 2; hh++)
#pragma unroll
              for (int m = 0; m < 5; m++) {
                const int i = 2 * ip + hh + m;
                if (i < 12) hmma(acc[i], A[m][0], A[m][1], A[m][2], A[m][3], b[2 * hh], b[2 * hh + 1]);
              }
          }
        }
        const uint32_t a = zb + ZA2 + ((lane ^ ((lane >> 1) & 4)) << 4);
#pragma unroll
        for (int i = 0; i < 6; i++)
          stsm4(a + i * 512, pack_bf(acc[2 * i][0], acc[2 * i][1]), pack_bf(acc[2 * i][2], acc[2 * i][3]),
                pack_bf(acc[2 * i + 1][0], acc[2 * i + 1][1]), pack_bf(acc[2 * i + 1][2], acc[2 * i + 1][3]));
      }
      bar_sync(3 + wg, 128);
      if (ch == 4 && (tid & 127) == 0) mbar_arrive(bar + 8 * B_MMA);
      {
        const int row = (wid & 15) * 5 + ch;
        const int c = tid & 127, c1 = c < 112 ? c + 32 : c - 112, c2 = c < 112 ? c + 144 : c - 96;
        const uint32_t zr = sb + OFF_ZERO + (lane & 7) * 16;
        const uint32_t a1 = c < 112 ? zb + ZA1 + ((2 * c) ^ ((c >> 2) & 1)) * 16 : zr;
        const uint32_t a2 = zb + ZA2 + ((c & ~15) - 32 + ((((c >> 1) & 7) + (c & 1) * 8) ^ ((c & 1) * 4))) * 16;
        const uint4 v0 = lds128(ub + uoff(upos(c1))), u0 = lds128(ub + uoff(upos(c2)));
        const uint4 y0 = lds128(a1), y1 = lds128(a1 ^ 16);
        const uint4 v2 = lds128(c1 >= 64 ? a2 : zr), u2 = lds128(c < 112 ? a2 + 112 * 16 : zr);
        uint4* dst = p.scr->sT + ((wid >> 4) * 16 * 80 + row) * 16 + ((c & 15) ^ (row & 7));
        const uint4 v = make_uint4(bmul(badd(badd(y0.x, v2.x), v0.x), chc.x), bmul(badd(badd(y0.y, v2.y), v0.y), chc.x),
                                   bmul(badd(badd(y1.x, v2.z), v0.z), chc.x), bmul(badd(badd(y1.y, v2.w), v0.w), chc.x));
        const uint4 u = make_uint4(bmul(badd(badd(y0.z, u2.x), u0.x), chc.x), bmul(badd(badd(y0.w, u2.y), u0.y), chc.x),
                                   bmul(badd(badd(y1.z, u2.z), u0.z), chc.x), bmul(badd(badd(y1.w, u2.w), u0.w), chc.x));
        fence_async_smem();
        dst[(c1 >> 4) * 1280] = v;
        dst[(c2 >> 4) * 1280] = u;
      }
      __syncwarp();
      if (lane == 0) mbar_arrive(bar + 8 * (B_FREE + ch));
    }
    if (warp == 12) {
      if (elect1()) {
        const uint4* srcA = p.scr->h + rg1 * 24 * 1024;
        const uint4* srcB = p.scr->w2p + j1 * 24 * 640;
        poll_cnt(cnt + C_H0 * 32, ep * 128);
        uint32_t d = sb;
#pragma unroll 1
        for (int s = 0; s < 24; s++) {
          if (s == NS2) poll_cnt(cnt + (C_H1 + rg1) * 32, ep * 8);
          if (s >= 3) mbar_wait(bar + 8 * (s < NS2 ? B_FREE + (s == 3 ? 0 : s - 2) : B_REL2 + s - NS2 + 1), 0);
          const uint32_t mb = bar + 8 * (B_FULL2 + s);
          mbar_expect(mb, SLOT2);
          bulk_g2s(d, srcA, 16384, mb);
          bulk_g2s(d + 16384, srcB, 10240, mb);
          srcA += 1024; srcB += 640;
          d = d == sb + (NS2 - 1) * SLOT2 ? sb : d + SLOT2;
        }
      }
      __syncwarp();
    } else if (warp == 13) {
      if (elect1()) {
        mbar_wait(bar + 8 * (B_FREE + 3), 0);
        mbar_wait(bar + 8 * (B_FREE + 4), 0);
        publish(cnt + (C_S + (wid >> 4)) * 32);
        mbar_expect(bar + 8 * B_SFULL, 20480);
        poll_cnt(cnt + (C_S + j1) * 32, ep * 16);
        bulk_g2s(sb + OFF_U, p.scr->sT + (j1 * 16 + rg1) * 1280, 20480, bar + 8 * B_SFULL);
      }
      __syncwarp();
    }
  }
}

typedef CUresult (*EncodeFn)(CUtensorMap*, CUtensorMapDataType, cuuint32_t, void*, const cuuint64_t*, const cuuint64_t*,
                             const cuuint32_t*, const cuuint32_t*, CUtensorMapInterleave, CUtensorMapSwizzle,
                             CUtensorMapL2promotion, CUtensorMapFloatOOBfill);

}

extern "C" void kernel_launch(void* const* d_in, const int* in_sizes, int n_in, void* d_out, int out_size) {
  static EncodeFn enc = nullptr;
  static int nsm = 0;
  static void* scr = nullptr;
  if (!enc) {
    void* fn = nullptr;
    cudaDriverEntryPointQueryResult qr;
    cudaGetDriverEntryPoint("cuTensorMapEncodeTiled", &fn, cudaEnableDefault, &qr);
    enc = (EncodeFn)fn;
    int dev = 0;
    cudaGetDevice(&dev);
    cudaDeviceGetAttribute(&nsm, cudaDevAttrMultiProcessorCount, dev);
    cudaFuncSetAttribute(fused_s4_ffn_kernel<true>, cudaFuncAttributeMaxDynamicSharedMemorySize, SMEM_BYTES);
    cudaFuncSetAttribute(fused_s4_ffn_kernel<false>, cudaFuncAttributeMaxDynamicSharedMemorySize, SMEM_BYTES);
    cudaGetSymbolAddress(&scr, g_scr);
  }
  Params p;
  p.x = (const __nv_bfloat16*)d_in[0];
  p.are = (const __nv_bfloat16*)d_in[1]; p.aim = (const __nv_bfloat16*)d_in[2];
  p.bre = (const __nv_bfloat16*)d_in[3]; p.bim = (const __nv_bfloat16*)d_in[4];
  p.cre = (const __nv_bfloat16*)d_in[5]; p.cim = (const __nv_bfloat16*)d_in[6];
  p.logdt = (const __nv_bfloat16*)d_in[7]; p.dskip = (const __nv_bfloat16*)d_in[8];
  p.w1 = (const __nv_bfloat16*)d_in[10]; p.w2 = (const __nv_bfloat16*)d_in[11];
  p.out = (__nv_bfloat16*)d_out;
  p.scr = (Scratch*)scr;
  CUtensorMap tmX, tmW1, tmU, tmW2;
  const cuuint32_t es[5] = {1, 1, 1, 1, 1};
  {
    const cuuint64_t gd[5] = {DM, 2, 4, 4, FF / 32}, gs[4] = {DM * 2, DM * 16, DM * 4, DM * 64};
    const cuuint32_t bx[5] = {88, 2, 4, 4, 3};
    enc(&tmW2, CU_TENSOR_MAP_DATA_TYPE_BFLOAT16, 5, d_in[11], gd, gs, bx, es, CU_TENSOR_MAP_INTERLEAVE_NONE,
        CU_TENSOR_MAP_SWIZZLE_NONE, CU_TENSOR_MAP_L2_PROMOTION_NONE, CU_TENSOR_MAP_FLOAT_OOB_FILL_NONE);
  }
  {
    const cuuint64_t gd[2] = {16 * DM, 128}, gs[1] = {DM * 32};
    const cuuint32_t bx[2] = {80, 128};
    enc(&tmU, CU_TENSOR_MAP_DATA_TYPE_FLOAT16, 2, p.scr->uT, gd, gs, bx, es, CU_TENSOR_MAP_INTERLEAVE_NONE,
        CU_TENSOR_MAP_SWIZZLE_NONE, CU_TENSOR_MAP_L2_PROMOTION_NONE, CU_TENSOR_MAP_FLOAT_OOB_FILL_NONE);
  }
  {
    const cuuint64_t gd[2] = {DM, SEQ}, gs[1] = {DM * 2};
    const cuuint32_t bx[2] = {64, 128};
    enc(&tmX, CU_TENSOR_MAP_DATA_TYPE_BFLOAT16, 2, d_in[0], gd, gs, bx, es, CU_TENSOR_MAP_INTERLEAVE_NONE,
        CU_TENSOR_MAP_SWIZZLE_128B, CU_TENSOR_MAP_L2_PROMOTION_L2_128B, CU_TENSOR_MAP_FLOAT_OOB_FILL_NONE);
  }
  {
    const cuuint64_t gd[3] = {64, DM, FF / 64}, gs[2] = {FF * 2, 128};
    const cuuint32_t bx[3] = {64, 64, 3};
    enc(&tmW1, CU_TENSOR_MAP_DATA_TYPE_BFLOAT16, 3, d_in[10], gd, gs, bx, es, CU_TENSOR_MAP_INTERLEAVE_NONE,
        CU_TENSOR_MAP_SWIZZLE_128B, CU_TENSOR_MAP_L2_PROMOTION_L2_128B, CU_TENSOR_MAP_FLOAT_OOB_FILL_NONE);
  }
  if (nsm == 132) fused_s4_ffn_kernel<true><<<132, 512, SMEM_BYTES>>>(p, tmX, tmW1, tmU, tmW2);
  else fused_s4_ffn_kernel<false><<<132, 512, SMEM_BYTES>>>(p, tmX, tmW1, tmU, tmW2);
}
```

```cpp
#include <cuda_runtime.h>
#include <cuda_bf16.h>
#include <cuda_fp16.h>
#include <cuda.h>
#include <stdint.h>

namespace {

constexpr int SEQ = 2048, DM = 640, FF = 1536;

constexpr int SLOT1 = 40960;
constexpr int SLOT2 = 26624;
constexpr int NS2 = 6;
#define PACE_NS 30
constexpr int OFF_Z = 91904, ZSZ = 19712;
constexpr int ZA3 = 0, ZB3 = 2048, ZS = 4096, ZA2 = 6144, ZB2 = 9216, ZA1 = 12288, ZB1 = 16000;
constexpr int OFF_W2S = OFF_Z + 4 * ZSZ;
constexpr int OFF_U = 190464;
constexpr int OFF_P = 210944;
constexpr int OFF_KS = 163840;
constexpr int OFF_LNP = 225280;
constexpr int OFF_MISC = 226304;
constexpr int OFF_CHC = OFF_MISC + 16;
constexpr int OFF_EP = OFF_MISC + 64;
constexpr int OFF_ZERO = OFF_MISC + 128;
constexpr int OFF_STAT = OFF_MISC + 1024;
constexpr int OFF_CS = OFF_MISC + 2048;
constexpr int OFF_BAR = OFF_MISC + 2816;
constexpr int SMEM_BYTES = OFF_MISC + 6144;
constexpr int P0 = 8, PA1 = 280, PB1 = 360, PA2 = 448, PB2 = 544, PA3 = 632, PB3 = 704;
enum { B_FULL1 = 0, B_FULL2 = 10, B_UFULL = 34, B_EPI = 35, B_SFULL = 36, B_W2 = 37, B_MMA = 38,
       B_FREE = 40,
       B_REL1 = 45, B_REL2 = 55, B_NUM = 80 };
enum { C_LN = 0, C_CS = 1, C_H0 = 2, C_H1 = 18, C_S = 34, C_W2 = 42, C_NUM = 43 };

struct Scratch {
  unsigned cnt[64 * 32];
  unsigned epoch[256];
  unsigned flag_ln[128], flag_h0[128];
  float2 stats[SEQ];
  float cs[FF];
  uint4 uT[DM * 256];
  uint4 w2p[8 * 24 * 640];
  uint4 sT[8 * 16 * 1280];
  uint4 h[16 * 24 * 1024];
};
__device__ __align__(1024) Scratch g_scr;
constexpr uint32_t sb = 1024;
constexpr uint32_t bar = sb + OFF_BAR;

struct Params {
  const __nv_bfloat16 *are, *aim, *bre, *bim, *cre, *cim, *logdt, *dskip, *x, *w1, *w2;
  __nv_bfloat16* out;
  Scratch* scr;
};

__device__ __forceinline__ void mbar_init(uint32_t a, int c) { asm volatile("mbarrier.init.shared::cta.b64 [%0], %1;" ::"r"(a), "r"(c)); }
__device__ __forceinline__ void mbar_expect(uint32_t a, int b) { asm volatile("mbarrier.arrive.expect_tx.shared::cta.b64 _, [%0], %1;" ::"r"(a), "r"(b) : "memory"); }
__device__ __forceinline__ void mbar_arrive(uint32_t a) { asm volatile("mbarrier.arrive.shared::cta.b64 _, [%0];" ::"r"(a) : "memory"); }
__device__ __forceinline__ void mbar_wait(uint32_t a, int ph) {
  asm volatile(
      "{\n.reg .pred p;\n.reg .u32 n;\n"
      "mbarrier.try_wait.parity.shared::cta.b64 p, [%0], %1;\n@p bra LD;\nmov.u32 n, 0;\n"
      "LW:\nmbarrier.try_wait.parity.shared::cta.b64 p, [%0], %1, 20000;\n@p bra LD;\n"
      "add.u32 n, n, 1;\nsetp.lt.u32 p, n, 100000;\n@p bra LW;\ntrap;\nLD:\n}\n" ::"r"(a), "r"(ph) : "memory");
}
__device__ __forceinline__ void poll_cnt(const unsigned* p, unsigned target) {
  asm volatile(
      "{\n.reg .pred p;\n.reg .u32 n;\n.reg .s32 v;\nmov.u32 n, 0;\n"
      "LW:\nld.relaxed.gpu.global.u32 v, [%0];\nsub.s32 v, v, %1;\nsetp.ge.s32 p, v, 0;\n@p bra LD;\n"
      "add.u32 n, n, 1;\nsetp.lt.u32 p, n, 4000000;\n@p bra LW;\ntrap;\n"
      "LD:\nfence.acquire.gpu;\nfence.proxy.async.global;\n}\n" ::"l"(p), "r"(target) : "memory");
}
__device__ __forceinline__ void publish(unsigned* p) {
  asm volatile("fence.proxy.async.global;\nfence.release.gpu;\nred.relaxed.gpu.global.add.u32 [%0], 1;" ::"l"(p) : "memory");
}
__device__ __forceinline__ void publish_flag(unsigned* p, unsigned ep) {
  asm volatile("fence.proxy.async.global;\nfence.release.gpu;\nst.relaxed.gpu.global.u32 [%0], %1;" ::"l"(p), "r"(ep) : "memory");
}
__device__ __forceinline__ void poll_flags(const unsigned* p, unsigned ep) {
  asm volatile(
      "{\n.reg .pred p;\n.reg .u32 n, a, b, c, d;\nmov.u32 n, 0;\n"
      "LW:\nld.relaxed.gpu.global.v4.u32 {a, b, c, d}, [%0];\n"
      "lop3.b32 a, a, b, %1, 0x7e;\nlop3.b32 c, c, d, %1, 0x7e;\nor.b32 a, a, c;\nsetp.eq.u32 p, a, 0;\n"
      "vote.sync.all.pred p, p, 0xffffffff;\n@p bra.uni LD;\n"
      "add.u32 n, n, 1;\nsetp.lt.u32 p, n, 4000000;\n@p bra.uni LW;\ntrap;\n"
      "LD:\nfence.acquire.gpu;\nfence.proxy.async.global;\n}\n" ::"l"(p), "r"(ep) : "memory");
}
__device__ __forceinline__ uint32_t movm(uint32_t v) { uint32_t r; asm volatile("movmatrix.sync.aligned.m8n8.trans.b16 %0, %1;" : "=r"(r) : "r"(v)); return r; }
__device__ __forceinline__ void fence_async_smem() { asm volatile("fence.proxy.async.shared::cta;" ::: "memory"); }
__device__ __forceinline__ bool elect1() { uint32_t p; asm volatile("{\n.reg .pred P;\nelect.sync _|P, 0xffffffff;\nselp.u32 %0,1,0,P;\n}\n" : "=r"(p)); return p; }
__device__ __forceinline__ void bar_sync(int id, int n) { asm volatile("bar.sync %0, %1;" ::"r"(id), "r"(n) : "memory"); }
__device__ __forceinline__ void bar_arrive(int id, int n) { asm volatile("bar.arrive %0, %1;" ::"r"(id), "r"(n) : "memory"); }
__device__ __forceinline__ void bulk_g2s(uint32_t dst, const void* src, int bytes, uint32_t mb) {
  asm volatile("cp.async.bulk.shared::cluster.global.mbarrier::complete_tx::bytes [%0], [%1], %2, [%3];" ::"r"(dst), "l"(src), "r"(bytes), "r"(mb) : "memory");
}
__device__ __forceinline__ void bulk_prefetch(const void* src, int bytes) { asm volatile("cp.async.bulk.prefetch.L2.global [%0], %1;" ::"l"(src), "r"(bytes) : "memory"); }
__device__ __forceinline__ void tma2d(uint32_t dst, const CUtensorMap* m, int c0, int c1, uint32_t mb) {
  asm volatile("cp.async.bulk.tensor.2d.shared::cluster.global.mbarrier::complete_tx::bytes [%0], [%1, {%3, %4}], [%2];" ::"r"(dst), "l"(m), "r"(mb), "r"(c0), "r"(c1) : "memory");
}
__device__ __forceinline__ void tma3d(uint32_t dst, const CUtensorMap* m, int c0, int c1, int c2, uint32_t mb) {
  asm volatile("cp.async.bulk.tensor.3d.shared::cluster.global.mbarrier::complete_tx::bytes [%0], [%1, {%3, %4, %5}], [%2];" ::"r"(dst), "l"(m), "r"(mb), "r"(c0), "r"(c1), "r"(c2) : "memory");
}
__device__ __forceinline__ int frag_col(int l) {
  const int tl = l >> 3, i = l & 7;
  return (tl < 8 ? 32 * (tl >> 2) + 8 * (i >> 1) + 2 * (tl & 3) : 48 + 4 * (i >> 1) + 2 * tl) + (i & 1);
}
__device__ __forceinline__ void tma5d(uint32_t dst, const CUtensorMap* m, int c0, int c4, uint32_t mb) {
  asm volatile("cp.async.bulk.tensor.5d.shared::cluster.global.mbarrier::complete_tx::bytes [%0], [%1, {%3, %5, %5, %5, %4}], [%2];" ::"r"(dst), "l"(m), "r"(mb), "r"(c0), "r"(c4), "r"(0) : "memory");
}
__device__ __forceinline__ uint64_t dsc(uint32_t lo, uint32_t hi) { return ((uint64_t)hi << 32) | lo; }
__device__ __forceinline__ void wg_fence() { asm volatile("wgmma.fence.sync.aligned;" ::: "memory"); }
__device__ __forceinline__ void wg_commit() { asm volatile("wgmma.commit_group.sync.aligned;" ::: "memory"); }
template <int N> __device__ __forceinline__ void wg_wait() { asm volatile("wgmma.wait_group.sync.aligned %0;" ::"n"(N) : "memory"); }
__device__ __forceinline__ void wgmma_n192(float (&d)[96], uint64_t da, uint64_t db, int scale_d) {
  asm volatile("{\n.reg .pred p;\nsetp.ne.b32 p, %98, 0;\n"
    "wgmma.mma_async.sync.aligned.m64n192k16.f32.bf16.bf16 "
    "{"
    "%0, %1, %2, %3, %4, %5, %6, %7, %8, %9, %10, %11, %12, %13, %14, %15, "
    "%16, %17, %18, %19, %20, %21, %22, %23, %24, %25, %26, %27, %28, %29, %30, %31, "
    "%32, %33, %34, %35, %36, %37, %38, %39, %40, %41, %42, %43, %44, %45, %46, %47, "
    "%48, %49, %50, %51, %52, %53, %54, %55, %56, %57, %58, %59, %60, %61, %62, %63, "
    "%64, %65, %66, %67, %68, %69, %70, %71, %72, %73, %74, %75, %76, %77, %78, %79, "
    "%80, %81, %82, %83, %84, %85, %86, %87, %88, %89, %90, %91, %92, %93, %94, %95"
    "}, "
    "%96, %97, p, 1, 1, 0, 1;\n}\n"
    : "+f"(d[0]), "+f"(d[1]), "+f"(d[2]), "+f"(d[3]), "+f"(d[4]), "+f"(d[5]), "+f"(d[6]), "+f"(d[7]),
      "+f"(d[8]), "+f"(d[9]), "+f"(d[10]), "+f"(d[11]), "+f"(d[12]), "+f"(d[13]), "+f"(d[14]), "+f"(d[15]),
      "+f"(d[16]), "+f"(d[17]), "+f"(d[18]), "+f"(d[19]), "+f"(d[20]), "+f"(d[21]), "+f"(d[22]), "+f"(d[23]),
      "+f"(d[24]), "+f"(d[25]), "+f"(d[26]), "+f"(d[27]), "+f"(d[28]), "+f"(d[29]), "+f"(d[30]), "+f"(d[31]),
      "+f"(d[32]), "+f"(d[33]), "+f"(d[34]), "+f"(d[35]), "+f"(d[36]), "+f"(d[37]), "+f"(d[38]), "+f"(d[39]),
      "+f"(d[40]), "+f"(d[41]), "+f"(d[42]), "+f"(d[43]), "+f"(d[44]), "+f"(d[45]), "+f"(d[46]), "+f"(d[47]),
      "+f"(d[48]), "+f"(d[49]), "+f"(d[50]), "+f"(d[51]), "+f"(d[52]), "+f"(d[53]), "+f"(d[54]), "+f"(d[55]),
      "+f"(d[56]), "+f"(d[57]), "+f"(d[58]), "+f"(d[59]), "+f"(d[60]), "+f"(d[61]), "+f"(d[62]), "+f"(d[63]),
      "+f"(d[64]), "+f"(d[65]), "+f"(d[66]), "+f"(d[67]), "+f"(d[68]), "+f"(d[69]), "+f"(d[70]), "+f"(d[71]),
      "+f"(d[72]), "+f"(d[73]), "+f"(d[74]), "+f"(d[75]), "+f"(d[76]), "+f"(d[77]), "+f"(d[78]), "+f"(d[79]),
      "+f"(d[80]), "+f"(d[81]), "+f"(d[82]), "+f"(d[83]), "+f"(d[84]), "+f"(d[85]), "+f"(d[86]), "+f"(d[87]),
      "+f"(d[88]), "+f"(d[89]), "+f"(d[90]), "+f"(d[91]), "+f"(d[92]), "+f"(d[93]), "+f"(d[94]), "+f"(d[95])
    : "l"(da), "l"(db), "r"(scale_d));
}

__device__ __forceinline__ void wgmma_n80(float (&d)[40], uint64_t da, uint64_t db, int scale_d) {
  asm volatile("{\n.reg .pred p;\nsetp.ne.b32 p, %42, 0;\n"
    "wgmma.mma_async.sync.aligned.m64n80k16.f32.bf16.bf16 "
    "{"
    "%0, %1, %2, %3, %4, %5, %6, %7, %8, %9, %10, %11, %12, %13, %14, %15, "
    "%16, %17, %18, %19, %20, %21, %22, %23, %24, %25, %26, %27, %28, %29, %30, %31, "
    "%32, %33, %34, %35, %36, %37, %38, %39"
    "}, "
    "%40, %41, p, 1, 1, 0, 1;\n}\n"
    : "+f"(d[0]), "+f"(d[1]), "+f"(d[2]), "+f"(d[3]), "+f"(d[4]), "+f"(d[5]), "+f"(d[6]), "+f"(d[7]),
      "+f"(d[8]), "+f"(d[9]), "+f"(d[10]), "+f"(d[11]), "+f"(d[12]), "+f"(d[13]), "+f"(d[14]), "+f"(d[15]),
      "+f"(d[16]), "+f"(d[17]), "+f"(d[18]), "+f"(d[19]), "+f"(d[20]), "+f"(d[21]), "+f"(d[22]), "+f"(d[23]),
      "+f"(d[24]), "+f"(d[25]), "+f"(d[26]), "+f"(d[27]), "+f"(d[28]), "+f"(d[29]), "+f"(d[30]), "+f"(d[31]),
      "+f"(d[32]), "+f"(d[33]), "+f"(d[34]), "+f"(d[35]), "+f"(d[36]), "+f"(d[37]), "+f"(d[38]), "+f"(d[39])
    : "l"(da), "l"(db), "r"(scale_d));
}

__device__ __forceinline__ void hmma(float* c, uint32_t a0, uint32_t a1, uint32_t a2, uint32_t a3, uint32_t b0, uint32_t b1) {
  asm volatile("mma.sync.aligned.m16n8k16.row.col.f32.f16.f16.f32 {%0,%1,%2,%3}, {%4,%5,%6,%7}, {%8,%9}, {%0,%1,%2,%3};"
      : "+f"(c[0]), "+f"(c[1]), "+f"(c[2]), "+f"(c[3]) : "r"(a0), "r"(a1), "r"(a2), "r"(a3), "r"(b0), "r"(b1));
}
__device__ __forceinline__ void ldsm4(uint32_t* r, uint32_t a) { asm volatile("ldmatrix.sync.aligned.m8n8.x4.shared.b16 {%0,%1,%2,%3}, [%4];" : "=r"(r[0]), "=r"(r[1]), "=r"(r[2]), "=r"(r[3]) : "r"(a) : "memory"); }
__device__ __forceinline__ void ldsm4t(uint32_t* r, uint32_t a) { asm volatile("ldmatrix.sync.aligned.m8n8.x4.trans.shared.b16 {%0,%1,%2,%3}, [%4];" : "=r"(r[0]), "=r"(r[1]), "=r"(r[2]), "=r"(r[3]) : "r"(a) : "memory"); }
__device__ __forceinline__ void stsm4(uint32_t a, uint32_t r0, uint32_t r1, uint32_t r2, uint32_t r3) { asm volatile("stmatrix.sync.aligned.m8n8.x4.shared.b16 [%0], {%1,%2,%3,%4};" ::"r"(a), "r"(r0), "r"(r1), "r"(r2), "r"(r3) : "memory"); }
__device__ __forceinline__ void stsm4t(uint32_t a, uint32_t r0, uint32_t r1, uint32_t r2, uint32_t r3) { asm volatile("stmatrix.sync.aligned.m8n8.x4.trans.shared.b16 [%0], {%1,%2,%3,%4};" ::"r"(a), "r"(r0), "r"(r1), "r"(r2), "r"(r3) : "memory"); }
__device__ __forceinline__ uint32_t lds32(uint32_t a) { uint32_t v; asm volatile("ld.shared.u32 %0, [%1];" : "=r"(v) : "r"(a) : "memory"); return v; }
__device__ __forceinline__ uint2 lds64(uint32_t a) { uint2 v; asm volatile("ld.shared.v2.u32 {%0,%1}, [%2];" : "=r"(v.x), "=r"(v.y) : "r"(a) : "memory"); return v; }
__device__ __forceinline__ uint4 lds128(uint32_t a) { uint4 v; asm volatile("ld.shared.v4.u32 {%0,%1,%2,%3}, [%4];" : "=r"(v.x), "=r"(v.y), "=r"(v.z), "=r"(v.w) : "r"(a) : "memory"); return v; }
__device__ __forceinline__ void sts16(uint32_t a, uint32_t v) { asm volatile("st.shared.u16 [%0], %1;" ::"r"(a), "h"((unsigned short)v) : "memory"); }
__device__ __forceinline__ void sts32(uint32_t a, uint32_t v) { asm volatile("st.shared.u32 [%0], %1;" ::"r"(a), "r"(v) : "memory"); }
__device__ __forceinline__ void sts64(uint32_t a, uint32_t x, uint32_t y) { asm volatile("st.shared.v2.u32 [%0], {%1,%2};" ::"r"(a), "r"(x), "r"(y) : "memory"); }
__device__ __forceinline__ void sts128(uint32_t a, uint32_t x, uint32_t y, uint32_t z, uint32_t w) { asm volatile("st.shared.v4.u32 [%0], {%1,%2,%3,%4};" ::"r"(a), "r"(x), "r"(y), "r"(z), "r"(w) : "memory"); }
__device__ __forceinline__ float bflo(uint32_t v) { return __uint_as_float(v << 16); }
__device__ __forceinline__ float bfhi(uint32_t v) { return __uint_as_float(v & 0xffff0000u); }
__device__ __forceinline__ uint32_t pack_bf(float lo, float hi) { uint32_t r; asm("cvt.rn.bf16x2.f32 %0, %1, %2;" : "=r"(r) : "f"(hi), "f"(lo)); return r; }
__device__ __forceinline__ uint32_t pack_h(float lo, float hi) { uint32_t r; asm("cvt.rn.f16x2.f32 %0, %1, %2;" : "=r"(r) : "f"(hi), "f"(lo)); return r; }
__device__ __forceinline__ float rnd_bf(float v) { return __bfloat162float(__float2bfloat16_rn(v)); }
__device__ __forceinline__ float ex2a(float v) { float r; asm("ex2.approx.ftz.f32 %0, %1;" : "=f"(r) : "f"(v)); return r; }
__device__ __forceinline__ float tanha(float v) { float r; asm("tanh.approx.f32 %0, %1;" : "=f"(r) : "f"(v)); return r; }
__device__ __forceinline__ uint32_t hadd(uint32_t a, uint32_t b) { uint32_t r; asm("add.rn.f16x2 %0, %1, %2;" : "=r"(r) : "r"(a), "r"(b)); return r; }
__device__ __forceinline__ uint32_t badd(uint32_t a, uint32_t b) { uint32_t r; asm("add.rn.bf16x2 %0, %1, %2;" : "=r"(r) : "r"(a), "r"(b)); return r; }
__device__ __forceinline__ uint32_t bmul(uint32_t a, uint32_t b) { uint32_t r; asm("mul.rn.bf16x2 %0, %1, %2;" : "=r"(r) : "r"(a), "r"(b)); return r; }
__device__ __forceinline__ uint32_t bsub(uint32_t a, uint32_t b) { uint32_t r; asm("sub.rn.bf16x2 %0, %1, %2;" : "=r"(r) : "r"(a), "r"(b)); return r; }
__device__ __forceinline__ uint32_t dup(uint32_t v, uint32_t nz) { uint32_t r; asm volatile("add.rn.f32 %0, %1, %2;" : "=r"(r) : "r"(v), "r"(nz)); return r; }
__device__ __forceinline__ void bmma(float* c, uint32_t a0, uint32_t a1, uint32_t a2, uint32_t a3, uint32_t b0, uint32_t b1) {
  asm("mma.sync.aligned.m16n8k16.row.col.f32.bf16.bf16.f32 {%0,%1,%2,%3}, {%4,%5,%6,%7}, {%8,%9}, {%0,%1,%2,%3};"
      : "+f"(c[0]), "+f"(c[1]), "+f"(c[2]), "+f"(c[3]) : "r"(a0), "r"(a1), "r"(a2), "r"(a3), "r"(b0), "r"(b1));
}
__device__ __forceinline__ uint32_t odd_pair(uint32_t a, uint32_t b) { return __byte_perm(a, b, 0x5432); }
__device__ __forceinline__ int upos(int c) { return c ^ (c >> 5) ^ ((c >> 3) & 1); }
__device__ __forceinline__ int uoff(int pos) { return (pos >> 1) * 160 + (pos & 1) * 16; }

struct cf { float r, i; };
__device__ __forceinline__ cf cmul(cf a, cf b) { cf o; o.r = fmaf(a.r, b.r, -a.i * b.i); o.i = fmaf(a.r, b.i, a.i * b.r); return o; }
__device__ __forceinline__ cf csq(cf a) { cf o; o.r = fmaf(a.r, a.r, -a.i * a.i); o.i = (a.r + a.r) * a.i; return o; }
struct hp { uint32_t r, i; };
__device__ __forceinline__ hp hpack(cf a, cf b) { hp o; o.r = pack_h(a.r, b.r); o.i = pack_h(a.i, b.i); return o; }
__device__ __forceinline__ hp hmulc(hp a, uint32_t c) {
  __half2 ar = *reinterpret_cast<__half2*>(&a.r), ai = *reinterpret_cast<__half2*>(&a.i), cc = *reinterpret_cast<__half2*>(&c);
  __half2 orr = __hfma2(ar, __low2half2(cc), __hneg2(__hmul2(ai, __high2half2(cc))));
  __half2 oi = __hfma2(ar, __high2half2(cc), __hmul2(ai, __low2half2(cc)));
  hp o; o.r = *reinterpret_cast<uint32_t*>(&orr); o.i = *reinterpret_cast<uint32_t*>(&oi); return o;
}
__device__ __forceinline__ void sts_tile(uint32_t a, const hp* t) {
  sts128(a, t[0].r, t[1].r, t[2].r, t[3].r);
  sts128(a + 512, t[0].i, t[1].i, t[2].i, t[3].i);
}
template <int STEP> __device__ __forceinline__ void put2(uint32_t a0, uint32_t a1, uint32_t h, uint32_t sel) {
  const uint32_t x = __byte_perm(h, h, sel), y = x >> 16;
  sts16(a0, x); sts16(a0 + STEP * 4 + 2, x);
  sts16(a1, y); sts16(a1 + STEP * 4 + 2, y);
}

__device__ __forceinline__ void spare_work(const Params& p, const CUtensorMap* tmW1, int k, int tid) {
  const int lane = tid & 31;
  unsigned ep = 0;
  if (tid >= 480) ep = p.scr->epoch[128 + k] + 1;
  if (tid == 480) {
    for (int i = 0; i < 8; i++) mbar_init(bar + 8 * i, i < 4 ? 1 : 12);
    asm volatile("fence.mbarrier_init.release.cluster;" ::: "memory");
    fence_async_smem();
  }
  __syncthreads();
  float a[2][4] = {{0.f, 0.f, 0.f, 0.f}, {0.f, 0.f, 0.f, 0.f}};
  if (tid >= 480) {
    if (elect1()) {
#pragma unroll 1
      for (int s = 0; s < 10; s++) {
        mbar_wait(bar + 8 * (4 + (s & 3)), ((s >> 2) & 1) ^ 1);
        mbar_expect(bar + 8 * (s & 3), 49152);
#pragma unroll 1
        for (int b = 0; b < 2; b++) tma3d(sb + (s & 3) * 49152 + b * 24576, tmW1, 0, s * 64, k * 6 + b * 3, bar + 8 * (s & 3));
      }
    }
    __syncwarp();
  } else if (tid < 384) {
    const uint32_t idn = (lane >> 3) == (lane & 3) ? ((lane & 4) ? 0x3f800000u : 0x3f80u) : 0u;
#pragma unroll 1
    for (int s = 0; s < 10; s++) {
      mbar_wait(bar + 8 * (s & 3), (s >> 2) & 1);
      const uint32_t ad = sb + (s & 3) * 49152 + (tid >> 6) * 8192 + (tid & 63) * 16;
#pragma unroll
      for (int i = 0; i < 8; i += 2) {
        const uint4 v = lds128(ad + i * 1024), w = lds128(ad + i * 1024 + 1024);
        bmma(a[0], v.x, v.y, w.x, w.y, idn, idn);
        bmma(a[1], v.z, v.w, w.z, w.w, idn, idn);
      }
      __syncwarp();
      if (lane == 0) mbar_arrive(bar + 8 * (4 + (s & 3)));
    }
    const int rho = (tid >> 3) & 7;
    const uint32_t ad = sb + 196608 + rho * 1536 + ((tid >> 6) * 8 + ((tid & 7) ^ rho)) * 32;
    sts128(ad, __float_as_uint(a[0][0]), __float_as_uint(a[0][1]), __float_as_uint(a[0][2]), __float_as_uint(a[0][3]));
    sts128(ad + 16, __float_as_uint(a[1][0]), __float_as_uint(a[1][1]), __float_as_uint(a[1][2]), __float_as_uint(a[1][3]));
  }
  __syncthreads();
  if (tid < 384) {
    float s = 0.f;
#pragma unroll
    for (int r = 0; r < 8; r++) s += __uint_as_float(lds32(sb + 196608 + r * 1536 + tid * 4));
    p.scr->cs[k * 384 + tid] = s;
  }
  __syncthreads();
  if (tid == 480) {
    publish(p.scr->cnt + C_CS * 32);
    p.scr->epoch[128 + k] = ep;
  }
  __syncwarp();
  if (tid >= 480) poll_flags(p.scr->flag_h0 + lane * 4, ep);
}

__device__ __forceinline__ void load1(int s, const CUtensorMap* tmX, const CUtensorMap* tmW1, int rg1, int j1) {
  const uint32_t d = sb + (s & 3) * SLOT1, mb = bar + 8 * (B_FULL1 + s);
  mbar_expect(mb, SLOT1);
  tma2d(d, tmX, s * 64, rg1 * 128, mb);
  tma3d(d + 16384, tmW1, 0, s * 64, j1 * 3, mb);
}
__device__ __forceinline__ void load_x(uint32_t (&xv)[2][10], const __nv_bfloat16* xc, int rstep, int q) {
#pragma unroll
  for (int r = 0; r < 2; r++) {
    const uint4 a = __ldg((const uint4*)(xc + r * rstep) + q), b = __ldg((const uint4*)(xc + r * rstep) + 4 + q);
    const uint2 c = __ldg((const uint2*)(xc + r * rstep + 64) + q);
    xv[r][0] = a.x; xv[r][1] = a.y; xv[r][2] = a.z; xv[r][3] = a.w; xv[r][4] = b.x; xv[r][5] = b.y; xv[r][6] = b.z; xv[r][7] = b.w;
    xv[r][8] = c.x; xv[r][9] = c.y;
  }
}

template <bool USE_SMID>
__global__ void __launch_bounds__(512, 1)
fused_s4_ffn_kernel(const Params p, const __grid_constant__ CUtensorMap tmX, const __grid_constant__ CUtensorMap tmW1,
                    const __grid_constant__ CUtensorMap tmU, const __grid_constant__ CUtensorMap tmW2) {
  extern __shared__ __align__(1024) unsigned char smem_raw[];
  const int tid = threadIdx.x, lane = tid & 31;
  const int warp = __shfl_sync(0xffffffffu, tid >> 5, 0);
  const int g = lane >> 2, q = lane & 3;
  uint32_t sid;
  if (USE_SMID) asm("mov.u32 %0, %smid;" : "=r"(sid)); else sid = blockIdx.x;
  if (sid - 120u < 4u) { spare_work(p, &tmW1, sid - 120, tid); return; }
  const int wid = sid < 120 ? sid : sid - 4;
  unsigned* const cnt = p.scr->cnt;

  float kacc[5][4];
  const int kpart = (warp >= 5) + (warp >= 10), kch = warp - 5 * kpart;
  float dt, k0;
  uint32_t xv[2][10], xs[2], mw, pds;
  {
    uint32_t pa[6], pld;
    unsigned ep0;
    if (warp < 15) {
      const int ch = (wid >> 4) * 80 + frag_col((wid & 15) * 5 + kch);
      const int o = (ch * 3 + kpart) * 32 + lane;
      pa[0] = __ldg((const uint32_t*)p.are + o); pa[1] = __ldg((const uint32_t*)p.aim + o);
      pa[2] = __ldg((const uint32_t*)p.bre + o); pa[3] = __ldg((const uint32_t*)p.bim + o);
      pa[4] = __ldg((const uint32_t*)p.cre + o); pa[5] = __ldg((const uint32_t*)p.cim + o);
      pld = __ldg((const unsigned short*)p.logdt + ch);
      pds = __ldg((const unsigned short*)p.dskip + ch);
    } else {
      ep0 = p.scr->epoch[wid];
      if ((uint32_t)__cvta_generic_to_shared(smem_raw) != sb) __trap();
    }
    if (elect1()) {
      const int gi = (warp + 1) & 15;
#pragma unroll
      for (int i = 0; i < 5; i++) mbar_init(bar + 40 * gi + 8 * i, gi < 8 ? 1 : gi == 8 ? 4 : 8);
      asm volatile("fence.mbarrier_init.release.cluster;" ::: "memory");
    }
    if (warp == 15) {
      sts64(sb + OFF_ZERO + (lane & 15) * 8 + (lane >> 4) * 640, 0, 0);
      int gpc, i;
      if (sid < 64) { gpc = (sid & 15) >> 1; i = sid >> 4; }
      else if (sid < 120) { const int t = sid - 64; i = t / 14; gpc = 1 + ((t - i * 14) >> 1); i += 4; }
      else { gpc = 0; i = 4 + ((sid - 124) >> 1); }
      const int qi = ((0x52741630 >> (4 * i)) & 7) * 2 + (sid & 1);
      const int rg = 4 * (gpc >> 1) + (qi >> 2), jc = 4 * (gpc & 1) + (qi & 3);
      sts64(sb + OFF_EP + 8, rg, jc);
      __syncwarp();
      if (elect1()) {
        bulk_prefetch(p.x + wid * 16 * DM, 16 * DM * 2);
#pragma unroll 1
        for (int s = 0; s < 4; s++) load1(s, &tmX, &tmW1, rg, jc);
        bulk_prefetch(p.w1 + wid * 5 * FF, 5 * FF * 2);
        bulk_prefetch(p.w2 + wid * 12 * DM, 12 * DM * 2);
        asm volatile("prefetch.tensormap [%0];\nprefetch.tensormap [%1];" ::"l"(&tmU), "l"(&tmW2) : "memory");
      }
    }
#pragma unroll
    for (int j = 0; j < 5; j++) { kacc[j][0] = kacc[j][1] = kacc[j][2] = kacc[j][3] = 0.f; }
    float zr, th, zr1, th1;
    cf c, c1;
    const uint32_t ks = sb + OFF_KS + warp * 4096;
    if (warp < 15) {
      dt = rnd_bf(expf(bflo(pld)));
      c = cmul(cf{bflo(pa[4]), bflo(pa[5])}, cf{bflo(pa[2]), bflo(pa[3])});
      c1 = cmul(cf{bfhi(pa[4]), bfhi(pa[5])}, cf{bfhi(pa[2]), bfhi(pa[3])});
      mw = __reduce_max_sync(0xffffffffu, __float_as_uint(fmaxf(fmaxf(fabsf(c.r), fabsf(c.i)), fmaxf(fabsf(c1.r), fabsf(c1.i)))));
      mw = min(max(mw & 0x7f800000u, 20u << 23), 240u << 23);
      const float sc = __uint_as_float((259u << 23) - mw), dl2 = dt * 1.4426950408889634f;
      k0 = c.r + c1.r;
      zr = bflo(pa[0]) * dl2; th = bflo(pa[1]) * dt; zr1 = bfhi(pa[0]) * dl2; th1 = bfhi(pa[1]) * dt;
      c.r *= sc; c.i *= sc; c1.r *= sc; c1.i *= sc;
    }
    __syncwarp();
    if (warp >= 8) {
      const __nv_bfloat16* xr = p.x + (wid * 16 + ((g >> 1) << 2) + (g & 1)) * DM;
      load_x(xv, xr + (warp - 8) * 80, 2 * DM, q);
      xs[0] = __ldg((const uint32_t*)xr); xs[1] = __ldg((const uint32_t*)(xr + 2 * DM));
    }
    {
      const uint32_t ka = ks + (lane >> 3) * 512 + (lane & 7) * 16;
      const uint32_t kb = ks + ((lane >> 3) & 1) * 512 + ((lane >> 4) * 8 + (lane & 7)) * 16;
#pragma unroll 1
      for (int it = 0; it < 2; it++) {
        if (it == 1 && warp >= 8) {
          float sm[4] = {0.f, 0.f, 0.f, 0.f}, g0[4] = {0.f, 0.f, 0.f, 0.f}, g1[4] = {0.f, 0.f, 0.f, 0.f};
#pragma unroll
          for (int r = 0; r < 2; r++)
            xs[r] = fabsf(bflo(xs[r]) - bfhi(xs[r])) * 8.f < fabsf(bflo(xs[r])) ? __byte_perm(xs[r], 0, 0x1010) : 0u;
#pragma unroll
          for (int i = 0; i < 10; i += 2) {
            const uint32_t a0 = bsub(xv[0][i], xs[0]), a1 = bsub(xv[1][i], xs[1]), a2 = bsub(xv[0][i + 1], xs[0]), a3 = bsub(xv[1][i + 1], xs[1]);
            bmma(sm, a0, a1, a2, a3, 0x3f803f80u, 0x3f803f80u);
            bmma(g0, a0, a1, a2, a3, xv[0][i], xv[0][i + 1]);
            bmma(g1, a0, a1, a2, a3, xv[1][i], xv[1][i + 1]);
          }
          if (q == (g >> 1))
            sts128(sb + OFF_LNP + (warp - 8) * 128 + g * 16, __float_as_uint(sm[0]), __float_as_uint((g & 1) ? g0[1] : g0[0]),
                   __float_as_uint(sm[2]), __float_as_uint((g & 1) ? g1[3] : g1[2]));
          if (warp < 15) bar_arrive(1, 256);
        }
        if (warp == 15) continue;
        float m = ex2a(zr);
        const cf w1 = cf{m * __cosf(th), m * __sinf(th)};
        m = ex2a(zr * 8.f);
        const cf w8 = cf{m * __cosf(th * 8.f), m * __sinf(th * 8.f)};
        const cf w16 = csq(w8), w32 = csq(w16), w64 = csq(w32), w128 = csq(w64), w256 = csq(w128), w512 = csq(w256), w1024 = csq(w512);
        hp lo[8];
        lo[0] = hpack(cf{1.f, 0.f}, cf{w8.r, -w8.i});
        lo[1] = hmulc(lo[0], pack_h(w16.r, -w16.i));
        { const uint32_t k = pack_h(w32.r, -w32.i); lo[2] = hmulc(lo[0], k); lo[3] = hmulc(lo[1], k); }
        { const uint32_t k = pack_h(w64.r, -w64.i);
#pragma unroll
          for (int i = 0; i < 4; i++) lo[4 + i] = hmulc(lo[i], k); }
        const uint32_t st = ks + lane * 16;
        sts128(st, lo[0].r, lo[1].r, lo[2].r, lo[3].r);
        sts128(st + 512, lo[4].r, lo[5].r, lo[6].r, lo[7].r);
        sts128(st + 1024, lo[0].i, lo[1].i, lo[2].i, lo[3].i);
        sts128(st + 1536, lo[4].i, lo[5].i, lo[6].i, lo[7].i);
        const cf t1 = cmul(c, w1), t2 = cmul(t1, w1), t3 = cmul(t2, w1), t4 = cmul(t3, w1);
        const cf t5 = cmul(t4, w1), t6 = cmul(t5, w1), t7 = cmul(t6, w1), t8 = cmul(c, w8);
        hp T0[4], T1[4], T2[4], T3[4], T4[4];
        T0[0] = hpack(t4, t8); T0[1] = hpack(t2, t6); T0[2] = hpack(t1, t5); T0[3] = hpack(t3, t7);
        const uint32_t k128 = pack_h(w128.r, w128.i), k256 = pack_h(w256.r, w256.i), k512 = pack_h(w512.r, w512.i);
#pragma unroll
        for (int i = 0; i < 4; i++) T1[i] = hmulc(T0[i], k128);
        sts_tile(st + 2048, T0);
        sts_tile(st + 3072, T1);
        __syncwarp();
        uint32_t af[4][4];
#pragma unroll
        for (int mg = 0; mg < 4; mg++) ldsm4t(af[mg], ka + mg * 128);
#pragma unroll
        for (int j = 0; j < 2; j++)
#pragma unroll
          for (int mg = 0; mg < 4; mg += 2) {
            uint32_t b[4];
            ldsm4t(b, kb + 2048 + j * 1024 + mg * 128);
            hmma(kacc[j], af[mg][0], af[mg][1], af[mg][2], af[mg][3], b[0], b[1]);
            hmma(kacc[j], af[mg + 1][0], af[mg + 1][1], af[mg + 1][2], af[mg + 1][3], b[2], b[3]);
          }
        T2[0] = hmulc(T0[0], k256); T2[1] = hmulc(T0[1], k256); T2[2] = hmulc(T1[0], k256); T2[3] = hmulc(T1[1], k256);
        T3[0] = hmulc(T0[0], k512); T3[1] = hmulc(T1[0], k512); T3[2] = hmulc(T2[0], k512); T3[3] = hmulc(T2[2], k512);
        { const cf u0 = cmul(t8, w1024), u1 = cmul(u0, w128);
          T4[0] = hpack(u0, u1); T4[1] = hmulc(T4[0], k256); T4[2] = hmulc(T4[0], k512); T4[3] = hmulc(T4[1], k512); }
        __syncwarp();
        sts_tile(st, T2);
        sts_tile(st + 1024, T3);
        sts_tile(st + 2048, T4);
        __syncwarp();
#pragma unroll
        for (int j = 0; j < 3; j++)
#pragma unroll
          for (int mg = 0; mg < 4; mg += 2) {
            uint32_t b[4];
            ldsm4t(b, kb + j * 1024 + mg * 128);
            hmma(kacc[2 + j], af[mg][0], af[mg][1], af[mg][2], af[mg][3], b[0], b[1]);
            hmma(kacc[2 + j], af[mg + 1][0], af[mg + 1][1], af[mg + 1][2], af[mg + 1][3], b[2], b[3]);
          }
        __syncwarp();
        zr = zr1; th = th1; c = c1;
      }
    }
    if (warp < 10) {
#pragma unroll
      for (int j = 0; j < 5; j++)
        sts128(ks + j * 512 + lane * 16, __float_as_uint(kacc[j][0]), __float_as_uint(kacc[j][1]), __float_as_uint(kacc[j][2]), __float_as_uint(kacc[j][3]));
      sts64(ks + 2560 + lane * 8, __float_as_uint(k0), mw);
    } else if (warp == 15) {
      if (lane == 0) { p.scr->epoch[wid] = ep0 + 1; sts32(sb + OFF_EP, ep0 + 1); }
      bar_sync(1, 256);
      float s1 = 0.f, s2 = 0.f;
#pragma unroll
      for (int w = 0; w < 8; w++) {
        const uint2 v = lds64(sb + OFF_LNP + w * 128 + g * 16 + (q & 1) * 8);
        s1 += __uint_as_float(v.x); s2 += __uint_as_float(v.y);
      }
      const float md = s1 * (1.f / DM), mean = bflo((q & 1) ? xs[1] : xs[0]) + md;
      const float var = fmaxf(fmaf(-md, mean, s2 * (1.f / DM)), 0.f);
      const float m = rnd_bf(mean);
      float sd, ri;
      asm("sqrt.approx.f32 %0, %1;" : "=f"(sd) : "f"(rnd_bf(rnd_bf(var) + 1e-5f)));
      asm("rcp.approx.f32 %0, %1;" : "=f"(ri) : "f"(rnd_bf(sd)));
      if (q < 2) {
        p.scr->stats[wid * 16 + ((g >> 1) << 2) + (g & 1) + 2 * q] = make_float2(-m, 0.5f * ri);
        sts64(sb + OFF_STAT + g * 16 + q * 8, __float_as_uint(-m * ri), __float_as_uint(ri));
      }
    }
  }
  __syncthreads();

  if (warp < 8) {
    float acc[96];
    const uint32_t alo = ((sb >> 4) | (1 << 16)) + (warp >> 2) * 512;
#pragma unroll 1
    for (int s = 0; s < 10; s++) {
      const uint32_t so = (s & 3) * (SLOT1 >> 4);
      mbar_wait(bar + 8 * (B_FULL1 + s), 0);
      wg_fence();
#pragma unroll
      for (int kk = 0; kk < 4; kk++)
        wgmma_n192(acc, dsc(alo + so + kk * 2, 0x40000040u), dsc((((sb + 16384) >> 4) | (512 << 16)) + so + kk * 128, 0x40000040u), (s | kk) != 0);
      wg_commit();
      wg_wait<1>();
      if (lane == 0) mbar_arrive(bar + 8 * (B_REL1 + s));
    }
    wg_wait<0>();
    bar_arrive(14, 512);
    mbar_wait(bar + 8 * B_EPI, 0);
    const uint2 s0 = lds64(sb + OFF_STAT + (warp * 16 + g) * 8), s1 = lds64(sb + OFF_STAT + (warp * 16 + g + 8) * 8);
    const float nm0 = __uint_as_float(s0.x), r0 = __uint_as_float(s0.y), nm1 = __uint_as_float(s1.x), r1 = __uint_as_float(s1.y);
    const uint4 erj = lds128(sb + OFF_EP);
    const unsigned ep = erj.x;
    const int rg1 = erj.z, j1 = erj.w;
    uint4* hd = p.scr->h + (rg1 * 24 + j1) * 1024 + warp * 128 + q * 8 + g;
#pragma unroll
    for (int grp = 0; grp < 6; grp++) {
      uint32_t o0[4], o1[4];
#pragma unroll
      for (int tl = 0; tl < 4; tl++) {
        const int nt = grp * 4 + tl;
        const uint2 cs = lds64(sb + OFF_CS + (nt * 8 + 2 * q) * 4);
        const float ca = __uint_as_float(cs.x), cb = __uint_as_float(cs.y);
        const float a = fmaf(nm0, ca, acc[4 * nt]) * r0, b = fmaf(nm0, cb, acc[4 * nt + 1]) * r0;
        const float c = fmaf(nm1, ca, acc[4 * nt + 2]) * r1, d = fmaf(nm1, cb, acc[4 * nt + 3]) * r1;
        o0[tl] = pack_bf(fmaf(a, tanha(a), a), fmaf(b, tanha(b), b));
        o1[tl] = pack_bf(fmaf(c, tanha(c), c), fmaf(d, tanha(d), d));
      }
      uint4* dst = hd + (grp >> 1) * 8192 + (grp & 1) * 32;
      dst[0] = make_uint4(o0[0], o0[1], o0[2], o0[3]);
      dst[64] = make_uint4(o1[0], o1[1], o1[2], o1[3]);
      if (PACE_NS) __nanosleep(PACE_NS);
      if (grp == 1) {
        if (warp == 7) { bar_sync(2, 448); if (lane == 0) publish_flag(p.scr->flag_h0 + wid, ep); __syncwarp(); }
        else bar_arrive(2, 448);
      }
    }
    if (warp == 6) { bar_sync(11, 256); if (lane == 0) publish(cnt + (C_H1 + rg1) * 32); __syncwarp(); }
    else bar_arrive(11, 256);
    const int go = (rg1 * 128 + warp * 16 + g) * DM + j1 * 80;
    load_x(xv, p.x + go, 8 * DM, q);
    if (warp == 4) {
      poll_flags(p.scr->flag_h0 + lane * 4, ep);
      if (elect1()) {
#pragma unroll 1
        for (int s = 0; s < NS2; s++) {
          if (s == 3) poll_cnt(cnt + (C_H1 + rg1) * 32, ep * 8);
          if (s >= 3) mbar_wait(bar + 8 * (B_FREE + (s == 3 ? 0 : s - 2)), 0);
          if (s == 4) mbar_wait(bar + 8 * (B_FREE + 1), 0);
          const uint32_t mb = bar + 8 * (B_FULL2 + s);
          mbar_expect(mb, SLOT2);
          bulk_g2s(sb + s * SLOT2, p.scr->h + (rg1 * 24 + s) * 1024, 16384, mb);
          bulk_g2s(sb + s * SLOT2 + 16384, p.scr->w2p + (j1 * 24 + s) * 640, 10240, mb);
        }
      }
      __syncwarp();
    }
    float acc2[40];
    mbar_wait(bar + 8 * B_MMA, 0);
    {
      const uint32_t al2 = ((sb >> 4) | (8 << 16)) + (warp >> 2) * 512;
      uint32_t so = 0;
#pragma unroll 1
      for (int s = 0; s < 24; s++) {
        mbar_wait(bar + 8 * (B_FULL2 + s), 0);
        wg_fence();
#pragma unroll
        for (int kk = 0; kk < 4; kk++)
          wgmma_n80(acc2, dsc(al2 + so + kk * 16, 64), dsc((((sb + 16384) >> 4) | (80 << 16)) + so + kk * 160, 8), (s | kk) != 0);
        wg_commit();
        so = so == (NS2 - 1) * (SLOT2 >> 4) ? 0 : so + (SLOT2 >> 4);
        wg_wait<1>();
        if (lane == 0) mbar_arrive(bar + 8 * (B_REL2 + s));
      }
    }
    mbar_wait(bar + 8 * B_SFULL, 0);
    uint32_t sv[5][4];
    {
      const int i = lane & 7, mi = lane >> 3;
      const uint32_t a = sb + OFF_U + ((mi >> 1) * 8 + i) * 256 + (((2 * warp + (mi & 1)) ^ i) << 4);
#pragma unroll
      for (int k = 0; k < 5; k++) ldsm4t(sv[k], a + k * 4096);
    }
    wg_wait<0>();
#pragma unroll
    for (int hh = 0; hh < 2; hh++) {
      uint32_t o[10];
#pragma unroll
      for (int tl = 0; tl < 10; tl++) {
        const uint32_t xw = xv[hh][tl];
        const uint32_t sw = sv[tl >> 1][(tl & 1) * 2 + hh];
        const float a = acc2[4 * tl + 2 * hh], b = acc2[4 * tl + 2 * hh + 1];
        o[tl] = pack_bf(fmaf(bflo(sw), fmaf(a, tanha(a), a), bflo(xw)), fmaf(bfhi(sw), fmaf(b, tanha(b), b), bfhi(xw)));
      }
      __nv_bfloat16* op = p.out + go + hh * 8 * DM;
      ((uint4*)op)[q] = make_uint4(o[0], o[1], o[2], o[3]);
      ((uint4*)op)[4 + q] = make_uint4(o[4], o[5], o[6], o[7]);
      ((uint2*)(op + 64))[q] = make_uint2(o[8], o[9]);
    }
  } else {
    const int cw = warp - 8;
    const uint4 erj = lds128(sb + OFF_EP);
    const unsigned ep = erj.x;
    const int rg1 = erj.z, j1 = erj.w;
    {
      const uint4 st = lds128(sb + OFF_STAT + g * 16);
      const float n0 = __uint_as_float(st.x), r0 = __uint_as_float(st.y), n1 = __uint_as_float(st.z), r1 = __uint_as_float(st.w);
      const int up = upos(2 * wid);
      uint2* dst = (uint2*)p.scr->uT + ((up >> 1) * DM + cw * 80) * 4 + (lane ^ ((up & 1) << 1));
#pragma unroll
      for (int i = 0; i < 10; i++) {
        const uint32_t a = movm(pack_h(fmaf(bflo(xv[0][i]), r0, n0), fmaf(bfhi(xv[0][i]), r0, n0)));
        const uint32_t b = movm(pack_h(fmaf(bflo(xv[1][i]), r1, n1), fmaf(bfhi(xv[1][i]), r1, n1)));
        dst[i * 32] = make_uint2(a, b);
      }
    }
    if (warp == 8) {
      bar_sync(12, 256);
      if (lane == 0) publish_flag(p.scr->flag_ln + wid, ep);
      __syncwarp();
    } else bar_arrive(12, 256);
    if (warp == 15) {
      if (elect1()) {
#pragma unroll 1
        for (int s = 4; s < 10; s++) {
          mbar_wait(bar + 8 * (B_REL1 + s - 3), 0);
          load1(s, &tmX, &tmW1, rg1, j1);
        }
      }
      __syncwarp();
    }
    if (warp >= 10 && warp < 15) {
      const uint32_t pb = sb + OFF_P + kch * 3072, pk = sb + OFF_KS + kch * 4096;
      const uint2 e0 = lds64(pk + 2560 + lane * 8), e1 = lds64(pk + 5 * 4096 + 2560 + lane * 8);
      const float dsk = bflo(pds);
      uint32_t kex = __float_as_uint(fmaxf(__uint_as_float(max(max(e0.y, e1.y), mw)) * dt, fabsf(dsk) * (1.f / 256.f))) >> 23;
      kex = min(max(kex, 20u), 240u);
      const float s2 = __uint_as_float((258 - kex) << 23), sd = s2 * dt * (1.f / 32.f);
      const float f0 = __uint_as_float(e0.y) * sd, f1 = __uint_as_float(e1.y) * sd, f2 = __uint_as_float(mw) * sd;
      k0 += __uint_as_float(e0.x) + __uint_as_float(e1.x);
#pragma unroll
      for (int o = 16; o; o >>= 1) k0 += __shfl_xor_sync(0xffffffffu, k0, o);
      const float k0n = fmaf(k0, dt, dsk) * s2;
      uint32_t h[5][2];
#pragma unroll
      for (int j = 0; j < 5; j++) {
        const uint4 a = lds128(pk + j * 512 + lane * 16), b = lds128(pk + 5 * 4096 + j * 512 + lane * 16);
#pragma unroll
        for (int e = 0; e < 4; e++) kacc[j][e] = fmaf(__uint_as_float((&a.x)[e]), f0, fmaf(__uint_as_float((&b.x)[e]), f1, kacc[j][e] * f2));
        if (j == 1) {
          const float k256 = __shfl_sync(0xffffffffu, kacc[1][3], 28);
          if (lane == 31) kacc[1][3] -= k256;
        }
        if (j == 2 || j == 3) { h[j][0] = pack_h(kacc[j][0], kacc[j][2]); h[j][1] = pack_h(kacc[j][1], kacc[j][3]); }
        else { h[j][0] = pack_h(kacc[j][0], kacc[j][1]); h[j][1] = pack_h(kacc[j][2], kacc[j][3]); }
      }
      fence_async_smem();
      bar_arrive(4, 192);
#pragma unroll
      for (int i = 0; i < 6; i++) sts128(pb + i * 512 + lane * 16, 0, 0, 0, 0);
      __syncwarp();
      {
        const int sw = g >> 2;
        const uint32_t sel = sw ? 0x1032 : 0x3210;
        const uint32_t a = pb + (P0 + 8 * g + ((0x3124 >> (4 * q)) & 7)) * 4, a0 = a + sw * 16, a1 = a + 16 - sw * 16;
        put2<1>(a0, a1, h[0][0], sel);
        put2<1>(a0 + 256, a1 + 256, h[0][1], sel);
        put2<1>(a0 + 512, a1 + 512, h[1][0], sel);
        put2<1>(lane == 28 ? pb + PB1 * 4 : a0 + 768, a1 + 768, h[1][1], sel);
      }
      {
        const int sw = q >> 1;
        const uint32_t sel = sw ? 0x1032 : 0x3210;
        uint32_t a = pb + (((q & 1) ? PA1 : PB1 + 1) + 32 * sw + 2 * g) * 4;
        put2<1>(a + sw * 64, a + 64 - sw * 64, h[2][0], sel);
        put2<1>(a + 4 + sw * 64, a + 68 - sw * 64, h[2][1], sel);
        a = pb + (PA2 + g + 16 * q) * 4;
        put2<2>(a + sw * 32, a + 32 - sw * 32, h[3][0], sel);
        put2<2>(a + (PB2 - PA2) * 4 + sw * 32, a + (PB2 - PA2) * 4 + 32 - sw * 32, h[3][1], sel);
        a = pb + (((g & 1) ? PB3 : PA3) + (g >> 1) + 16 * q) * 4;
        const uint32_t hx = sw ? h[4][1] : h[4][0], hy = sw ? h[4][0] : h[4][1];
        put2<1>(a + sw * 16, a + 32 + sw * 16, hx, 0x3210);
        put2<1>(a + 16 - sw * 16, a + 48 - sw * 16, hy, 0x3210);
      }
      if (lane == 30) put2<1>(pb + P0 * 4, pb + (PA1 + 64) * 4, pack_h(k0n, kacc[2][3]), 0x3210);
      if (lane == 31) sts64(sb + OFF_CHC + kch * 8, (kex - 4) * 0x00800080u, __byte_perm(h[3][1], 0, 0x3232));
    }
    if (warp == 8) {
      bar_sync(13, 64);
      if (elect1()) { mbar_expect(bar + 8 * B_UFULL, 20480); mbar_expect(bar + 8 * B_EPI, 1024 + 768); }
      poll_flags(p.scr->flag_ln + lane * 4, ep);
      if (elect1()) {
        tma2d(sb + OFF_U, &tmU, wid * 80, 0, bar + 8 * B_UFULL);
        bulk_g2s(sb + OFF_STAT, p.scr->stats + rg1 * 128, 1024, bar + 8 * B_EPI);
      }
      __syncwarp();
      bar_arrive(15, 224);
    } else if (warp == 9) {
      bar_sync(4, 192);
      bar_arrive(13, 64);
      if (elect1()) {
        mbar_expect(bar + 8 * B_W2, 96 * 176);
        tma5d(sb + OFF_W2S, &tmW2, (wid & 7) * 80, (wid >> 3) * 3, bar + 8 * B_W2);
        poll_cnt(cnt + C_CS * 32, ep * 4);
        bulk_g2s(sb + OFF_CS, p.scr->cs + j1 * 192, 768, bar + 8 * B_EPI);
      }
      __syncwarp();
    }
    if (warp >= 9 && warp < 15) {
      const int uu = (warp - 9) >> 1, G = (warp - 9) & 1;
      const int grp = (wid >> 3) * 3 + uu, jj = grp / 6, rem = grp - jj * 6;
      const uint32_t a = sb + OFF_W2S + (uu * 32 + lane) * 176;
      uint4* dst = p.scr->w2p + ((wid & 7) * 24 + 8 * (rem >> 1) + jj) * 640 + ((rem & 1) * 4 + (lane >> 3)) * 80 + (lane & 7);
      mbar_wait(bar + 8 * B_W2, 0);
      const uint4 wv[4] = {lds128(a + G * 64), lds128(a + G * 64 + 16), lds128(a + G * 64 + 32), lds128(a + G * 64 + 48)};
      const uint4 t0 = lds128(a + 128), t1 = lds128(a + 144);
      uint32_t w[20];
#pragma unroll
      for (int i = 0; i < 16; i++) w[i] = bmul((&wv[i >> 2].x)[i & 3], 0x3f003f00u);
      w[16] = bmul(G ? t0.y : t0.x, 0x3f003f00u); w[17] = bmul(G ? t0.w : t0.z, 0x3f003f00u);
      w[18] = bmul(G ? t1.y : t1.x, 0x3f003f00u); w[19] = bmul(G ? t1.w : t1.z, 0x3f003f00u);
      bar_sync(15, 224);
#pragma unroll
      for (int i = 0; i < 4; i++) dst[G * 32 + 8 * i] = make_uint4(w[i], w[4 + i], w[8 + i], w[12 + i]);
      dst[64 + G * 8] = make_uint4(w[16], w[17], w[18], w[19]);
      bar_arrive(2, 448);
      if (warp == 12) bar_arrive(3, 64);
    } else if (warp == 15) bar_sync(3, 64);
    mbar_wait(bar + 8 * B_UFULL, 0);
#pragma unroll 1
    for (int ch = (cw >> 2) * 4; ch != 4 + (cw >> 2); ch = ch == 4 ? 1 : ch + 2) {
      if (ch < 4) mbar_wait(bar + 8 * (B_REL1 + (ch ? 8 : 7)), 0);
      const int qt = (cw + ch) & 3, j = qt * 32 + lane;
      const uint32_t ub = sb + OFF_U + ch * 32, zb = sb + OFF_Z + ch * ZSZ;
      uint32_t w_[20], o_[20], d_[20], b3_[20];
      uint32_t *w = w_ + 8, *o = o_ + 8, *d = d_ + 8, *b3 = b3_ + 8;
      {
        const uint32_t am = j > 0 ? ub + uoff(upos(2 * j - 2)) : sb + OFF_ZERO, a0 = ub + uoff(upos(2 * j));
        const uint2 a = lds64(am + 8);
        const uint4 b = lds128(am ^ 16), c = lds128(a0), e = lds128(a0 ^ 16);
        w[8] = lds32(ub + uoff(upos((2 * j + 2) & 255)));
        w[-6] = a.x; w[-5] = a.y; w[-4] = b.x; w[-3] = b.y; w[-2] = b.z; w[-1] = b.w;
        w[0] = c.x; w[1] = c.y; w[2] = c.z; w[3] = c.w; w[4] = e.x; w[5] = e.y; w[6] = e.z; w[7] = e.w;
      }
#pragma unroll
      for (int i = -1; i <= 7; i++) o[i] = odd_pair(w[i], w[i + 1]);
#pragma unroll
      for (int i = 0; i <= 7; i++) { d[i] = hadd(w[i], o[i]); b3[i] = hadd(d[i], o[i - 1]); }
      if (j < 112) {
        const int gr = j >> 1;
        const uint32_t a1 = zb + ZA1 + 128 + (gr ^ ((gr >> 2) & 1)) * 64 + ((gr >> 1) & 3) * 16 + (j & 1) * 8;
#pragma unroll
        for (int pp = 0; pp < 4; pp++) {
          const uint32_t sel = (pp & 1) ? 0x7632 : 0x5410;
          const int k = pp >> 1;
          sts64(a1 ^ (pp * 16), __byte_perm(w[k - 1], w[k + 1], sel), __byte_perm(w[k + 3], w[k + 5], sel));
          sts64((a1 ^ (pp * 16)) + (ZB1 - ZA1), __byte_perm(b3[k], b3[k + 2], sel), __byte_perm(b3[k + 4], b3[k + 6], sel));
        }
      } else if (j >= 120) {
        sts128(zb + ZA1 + ((lane >> 2) & 1) * (ZB1 - ZA1) + (3 - q) * 16, 0, 0, 0, j == 127 ? w[8] << 16 : 0u);
      }
      if (qt < 3) {
        uint32_t e_[20], b5_[20];
        uint32_t *e = e_ + 8, *b5 = b5_ + 8;
#pragma unroll
        for (int i = -6; i <= -2; i++) o[i] = odd_pair(w[i], w[i + 1]);
#pragma unroll
        for (int i = -6; i <= -1; i++) d[i] = hadd(w[i], o[i]);
#pragma unroll
        for (int i = -5; i <= -1; i++) b3[i] = hadd(d[i], o[i - 1]);
#pragma unroll
        for (int i = -5; i <= 4; i++) e[i] = hadd(d[i - 1], d[i]);
#pragma unroll
        for (int i = -4; i <= 4; i++) b5[i] = hadd(e[i], w[i + 1]);
        const uint32_t a2 = zb + ((j >> 3) * 16 + (j & 7)) * 16;
        sts128(a2 + ZA2, b3[-2], b3[-1], b3[0], b3[1]);
        sts128(a2 + ZA2 + 128, b3[2], b3[3], b3[4], b3[5]);
        sts128(a2 + ZB2, b5[-4], b5[-3], b5[-2], b5[-1]);
        sts128(a2 + ZB2 + 128, b5[0], b5[1], b5[2], b5[3]);
        if (qt < 2) {
          sts128(a2 + ZS, d[-2], d[-1], d[0], d[1]);
          sts128(a2 + ZS + 128, d[2], d[3], d[4], d[5]);
          uint32_t b7[8], b9[8];
#pragma unroll
          for (int i = -4; i <= 3; i++) { b7[i + 4] = hadd(b3[i - 1], e[i + 1]); b9[i + 4] = hadd(e[i - 1], b5[i + 1]); }
          const uint32_t a3 = zb + ((j >> 4) * 32 + (j & 15)) * 16;
          sts128(a3 + ZA3, b7[0], b7[1], b7[2], b7[3]);
          sts128(a3 + ZA3 + 256, b7[4], b7[5], b7[6], b7[7]);
          sts128(a3 + ZB3 + 256, b9[0], b9[1], b9[2], b9[3]);
          if (j < 63) sts128(a3 + ZB3 + ((j & 15) == 15 ? 272 : 16), b9[4], b9[5], b9[6], b9[7]);
          else sts128(zb + ZB3, 0, 0, 0, 0);
        }
      }
    }
    const int wg = warp >> 2, role = (warp + 2 * wg) & 3;
    bar_sync(14, 512);
    const uint32_t nz = lds32(sb + OFF_ZERO) | 0x80000000u;
#pragma unroll 1
    for (int ch = wg - 2; ch < 5; ch += 2) {
      const uint32_t ub = sb + OFF_U + ch * 32, zb = sb + OFF_Z + ch * ZSZ, pb = sb + OFF_P + ch * 3072;
      const uint2 chc = lds64(sb + OFF_CHC + ch * 8);
      const int tid = lds32(sb + OFF_ZERO + 20) + threadIdx.x;
      const int lane = tid & 31, g = lane >> 2, q = lane & 3;
      const uint32_t pa = pb + (g - 2 * q) * 4;
      if (role < 2) {
        float acc[8][4];
#pragma unroll
        for (int r = 0; r < 8; r++) { acc[r][0] = acc[r][1] = acc[r][2] = acc[r][3] = 0.f; }
        float fix = 0.f;
        if (role == 1 && lane == 28) {
          const uint32_t k = lds32(pb + PB1 * 4), u0 = lds32(ub);
          fix = __low2float(*reinterpret_cast<const __half2*>(&k)) * __low2float(*reinterpret_cast<const __half2*>(&u0));
        }
        uint32_t ga[3][2];
#pragma unroll
        for (int gm = 0; gm < 3; gm++) {
          const int hb = 2 * (lane & 7) + role - 2 + gm, l3 = ((lane >> 3) ^ (hb >> 1)) & 7;
          ga[gm][0] = hb < 0 ? sb + OFF_ZERO + ((l3 * 16 + ch * 32) & 127) : ub + hb * 1280 + uoff(l3);
          ga[gm][1] = hb < 0 ? ga[gm][0] ^ 64 : ub + hb * 1280 + uoff(l3 ^ 4);
        }
        uint32_t b[12][4], A[17][4];
#pragma unroll
        for (int i = 11; i >= 8; i--) ldsm4(b[i], (ga[2][i & 1] ^ (((i >> 1) & 1) * 16)) + ((i >> 1) & 1) * 640);
        A[0][0] = lds32(pa + P0 * 4); A[0][1] = lds32(pa + P0 * 4 + 32); A[0][2] = lds32(sb + OFF_ZERO + 4);
#pragma unroll
        for (int m = 0; m <= 16; m++) {
          if (m < 16) {
            A[m + 1][0] = lds32(pa + P0 * 4 + (2 * m + 2) * 32);
            A[m + 1][1] = m < 15 ? lds32(pa + P0 * 4 + (2 * m + 3) * 32) : lds32(sb + OFF_ZERO + 8);
          }
          if ((m & 1) == 0 && m < 16) {
            const int i = 7 - (m >> 1);
            ldsm4(b[i], (ga[i >> 2][i & 1] ^ (((i >> 1) & 1) * 16)) + ((i >> 1) & 1) * 640);
          }
          A[m][3] = dup(A[m][0], nz);
          if (m < 16) A[m + 1][2] = dup(A[m][1], nz);
#pragma unroll
          for (int r = 7; r >= 0; r--) {
            const int f = 16 + r - m;
            hmma(acc[r], A[m][0], A[m][1], A[m][2], A[m][3], b[f >> 1][(f & 1) * 2], b[f >> 1][(f & 1) * 2 + 1]);
          }
        }
        acc[7][2] += fix;
        bar_sync(7 + wg, 64);
#pragma unroll
        for (int i = 3; i >= 0; i--)
          stsm4t((ga[2][i & 1] ^ (((i >> 1) & 1) * 16)) + ((i >> 1) & 1) * 640, pack_bf(acc[2 * i][0], acc[2 * i][1]), pack_bf(acc[2 * i][2], acc[2 * i][3]),
                 pack_bf(acc[2 * i + 1][0], acc[2 * i + 1][1]), pack_bf(acc[2 * i + 1][2], acc[2 * i + 1][3]));
      } else if (role == 2) {
        float acc[14][4];
#pragma unroll
        for (int r = 0; r < 14; r++) { acc[r][0] = acc[r][1] = acc[r][2] = acc[r][3] = 0.f; }
        const int mi = lane >> 3, hf = (lane >> 2) & 1;
        const uint32_t ze = zb + ZA1 + 128 - 512 + hf * 1792 + (mi ^ hf) * 64 + ((q ^ (mi >> 1) ^ (hf * 2)) << 4);
        const uint32_t zo = ze ^ 96;
#pragma unroll
        for (int arr = 0; arr < 2; arr++) {
          uint32_t A[5][4];
#pragma unroll
          for (int m = 0; m < 5; m++) {
            A[m][0] = lds32(pa + (arr ? PB1 : PA1) * 4 + m * 64);
            A[m][1] = m < 4 ? lds32(pa + (arr ? PB1 : PA1) * 4 + m * 64 + 32) : lds32(sb + OFF_ZERO + 4 + arr * 8);
          }
#pragma unroll
          for (int m = 4; m >= 1; m--) { A[m][2] = dup(A[m - 1][1], nz); A[m][3] = dup(A[m][0], nz); }
          A[0][2] = lds32(sb + OFF_ZERO + 8 + arr * 8); A[0][3] = dup(A[0][0], nz);
#pragma unroll
          for (int ip = 0; ip < 9; ip++) {
            uint32_t b[4];
            uint32_t ad = ((ip & 1) ? zo : ze) + ip * 256 + arr * (ZB1 - ZA1);
            if (ip < 2 && hf == 0 && (ip == 0 || mi != 3)) ad = sb + OFF_ZERO + (ad & 127);
            ldsm4(b, ad);
#pragma unroll
            for (int hh = 0; hh < 2; hh++)
#pragma unroll
              for (int m = 0; m < 5; m++) {
                const int i = 2 * ip + hh - 4 + m;
                if (i >= 0 && i < 14) hmma(acc[i], A[m][0], A[m][1], A[m][2], A[m][3], b[2 * hh], b[2 * hh + 1]);
              }
          }
        }
        const uint32_t a = zb + ZA1 + ((lane ^ (mi & 1)) << 4);
#pragma unroll
        for (int i = 0; i < 7; i++)
          stsm4(a + i * 512, pack_bf(acc[2 * i][0], acc[2 * i][1]), pack_bf(acc[2 * i][2], acc[2 * i][3]),
                pack_bf(acc[2 * i + 1][0], acc[2 * i + 1][1]), pack_bf(acc[2 * i + 1][2], acc[2 * i + 1][3]));
      } else {
        float acc[12][4];
        const uint32_t za = zb + lane * 16;
        {
          float d[4][2][4];
#pragma unroll
          for (int r = 0; r < 8; r++) { d[r >> 1][r & 1][0] = d[r >> 1][r & 1][1] = d[r >> 1][r & 1][2] = d[r >> 1][r & 1][3] = 0.f; }
#pragma unroll
          for (int arr = 0; arr < 2; arr++) {
            uint32_t A[4][4];
#pragma unroll
            for (int m = 0; m < 4; m++) { A[m][0] = lds32(pa + (arr ? PB3 : PA3) * 4 + m * 64); A[m][1] = lds32(pa + (arr ? PB3 : PA3) * 4 + m * 64 + 32); }
#pragma unroll
            for (int m = 0; m < 4; m++) { A[m][2] = m ? dup(A[m - 1][1], nz) : lds32(sb + OFF_ZERO + 4 + arr * 4); A[m][3] = dup(A[m][0], nz); }
#pragma unroll
            for (int io = 0; io < 4; io++) {
              uint32_t b[4];
              ldsm4t(b, za + (arr ? ZB3 : ZA3) + io * 512);
#pragma unroll
              for (int m = 0; m + io < 4; m++) {
                hmma(d[io + m][0], A[m][0], A[m][1], A[m][2], A[m][3], b[0], b[1]);
                hmma(d[io + m][1], A[m][0], A[m][1], A[m][2], A[m][3], b[2], b[3]);
              }
            }
          }
#pragma unroll
          for (int r = 0; r < 4; r++) {
            acc[r][0] = acc[r][1] = acc[r][2] = acc[r][3] = 0.f;
            acc[4 + 2 * r][0] = d[r][0][0]; acc[4 + 2 * r][1] = d[r][0][1]; acc[4 + 2 * r][2] = d[r][1][0]; acc[4 + 2 * r][3] = d[r][1][1];
            acc[5 + 2 * r][0] = d[r][0][2]; acc[5 + 2 * r][1] = d[r][0][3]; acc[5 + 2 * r][2] = d[r][1][2]; acc[5 + 2 * r][3] = d[r][1][3];
          }
        }
        {
          const uint32_t k0 = (g >> 1) == q ? (chc.y & ((g & 1) ? 0xffff0000u : 0xffffu)) : 0u;
          const uint32_t k1 = lds32(sb + OFF_ZERO + 12), k2 = lds32(sb + OFF_ZERO + 16), k3 = dup(k0, nz);
#pragma unroll
          for (int ip = 0; ip < 4; ip++) {
            uint32_t b[4];
            ldsm4t(b, za + ZS + ip * 512);
            hmma(acc[4 + 2 * ip], k0, k1, k2, k3, b[0], b[1]);
            hmma(acc[5 + 2 * ip], k0, k1, k2, k3, b[2], b[3]);
          }
        }
        const uint32_t pa2 = pb + (2 * g - 4 * q) * 4;
#pragma unroll
        for (int arr = 0; arr < 2; arr++) {
          uint32_t A[5][4];
#pragma unroll
          for (int m = 0; m < 5; m++) {
            const uint2 v = lds64(pa2 + (arr ? PB2 : PA2) * 4 + m * 64);
            A[m][0] = v.x; A[m][1] = v.y; A[m][2] = lds32(pa2 + (arr ? PB2 : PA2) * 4 + m * 64 - 4);
          }
#pragma unroll
          for (int m = 0; m < 5; m++) A[m][3] = dup(A[m][0], nz);
#pragma unroll
          for (int ip = 0; ip < 6; ip++) {
            uint32_t b[4];
            ldsm4t(b, za + (arr ? ZB2 : ZA2) + ip * 512);
#pragma unroll
            for (int hh = 0; hh < 2; hh++)
#pragma unroll
              for (int m = 0; m < 5; m++) {
                const int i = 2 * ip + hh + m;
                if (i < 12) hmma(acc[i], A[m][0], A[m][1], A[m][2], A[m][3], b[2 * hh], b[2 * hh + 1]);
              }
          }
        }
        const uint32_t a = zb + ZA2 + ((lane ^ ((lane >> 1) & 4)) << 4);
#pragma unroll
        for (int i = 0; i < 6; i++)
          stsm4(a + i * 512, pack_bf(acc[2 * i][0], acc[2 * i][1]), pack_bf(acc[2 * i][2], acc[2 * i][3]),
                pack_bf(acc[2 * i + 1][0], acc[2 * i + 1][1]), pack_bf(acc[2 * i + 1][2], acc[2 * i + 1][3]));
      }
      bar_sync(3 + wg, 128);
      if (ch == 4 && (tid & 127) == 0) mbar_arrive(bar + 8 * B_MMA);
      {
        const int row = (wid & 15) * 5 + ch;
        const int c = tid & 127, c1 = c < 112 ? c + 32 : c - 112, c2 = c < 112 ? c + 144 : c - 96;
        const uint32_t zr = sb + OFF_ZERO + (lane & 7) * 16;
        const uint32_t a1 = c < 112 ? zb + ZA1 + ((2 * c) ^ ((c >> 2) & 1)) * 16 : zr;
        const uint32_t a2 = zb + ZA2 + ((c & ~15) - 32 + ((((c >> 1) & 7) + (c & 1) * 8) ^ ((c & 1) * 4))) * 16;
        const uint4 v0 = lds128(ub + uoff(upos(c1))), u0 = lds128(ub + uoff(upos(c2)));
        const uint4 y0 = lds128(a1), y1 = lds128(a1 ^ 16);
        const uint4 v2 = lds128(c1 >= 64 ? a2 : zr), u2 = lds128(c < 112 ? a2 + 112 * 16 : zr);
        uint4* dst = p.scr->sT + ((wid >> 4) * 16 * 80 + row) * 16 + ((c & 15) ^ (row & 7));
        const uint4 v = make_uint4(bmul(badd(badd(y0.x, v2.x), v0.x), chc.x), bmul(badd(badd(y0.y, v2.y), v0.y), chc.x),
                                   bmul(badd(badd(y1.x, v2.z), v0.z), chc.x), bmul(badd(badd(y1.y, v2.w), v0.w), chc.x));
        const uint4 u = make_uint4(bmul(badd(badd(y0.z, u2.x), u0.x), chc.x), bmul(badd(badd(y0.w, u2.y), u0.y), chc.x),
                                   bmul(badd(badd(y1.z, u2.z), u0.z), chc.x), bmul(badd(badd(y1.w, u2.w), u0.w), chc.x));
        fence_async_smem();
        dst[(c1 >> 4) * 1280] = v;
        dst[(c2 >> 4) * 1280] = u;
      }
      __syncwarp();
      if (lane == 0) mbar_arrive(bar + 8 * (B_FREE + ch));
    }
    if (warp == 12) {
      if (elect1()) {
        const uint4* srcA = p.scr->h + (rg1 * 24 + NS2) * 1024;
        const uint4* srcB = p.scr->w2p + (j1 * 24 + NS2) * 640;
        uint32_t d = sb;
#pragma unroll 1
        for (int s = NS2; s < 24; s++) {
          mbar_wait(bar + 8 * (B_REL2 + s - NS2 + 1), 0);
          if (s == NS2) asm volatile("fence.proxy.async.global;" ::: "memory");
          const uint32_t mb = bar + 8 * (B_FULL2 + s);
          mbar_expect(mb, SLOT2);
          bulk_g2s(d, srcA, 16384, mb);
          bulk_g2s(d + 16384, srcB, 10240, mb);
          srcA += 1024; srcB += 640;
          d = d == sb + (NS2 - 1) * SLOT2 ? sb : d + SLOT2;
        }
      }
      __syncwarp();
    } else if (warp == 13) {
      if (elect1()) {
        mbar_wait(bar + 8 * (B_FREE + 3), 0);
        mbar_wait(bar + 8 * (B_FREE + 4), 0);
        publish(cnt + (C_S + (wid >> 4)) * 32);
        mbar_expect(bar + 8 * B_SFULL, 20480);
        poll_cnt(cnt + (C_S + j1) * 32, ep * 16);
        bulk_g2s(sb + OFF_U, p.scr->sT + (j1 * 16 + rg1) * 1280, 20480, bar + 8 * B_SFULL);
      }
      __syncwarp();
    }
  }
}

typedef CUresult (*EncodeFn)(CUtensorMap*, CUtensorMapDataType, cuuint32_t, void*, const cuuint64_t*, const cuuint64_t*,
                             const cuuint32_t*, const cuuint32_t*, CUtensorMapInterleave, CUtensorMapSwizzle,
                             CUtensorMapL2promotion, CUtensorMapFloatOOBfill);

}

extern "C" void kernel_launch(void* const* d_in, const int* in_sizes, int n_in, void* d_out, int out_size) {
  static EncodeFn enc = nullptr;
  static int nsm = 0;
  static void* scr = nullptr;
  if (!enc) {
    void* fn = nullptr;
    cudaDriverEntryPointQueryResult qr;
    cudaGetDriverEntryPoint("cuTensorMapEncodeTiled", &fn, cudaEnableDefault, &qr);
    enc = (EncodeFn)fn;
    int dev = 0;
    cudaGetDevice(&dev);
    cudaDeviceGetAttribute(&nsm, cudaDevAttrMultiProcessorCount, dev);
    cudaFuncSetAttribute(fused_s4_ffn_kernel<true>, cudaFuncAttributeMaxDynamicSharedMemorySize, SMEM_BYTES);
    cudaFuncSetAttribute(fused_s4_ffn_kernel<false>, cudaFuncAttributeMaxDynamicSharedMemorySize, SMEM_BYTES);
    cudaGetSymbolAddress(&scr, g_scr);
  }
  Params p;
  p.x = (const __nv_bfloat16*)d_in[0];
  p.are = (const __nv_bfloat16*)d_in[1]; p.aim = (const __nv_bfloat16*)d_in[2];
  p.bre = (const __nv_bfloat16*)d_in[3]; p.bim = (const __nv_bfloat16*)d_in[4];
  p.cre = (const __nv_bfloat16*)d_in[5]; p.cim = (const __nv_bfloat16*)d_in[6];
  p.logdt = (const __nv_bfloat16*)d_in[7]; p.dskip = (const __nv_bfloat16*)d_in[8];
  p.w1 = (const __nv_bfloat16*)d_in[10]; p.w2 = (const __nv_bfloat16*)d_in[11];
  p.out = (__nv_bfloat16*)d_out;
  p.scr = (Scratch*)scr;
  CUtensorMap tmX, tmW1, tmU, tmW2;
  const cuuint32_t es[5] = {1, 1, 1, 1, 1};
  {
    const cuuint64_t gd[5] = {DM, 2, 4, 4, FF / 32}, gs[4] = {DM * 2, DM * 16, DM * 4, DM * 64};
    const cuuint32_t bx[5] = {88, 2, 4, 4, 3};
    enc(&tmW2, CU_TENSOR_MAP_DATA_TYPE_BFLOAT16, 5, d_in[11], gd, gs, bx, es, CU_TENSOR_MAP_INTERLEAVE_NONE,
        CU_TENSOR_MAP_SWIZZLE_NONE, CU_TENSOR_MAP_L2_PROMOTION_NONE, CU_TENSOR_MAP_FLOAT_OOB_FILL_NONE);
  }
  {
    const cuuint64_t gd[2] = {16 * DM, 128}, gs[1] = {DM * 32};
    const cuuint32_t bx[2] = {80, 128};
    enc(&tmU, CU_TENSOR_MAP_DATA_TYPE_FLOAT16, 2, p.scr->uT, gd, gs, bx, es, CU_TENSOR_MAP_INTERLEAVE_NONE,
        CU_TENSOR_MAP_SWIZZLE_NONE, CU_TENSOR_MAP_L2_PROMOTION_NONE, CU_TENSOR_MAP_FLOAT_OOB_FILL_NONE);
  }
  {
    const cuuint64_t gd[2] = {DM, SEQ}, gs[1] = {DM * 2};
    const cuuint32_t bx[2] = {64, 128};
    enc(&tmX, CU_TENSOR_MAP_DATA_TYPE_BFLOAT16, 2, d_in[0], gd, gs, bx, es, CU_TENSOR_MAP_INTERLEAVE_NONE,
        CU_TENSOR_MAP_SWIZZLE_128B, CU_TENSOR_MAP_L2_PROMOTION_L2_128B, CU_TENSOR_MAP_FLOAT_OOB_FILL_NONE);
  }
  {
    const cuuint64_t gd[3] = {64, DM, FF / 64}, gs[2] = {FF * 2, 128};
    const cuuint32_t bx[3] = {64, 64, 3};
    enc(&tmW1, CU_TENSOR_MAP_DATA_TYPE_BFLOAT16, 3, d_in[10], gd, gs, bx, es, CU_TENSOR_MAP_INTERLEAVE_NONE,
        CU_TENSOR_MAP_SWIZZLE_128B, CU_TENSOR_MAP_L2_PROMOTION_L2_128B, CU_TENSOR_MAP_FLOAT_OOB_FILL_NONE);
  }
  if (nsm == 132) fused_s4_ffn_kernel<true><<<132, 512, SMEM_BYTES>>>(p, tmX, tmW1, tmU, tmW2);
  else fused_s4_ffn_kernel<false><<<132, 512, SMEM_BYTES>>>(p, tmX, tmW1, tmU, tmW2);
}
```

```cpp
#include <cuda_runtime.h>
#include <cuda_bf16.h>
#include <cuda_fp16.h>
#include <cuda.h>
#include <stdint.h>

namespace {

constexpr int SEQ = 2048, DM = 640, FF = 1536;

constexpr int SLOT1 = 40960;
constexpr int SLOT2 = 26624;
constexpr int NS2 = 7;
#define DELAY_NS 200
#define PACE_NS 30
constexpr int OFF_Z = 91904, ZSZ = 19712;
constexpr int ZA3 = 0, ZB3 = 2048, ZS = 4096, ZA2 = 6144, ZB2 = 9216, ZA1 = 12288, ZB1 = 16000;
constexpr int OFF_W2S = OFF_Z + 4 * ZSZ;
constexpr int OFF_U = 190464;
constexpr int OFF_P = 210944;
constexpr int OFF_KS = 163840;
constexpr int OFF_LNP = 225280;
constexpr int OFF_MISC = 226304;
constexpr int OFF_CHC = OFF_MISC + 16;
constexpr int OFF_EP = OFF_MISC + 64;
constexpr int OFF_ZERO = OFF_MISC + 128;
constexpr int OFF_STAT = OFF_MISC + 1024;
constexpr int OFF_CS = OFF_MISC + 2048;
constexpr int OFF_BAR = OFF_MISC + 2816;
constexpr int SMEM_BYTES = OFF_MISC + 6144;
constexpr int P0 = 8, PA1 = 280, PB1 = 360, PA2 = 448, PB2 = 544, PA3 = 632, PB3 = 704;
enum { B_FULL1 = 0, B_FULL2 = 10, B_UFULL = 34, B_EPI = 35, B_SFULL = 36, B_W2 = 37, B_MMA = 38,
       B_FREE = 40,
       B_REL1 = 45, B_REL2 = 55, B_NUM = 80 };
enum { C_LN = 0, C_CS = 1, C_H0 = 2, C_H1 = 18, C_S = 34, C_W2 = 42, C_NUM = 43 };

struct Scratch {
  unsigned cnt[64 * 32];
  unsigned epoch[256];
  float2 stats[SEQ];
  float cs[FF];
  uint4 uT[DM * 256];
  uint4 w2p[8 * 24 * 640];
  uint4 sT[8 * 16 * 1280];
  uint4 h[16 * 24 * 1024];
};
__device__ __align__(1024) Scratch g_scr;
constexpr uint32_t sb = 1024;
constexpr uint32_t bar = sb + OFF_BAR;

struct Params {
  const __nv_bfloat16 *are, *aim, *bre, *bim, *cre, *cim, *logdt, *dskip, *x, *w1, *w2;
  __nv_bfloat16* out;
  Scratch* scr;
};

__device__ __forceinline__ void mbar_init(uint32_t a, int c) { asm volatile("mbarrier.init.shared::cta.b64 [%0], %1;" ::"r"(a), "r"(c)); }
__device__ __forceinline__ void mbar_expect(uint32_t a, int b) { asm volatile("mbarrier.arrive.expect_tx.shared::cta.b64 _, [%0], %1;" ::"r"(a), "r"(b) : "memory"); }
__device__ __forceinline__ void mbar_arrive(uint32_t a) { asm volatile("mbarrier.arrive.shared::cta.b64 _, [%0];" ::"r"(a) : "memory"); }
__device__ __forceinline__ void mbar_wait(uint32_t a, int ph) {
  asm volatile(
      "{\n.reg .pred p;\n.reg .u32 n;\n"
      "mbarrier.try_wait.parity.shared::cta.b64 p, [%0], %1;\n@p bra LD;\nmov.u32 n, 0;\n"
      "LW:\nmbarrier.try_wait.parity.shared::cta.b64 p, [%0], %1, 20000;\n@p bra LD;\n"
      "add.u32 n, n, 1;\nsetp.lt.u32 p, n, 100000;\n@p bra LW;\ntrap;\nLD:\n}\n" ::"r"(a), "r"(ph) : "memory");
}
__device__ __forceinline__ void poll_cnt(const unsigned* p, unsigned target) {
  asm volatile(
      "{\n.reg .pred p;\n.reg .u32 n;\n.reg .s32 v;\nmov.u32 n, 0;\n"
      "LW:\nld.relaxed.gpu.global.u32 v, [%0];\nsub.s32 v, v, %1;\nsetp.ge.s32 p, v, 0;\n@p bra LD;\n"
      "nanosleep.u32 64;\nadd.u32 n, n, 1;\nsetp.lt.u32 p, n, 4000000;\n@p bra LW;\ntrap;\n"
      "LD:\nfence.acquire.gpu;\nfence.proxy.async.global;\n}\n" ::"l"(p), "r"(target) : "memory");
}
__device__ __forceinline__ void publish(unsigned* p) {
  asm volatile("fence.proxy.async.global;\nfence.release.gpu;\nred.relaxed.gpu.global.add.u32 [%0], 1;" ::"l"(p) : "memory");
}
__device__ __forceinline__ uint32_t movm(uint32_t v) { uint32_t r; asm volatile("movmatrix.sync.aligned.m8n8.trans.b16 %0, %1;" : "=r"(r) : "r"(v)); return r; }
__device__ __forceinline__ void fence_async_smem() { asm volatile("fence.proxy.async.shared::cta;" ::: "memory"); }
__device__ __forceinline__ bool elect1() { uint32_t p; asm volatile("{\n.reg .pred P;\nelect.sync _|P, 0xffffffff;\nselp.u32 %0,1,0,P;\n}\n" : "=r"(p)); return p; }
__device__ __forceinline__ void bar_sync(int id, int n) { asm volatile("bar.sync %0, %1;" ::"r"(id), "r"(n) : "memory"); }
__device__ __forceinline__ void bar_arrive(int id, int n) { asm volatile("bar.arrive %0, %1;" ::"r"(id), "r"(n) : "memory"); }
__device__ __forceinline__ void bulk_g2s(uint32_t dst, const void* src, int bytes, uint32_t mb) {
  asm volatile("cp.async.bulk.shared::cluster.global.mbarrier::complete_tx::bytes [%0], [%1], %2, [%3];" ::"r"(dst), "l"(src), "r"(bytes), "r"(mb) : "memory");
}
__device__ __forceinline__ void bulk_prefetch(const void* src, int bytes) { asm volatile("cp.async.bulk.prefetch.L2.global [%0], %1;" ::"l"(src), "r"(bytes) : "memory"); }
__device__ __forceinline__ void tma2d(uint32_t dst, const CUtensorMap* m, int c0, int c1, uint32_t mb) {
  asm volatile("cp.async.bulk.tensor.2d.shared::cluster.global.mbarrier::complete_tx::bytes [%0], [%1, {%3, %4}], [%2];" ::"r"(dst), "l"(m), "r"(mb), "r"(c0), "r"(c1) : "memory");
}
__device__ __forceinline__ void tma3d(uint32_t dst, const CUtensorMap* m, int c0, int c1, int c2, uint32_t mb) {
  asm volatile("cp.async.bulk.tensor.3d.shared::cluster.global.mbarrier::complete_tx::bytes [%0], [%1, {%3, %4, %5}], [%2];" ::"r"(dst), "l"(m), "r"(mb), "r"(c0), "r"(c1), "r"(c2) : "memory");
}
__device__ __forceinline__ int frag_col(int l) {
  const int tl = l >> 3, i = l & 7;
  return (tl < 8 ? 32 * (tl >> 2) + 8 * (i >> 1) + 2 * (tl & 3) : 48 + 4 * (i >> 1) + 2 * tl) + (i & 1);
}
__device__ __forceinline__ void tma5d(uint32_t dst, const CUtensorMap* m, int c0, int c4, uint32_t mb) {
  asm volatile("cp.async.bulk.tensor.5d.shared::cluster.global.mbarrier::complete_tx::bytes [%0], [%1, {%3, %5, %5, %5, %4}], [%2];" ::"r"(dst), "l"(m), "r"(mb), "r"(c0), "r"(c4), "r"(0) : "memory");
}
__device__ __forceinline__ uint64_t dsc(uint32_t lo, uint32_t hi) { return ((uint64_t)hi << 32) | lo; }
__device__ __forceinline__ void wg_fence() { asm volatile("wgmma.fence.sync.aligned;" ::: "memory"); }
__device__ __forceinline__ void wg_commit() { asm volatile("wgmma.commit_group.sync.aligned;" ::: "memory"); }
template <int N> __device__ __forceinline__ void wg_wait() { asm volatile("wgmma.wait_group.sync.aligned %0;" ::"n"(N) : "memory"); }
__device__ __forceinline__ void wgmma_n192(float (&d)[96], uint64_t da, uint64_t db, int scale_d) {
  asm volatile("{\n.reg .pred p;\nsetp.ne.b32 p, %98, 0;\n"
    "wgmma.mma_async.sync.aligned.m64n192k16.f32.bf16.bf16 "
    "{"
    "%0, %1, %2, %3, %4, %5, %6, %7, %8, %9, %10, %11, %12, %13, %14, %15, "
    "%16, %17, %18, %19, %20, %21, %22, %23, %24, %25, %26, %27, %28, %29, %30, %31, "
    "%32, %33, %34, %35, %36, %37, %38, %39, %40, %41, %42, %43, %44, %45, %46, %47, "
    "%48, %49, %50, %51, %52, %53, %54, %55, %56, %57, %58, %59, %60, %61, %62, %63, "
    "%64, %65, %66, %67, %68, %69, %70, %71, %72, %73, %74, %75, %76, %77, %78, %79, "
    "%80, %81, %82, %83, %84, %85, %86, %87, %88, %89, %90, %91, %92, %93, %94, %95"
    "}, "
    "%96, %97, p, 1, 1, 0, 1;\n}\n"
    : "+f"(d[0]), "+f"(d[1]), "+f"(d[2]), "+f"(d[3]), "+f"(d[4]), "+f"(d[5]), "+f"(d[6]), "+f"(d[7]),
      "+f"(d[8]), "+f"(d[9]), "+f"(d[10]), "+f"(d[11]), "+f"(d[12]), "+f"(d[13]), "+f"(d[14]), "+f"(d[15]),
      "+f"(d[16]), "+f"(d[17]), "+f"(d[18]), "+f"(d[19]), "+f"(d[20]), "+f"(d[21]), "+f"(d[22]), "+f"(d[23]),
      "+f"(d[24]), "+f"(d[25]), "+f"(d[26]), "+f"(d[27]), "+f"(d[28]), "+f"(d[29]), "+f"(d[30]), "+f"(d[31]),
      "+f"(d[32]), "+f"(d[33]), "+f"(d[34]), "+f"(d[35]), "+f"(d[36]), "+f"(d[37]), "+f"(d[38]), "+f"(d[39]),
      "+f"(d[40]), "+f"(d[41]), "+f"(d[42]), "+f"(d[43]), "+f"(d[44]), "+f"(d[45]), "+f"(d[46]), "+f"(d[47]),
      "+f"(d[48]), "+f"(d[49]), "+f"(d[50]), "+f"(d[51]), "+f"(d[52]), "+f"(d[53]), "+f"(d[54]), "+f"(d[55]),
      "+f"(d[56]), "+f"(d[57]), "+f"(d[58]), "+f"(d[59]), "+f"(d[60]), "+f"(d[61]), "+f"(d[62]), "+f"(d[63]),
      "+f"(d[64]), "+f"(d[65]), "+f"(d[66]), "+f"(d[67]), "+f"(d[68]), "+f"(d[69]), "+f"(d[70]), "+f"(d[71]),
      "+f"(d[72]), "+f"(d[73]), "+f"(d[74]), "+f"(d[75]), "+f"(d[76]), "+f"(d[77]), "+f"(d[78]), "+f"(d[79]),
      "+f"(d[80]), "+f"(d[81]), "+f"(d[82]), "+f"(d[83]), "+f"(d[84]), "+f"(d[85]), "+f"(d[86]), "+f"(d[87]),
      "+f"(d[88]), "+f"(d[89]), "+f"(d[90]), "+f"(d[91]), "+f"(d[92]), "+f"(d[93]), "+f"(d[94]), "+f"(d[95])
    : "l"(da), "l"(db), "r"(scale_d));
}

__device__ __forceinline__ void wgmma_n80(float (&d)[40], uint64_t da, uint64_t db, int scale_d) {
  asm volatile("{\n.reg .pred p;\nsetp.ne.b32 p, %42, 0;\n"
    "wgmma.mma_async.sync.aligned.m64n80k16.f32.bf16.bf16 "
    "{"
    "%0, %1, %2, %3, %4, %5, %6, %7, %8, %9, %10, %11, %12, %13, %14, %15, "
    "%16, %17, %18, %19, %20, %21, %22, %23, %24, %25, %26, %27, %28, %29, %30, %31, "
    "%32, %33, %34, %35, %36, %37, %38, %39"
    "}, "
    "%40, %41, p, 1, 1, 0, 1;\n}\n"
    : "+f"(d[0]), "+f"(d[1]), "+f"(d[2]), "+f"(d[3]), "+f"(d[4]), "+f"(d[5]), "+f"(d[6]), "+f"(d[7]),
      "+f"(d[8]), "+f"(d[9]), "+f"(d[10]), "+f"(d[11]), "+f"(d[12]), "+f"(d[13]), "+f"(d[14]), "+f"(d[15]),
      "+f"(d[16]), "+f"(d[17]), "+f"(d[18]), "+f"(d[19]), "+f"(d[20]), "+f"(d[21]), "+f"(d[22]), "+f"(d[23]),
      "+f"(d[24]), "+f"(d[25]), "+f"(d[26]), "+f"(d[27]), "+f"(d[28]), "+f"(d[29]), "+f"(d[30]), "+f"(d[31]),
      "+f"(d[32]), "+f"(d[33]), "+f"(d[34]), "+f"(d[35]), "+f"(d[36]), "+f"(d[37]), "+f"(d[38]), "+f"(d[39])
    : "l"(da), "l"(db), "r"(scale_d));
}

__device__ __forceinline__ void hmma(float* c, uint32_t a0, uint32_t a1, uint32_t a2, uint32_t a3, uint32_t b0, uint32_t b1) {
  asm volatile("mma.sync.aligned.m16n8k16.row.col.f32.f16.f16.f32 {%0,%1,%2,%3}, {%4,%5,%6,%7}, {%8,%9}, {%0,%1,%2,%3};"
      : "+f"(c[0]), "+f"(c[1]), "+f"(c[2]), "+f"(c[3]) : "r"(a0), "r"(a1), "r"(a2), "r"(a3), "r"(b0), "r"(b1));
}
__device__ __forceinline__ void ldsm4(uint32_t* r, uint32_t a) { asm volatile("ldmatrix.sync.aligned.m8n8.x4.shared.b16 {%0,%1,%2,%3}, [%4];" : "=r"(r[0]), "=r"(r[1]), "=r"(r[2]), "=r"(r[3]) : "r"(a) : "memory"); }
__device__ __forceinline__ void ldsm4t(uint32_t* r, uint32_t a) { asm volatile("ldmatrix.sync.aligned.m8n8.x4.trans.shared.b16 {%0,%1,%2,%3}, [%4];" : "=r"(r[0]), "=r"(r[1]), "=r"(r[2]), "=r"(r[3]) : "r"(a) : "memory"); }
__device__ __forceinline__ void stsm4(uint32_t a, uint32_t r0, uint32_t r1, uint32_t r2, uint32_t r3) { asm volatile("stmatrix.sync.aligned.m8n8.x4.shared.b16 [%0], {%1,%2,%3,%4};" ::"r"(a), "r"(r0), "r"(r1), "r"(r2), "r"(r3) : "memory"); }
__device__ __forceinline__ void stsm4t(uint32_t a, uint32_t r0, uint32_t r1, uint32_t r2, uint32_t r3) { asm volatile("stmatrix.sync.aligned.m8n8.x4.trans.shared.b16 [%0], {%1,%2,%3,%4};" ::"r"(a), "r"(r0), "r"(r1), "r"(r2), "r"(r3) : "memory"); }
__device__ __forceinline__ uint32_t lds32(uint32_t a) { uint32_t v; asm volatile("ld.shared.u32 %0, [%1];" : "=r"(v) : "r"(a) : "memory"); return v; }
__device__ __forceinline__ uint2 lds64(uint32_t a) { uint2 v; asm volatile("ld.shared.v2.u32 {%0,%1}, [%2];" : "=r"(v.x), "=r"(v.y) : "r"(a) : "memory"); return v; }
__device__ __forceinline__ uint4 lds128(uint32_t a) { uint4 v; asm volatile("ld.shared.v4.u32 {%0,%1,%2,%3}, [%4];" : "=r"(v.x), "=r"(v.y), "=r"(v.z), "=r"(v.w) : "r"(a) : "memory"); return v; }
__device__ __forceinline__ void sts16(uint32_t a, uint32_t v) { asm volatile("st.shared.u16 [%0], %1;" ::"r"(a), "h"((unsigned short)v) : "memory"); }
__device__ __forceinline__ void sts32(uint32_t a, uint32_t v) { asm volatile("st.shared.u32 [%0], %1;" ::"r"(a), "r"(v) : "memory"); }
__device__ __forceinline__ void sts64(uint32_t a, uint32_t x, uint32_t y) { asm volatile("st.shared.v2.u32 [%0], {%1,%2};" ::"r"(a), "r"(x), "r"(y) : "memory"); }
__device__ __forceinline__ void sts128(uint32_t a, uint32_t x, uint32_t y, uint32_t z, uint32_t w) { asm volatile("st.shared.v4.u32 [%0], {%1,%2,%3,%4};" ::"r"(a), "r"(x), "r"(y), "r"(z), "r"(w) : "memory"); }
__device__ __forceinline__ float bflo(uint32_t v) { return __uint_as_float(v << 16); }
__device__ __forceinline__ float bfhi(uint32_t v) { return __uint_as_float(v & 0xffff0000u); }
__device__ __forceinline__ uint32_t pack_bf(float lo, float hi) { uint32_t r; asm("cvt.rn.bf16x2.f32 %0, %1, %2;" : "=r"(r) : "f"(hi), "f"(lo)); return r; }
__device__ __forceinline__ uint32_t pack_h(float lo, float hi) { uint32_t r; asm("cvt.rn.f16x2.f32 %0, %1, %2;" : "=r"(r) : "f"(hi), "f"(lo)); return r; }
__device__ __forceinline__ float rnd_bf(float v) { return __bfloat162float(__float2bfloat16_rn(v)); }
__device__ __forceinline__ float ex2a(float v) { float r; asm("ex2.approx.ftz.f32 %0, %1;" : "=f"(r) : "f"(v)); return r; }
__device__ __forceinline__ float tanha(float v) { float r; asm("tanh.approx.f32 %0, %1;" : "=f"(r) : "f"(v)); return r; }
__device__ __forceinline__ uint32_t hadd(uint32_t a, uint32_t b) { uint32_t r; asm("add.rn.f16x2 %0, %1, %2;" : "=r"(r) : "r"(a), "r"(b)); return r; }
__device__ __forceinline__ uint32_t badd(uint32_t a, uint32_t b) { uint32_t r; asm("add.rn.bf16x2 %0, %1, %2;" : "=r"(r) : "r"(a), "r"(b)); return r; }
__device__ __forceinline__ uint32_t bmul(uint32_t a, uint32_t b) { uint32_t r; asm("mul.rn.bf16x2 %0, %1, %2;" : "=r"(r) : "r"(a), "r"(b)); return r; }
__device__ __forceinline__ uint32_t bsub(uint32_t a, uint32_t b) { uint32_t r; asm("sub.rn.bf16x2 %0, %1, %2;" : "=r"(r) : "r"(a), "r"(b)); return r; }
__device__ __forceinline__ uint32_t dup(uint32_t v, uint32_t nz) { uint32_t r; asm volatile("add.rn.f32 %0, %1, %2;" : "=r"(r) : "r"(v), "r"(nz)); return r; }
__device__ __forceinline__ void bmma(float* c, uint32_t a0, uint32_t a1, uint32_t a2, uint32_t a3, uint32_t b0, uint32_t b1) {
  asm("mma.sync.aligned.m16n8k16.row.col.f32.bf16.bf16.f32 {%0,%1,%2,%3}, {%4,%5,%6,%7}, {%8,%9}, {%0,%1,%2,%3};"
      : "+f"(c[0]), "+f"(c[1]), "+f"(c[2]), "+f"(c[3]) : "r"(a0), "r"(a1), "r"(a2), "r"(a3), "r"(b0), "r"(b1));
}
__device__ __forceinline__ uint32_t odd_pair(uint32_t a, uint32_t b) { return __byte_perm(a, b, 0x5432); }
__device__ __forceinline__ int upos(int c) { return c ^ (c >> 5) ^ ((c >> 3) & 1); }
__device__ __forceinline__ int uoff(int pos) { return (pos >> 1) * 160 + (pos & 1) * 16; }

struct cf { float r, i; };
__device__ __forceinline__ cf cmul(cf a, cf b) { cf o; o.r = fmaf(a.r, b.r, -a.i * b.i); o.i = fmaf(a.r, b.i, a.i * b.r); return o; }
__device__ __forceinline__ cf csq(cf a) { cf o; o.r = fmaf(a.r, a.r, -a.i * a.i); o.i = (a.r + a.r) * a.i; return o; }
struct hp { uint32_t r, i; };
__device__ __forceinline__ hp hpack(cf a, cf b) { hp o; o.r = pack_h(a.r, b.r); o.i = pack_h(a.i, b.i); return o; }
__device__ __forceinline__ hp hmulc(hp a, uint32_t c) {
  __half2 ar = *reinterpret_cast<__half2*>(&a.r), ai = *reinterpret_cast<__half2*>(&a.i), cc = *reinterpret_cast<__half2*>(&c);
  __half2 orr = __hfma2(ar, __low2half2(cc), __hneg2(__hmul2(ai, __high2half2(cc))));
  __half2 oi = __hfma2(ar, __high2half2(cc), __hmul2(ai, __low2half2(cc)));
  hp o; o.r = *reinterpret_cast<uint32_t*>(&orr); o.i = *reinterpret_cast<uint32_t*>(&oi); return o;
}
__device__ __forceinline__ void sts_tile(uint32_t a, const hp* t) {
  sts128(a, t[0].r, t[1].r, t[2].r, t[3].r);
  sts128(a + 512, t[0].i, t[1].i, t[2].i, t[3].i);
}
template <int STEP> __device__ __forceinline__ void put2(uint32_t a0, uint32_t a1, uint32_t h, uint32_t sel) {
  const uint32_t x = __byte_perm(h, h, sel), y = x >> 16;
  sts16(a0, x); sts16(a0 + STEP * 4 + 2, x);
  sts16(a1, y); sts16(a1 + STEP * 4 + 2, y);
}

__device__ __forceinline__ void spare_work(const Params& p, const CUtensorMap* tmW1, int k, int tid) {
  const int lane = tid & 31;
  unsigned ep = 0;
  if (tid >= 480) ep = p.scr->epoch[128 + k] + 1;
  if (tid == 480) {
    for (int i = 0; i < 8; i++) mbar_init(bar + 8 * i, i < 4 ? 1 : 12);
    asm volatile("fence.mbarrier_init.release.cluster;" ::: "memory");
    fence_async_smem();
  }
  __syncthreads();
  float a[2][4] = {{0.f, 0.f, 0.f, 0.f}, {0.f, 0.f, 0.f, 0.f}};
  if (tid >= 480) {
    if (elect1()) {
#pragma unroll 1
      for (int s = 0; s < 10; s++) {
        mbar_wait(bar + 8 * (4 + (s & 3)), ((s >> 2) & 1) ^ 1);
        mbar_expect(bar + 8 * (s & 3), 49152);
#pragma unroll 1
        for (int b = 0; b < 2; b++) tma3d(sb + (s & 3) * 49152 + b * 24576, tmW1, 0, s * 64, k * 6 + b * 3, bar + 8 * (s & 3));
      }
    }
    __syncwarp();
  } else if (tid < 384) {
    const uint32_t idn = (lane >> 3) == (lane & 3) ? ((lane & 4) ? 0x3f800000u : 0x3f80u) : 0u;
#pragma unroll 1
    for (int s = 0; s < 10; s++) {
      mbar_wait(bar + 8 * (s & 3), (s >> 2) & 1);
      const uint32_t ad = sb + (s & 3) * 49152 + (tid >> 6) * 8192 + (tid & 63) * 16;
#pragma unroll
      for (int i = 0; i < 8; i += 2) {
        const uint4 v = lds128(ad + i * 1024), w = lds128(ad + i * 1024 + 1024);
        bmma(a[0], v.x, v.y, w.x, w.y, idn, idn);
        bmma(a[1], v.z, v.w, w.z, w.w, idn, idn);
      }
      __syncwarp();
      if (lane == 0) mbar_arrive(bar + 8 * (4 + (s & 3)));
    }
    const int rho = (tid >> 3) & 7;
    const uint32_t ad = sb + 196608 + rho * 1536 + ((tid >> 6) * 8 + ((tid & 7) ^ rho)) * 32;
    sts128(ad, __float_as_uint(a[0][0]), __float_as_uint(a[0][1]), __float_as_uint(a[0][2]), __float_as_uint(a[0][3]));
    sts128(ad + 16, __float_as_uint(a[1][0]), __float_as_uint(a[1][1]), __float_as_uint(a[1][2]), __float_as_uint(a[1][3]));
  }
  __syncthreads();
  if (tid < 384) {
    float s = 0.f;
#pragma unroll
    for (int r = 0; r < 8; r++) s += __uint_as_float(lds32(sb + 196608 + r * 1536 + tid * 4));
    p.scr->cs[k * 384 + tid] = s;
  }
  __syncthreads();
  if (tid == 480) {
    publish(p.scr->cnt + C_CS * 32);
    p.scr->epoch[128 + k] = ep;
    poll_cnt(p.scr->cnt + C_LN * 32, ep * 128);
  }
}

__device__ __forceinline__ void load1(int s, const CUtensorMap* tmX, const CUtensorMap* tmW1, int rg1, int j1) {
  const uint32_t d = sb + (s & 3) * SLOT1, mb = bar + 8 * (B_FULL1 + s);
  mbar_expect(mb, SLOT1);
  tma2d(d, tmX, s * 64, rg1 * 128, mb);
  tma3d(d + 16384, tmW1, 0, s * 64, j1 * 3, mb);
}
__device__ __forceinline__ void load_x(uint32_t (&xv)[2][10], const __nv_bfloat16* xc, int rstep, int q) {
#pragma unroll
  for (int r = 0; r < 2; r++) {
    const uint4 a = __ldg((const uint4*)(xc + r * rstep) + q), b = __ldg((const uint4*)(xc + r * rstep) + 4 + q);
    const uint2 c = __ldg((const uint2*)(xc + r * rstep + 64) + q);
    xv[r][0] = a.x; xv[r][1] = a.y; xv[r][2] = a.z; xv[r][3] = a.w; xv[r][4] = b.x; xv[r][5] = b.y; xv[r][6] = b.z; xv[r][7] = b.w;
    xv[r][8] = c.x; xv[r][9] = c.y;
  }
}

template <bool USE_SMID>
__global__ void __launch_bounds__(512, 1)
fused_s4_ffn_kernel(const Params p, const __grid_constant__ CUtensorMap tmX, const __grid_constant__ CUtensorMap tmW1,
                    const __grid_constant__ CUtensorMap tmU, const __grid_constant__ CUtensorMap tmW2) {
  extern __shared__ __align__(1024) unsigned char smem_raw[];
  const int tid = threadIdx.x, lane = tid & 31;
  const int warp = __shfl_sync(0xffffffffu, tid >> 5, 0);
  const int g = lane >> 2, q = lane & 3;
  uint32_t sid;
  if (USE_SMID) asm("mov.u32 %0, %smid;" : "=r"(sid)); else sid = blockIdx.x;
  if (sid - 120u < 4u) { spare_work(p, &tmW1, sid - 120, tid); return; }
  const int wid = sid < 120 ? sid : sid - 4;
  unsigned* const cnt = p.scr->cnt;

  float kacc[5][4];
  const int kpart = (warp >= 5) + (warp >= 10), kch = warp - 5 * kpart;
  float dt, k0;
  uint32_t xv[2][10], xs[2], mw, pds;
  {
    uint32_t pa[6], pld;
    unsigned ep0;
    if (warp < 15) {
      const int ch = (wid >> 4) * 80 + frag_col((wid & 15) * 5 + kch);
      const int o = (ch * 3 + kpart) * 32 + lane;
      pa[0] = __ldg((const uint32_t*)p.are + o); pa[1] = __ldg((const uint32_t*)p.aim + o);
      pa[2] = __ldg((const uint32_t*)p.bre + o); pa[3] = __ldg((const uint32_t*)p.bim + o);
      pa[4] = __ldg((const uint32_t*)p.cre + o); pa[5] = __ldg((const uint32_t*)p.cim + o);
      pld = __ldg((const unsigned short*)p.logdt + ch);
      pds = __ldg((const unsigned short*)p.dskip + ch);
    } else {
      ep0 = p.scr->epoch[wid];
      if ((uint32_t)__cvta_generic_to_shared(smem_raw) != sb) __trap();
    }
    if (elect1()) {
      const int gi = (warp + 1) & 15;
#pragma unroll
      for (int i = 0; i < 5; i++) mbar_init(bar + 40 * gi + 8 * i, gi < 8 ? 1 : gi == 8 ? 4 : 8);
      asm volatile("fence.mbarrier_init.release.cluster;" ::: "memory");
    }
    if (warp == 15) {
      sts64(sb + OFF_ZERO + (lane & 15) * 8 + (lane >> 4) * 640, 0, 0);
      int gpc, i;
      if (sid < 64) { gpc = (sid & 15) >> 1; i = sid >> 4; }
      else if (sid < 120) { const int t = sid - 64; i = t / 14; gpc = 1 + ((t - i * 14) >> 1); i += 4; }
      else { gpc = 0; i = 4 + ((sid - 124) >> 1); }
      const int qi = ((0x52741630 >> (4 * i)) & 7) * 2 + (sid & 1);
      const int rg = 4 * (gpc >> 1) + (qi >> 2), jc = 4 * (gpc & 1) + (qi & 3);
      sts64(sb + OFF_EP + 8, rg, jc);
      __syncwarp();
      if (elect1()) {
        if (DELAY_NS) __nanosleep(DELAY_NS);
        bulk_prefetch(p.x + wid * 16 * DM, 16 * DM * 2);
#pragma unroll 1
        for (int s = 0; s < 4; s++) load1(s, &tmX, &tmW1, rg, jc);
        bulk_prefetch(p.w1 + wid * 5 * FF, 5 * FF * 2);
        bulk_prefetch(p.w2 + wid * 12 * DM, 12 * DM * 2);
        asm volatile("prefetch.tensormap [%0];\nprefetch.tensormap [%1];" ::"l"(&tmU), "l"(&tmW2) : "memory");
      }
    }
#pragma unroll
    for (int j = 0; j < 5; j++) { kacc[j][0] = kacc[j][1] = kacc[j][2] = kacc[j][3] = 0.f; }
    float zr, th, zr1, th1;
    cf c, c1;
    const uint32_t ks = sb + OFF_KS + warp * 4096;
    if (warp < 15) {
      dt = rnd_bf(expf(bflo(pld)));
      c = cmul(cf{bflo(pa[4]), bflo(pa[5])}, cf{bflo(pa[2]), bflo(pa[3])});
      c1 = cmul(cf{bfhi(pa[4]), bfhi(pa[5])}, cf{bfhi(pa[2]), bfhi(pa[3])});
      mw = __reduce_max_sync(0xffffffffu, __float_as_uint(fmaxf(fmaxf(fabsf(c.r), fabsf(c.i)), fmaxf(fabsf(c1.r), fabsf(c1.i)))));
      mw = min(max(mw & 0x7f800000u, 20u << 23), 240u << 23);
      const float sc = __uint_as_float((259u << 23) - mw), dl2 = dt * 1.4426950408889634f;
      k0 = c.r + c1.r;
      zr = bflo(pa[0]) * dl2; th = bflo(pa[1]) * dt; zr1 = bfhi(pa[0]) * dl2; th1 = bfhi(pa[1]) * dt;
      c.r *= sc; c.i *= sc; c1.r *= sc; c1.i *= sc;
    }
    __syncwarp();
    if (warp >= 8) {
      const __nv_bfloat16* xr = p.x + (wid * 16 + ((g >> 1) << 2) + (g & 1)) * DM;
      load_x(xv, xr + (warp - 8) * 80, 2 * DM, q);
      xs[0] = __ldg((const uint32_t*)xr); xs[1] = __ldg((const uint32_t*)(xr + 2 * DM));
    }
    {
      const uint32_t ka = ks + (lane >> 3) * 512 + (lane & 7) * 16;
      const uint32_t kb = ks + ((lane >> 3) & 1) * 512 + ((lane >> 4) * 8 + (lane & 7)) * 16;
#pragma unroll 1
      for (int it = 0; it < 2; it++) {
        if (it == 1 && warp >= 8) {
          float sm[4] = {0.f, 0.f, 0.f, 0.f}, g0[4] = {0.f, 0.f, 0.f, 0.f}, g1[4] = {0.f, 0.f, 0.f, 0.f};
#pragma unroll
          for (int r = 0; r < 2; r++)
            xs[r] = fabsf(bflo(xs[r]) - bfhi(xs[r])) * 8.f < fabsf(bflo(xs[r])) ? __byte_perm(xs[r], 0, 0x1010) : 0u;
#pragma unroll
          for (int i = 0; i < 10; i += 2) {
            const uint32_t a0 = bsub(xv[0][i], xs[0]), a1 = bsub(xv[1][i], xs[1]), a2 = bsub(xv[0][i + 1], xs[0]), a3 = bsub(xv[1][i + 1], xs[1]);
            bmma(sm, a0, a1, a2, a3, 0x3f803f80u, 0x3f803f80u);
            bmma(g0, a0, a1, a2, a3, xv[0][i], xv[0][i + 1]);
            bmma(g1, a0, a1, a2, a3, xv[1][i], xv[1][i + 1]);
          }
          if (q == (g >> 1))
            sts128(sb + OFF_LNP + (warp - 8) * 128 + g * 16, __float_as_uint(sm[0]), __float_as_uint((g & 1) ? g0[1] : g0[0]),
                   __float_as_uint(sm[2]), __float_as_uint((g & 1) ? g1[3] : g1[2]));
          if (warp < 15) bar_arrive(1, 256);
        }
        if (warp == 15) continue;
        float m = ex2a(zr);
        const cf w1 = cf{m * __cosf(th), m * __sinf(th)};
        m = ex2a(zr * 8.f);
        const cf w8 = cf{m * __cosf(th * 8.f), m * __sinf(th * 8.f)};
        const cf w16 = csq(w8), w32 = csq(w16), w64 = csq(w32), w128 = csq(w64), w256 = csq(w128), w512 = csq(w256), w1024 = csq(w512);
        hp lo[8];
        lo[0] = hpack(cf{1.f, 0.f}, cf{w8.r, -w8.i});
        lo[1] = hmulc(lo[0], pack_h(w16.r, -w16.i));
        { const uint32_t k = pack_h(w32.r, -w32.i); lo[2] = hmulc(lo[0], k); lo[3] = hmulc(lo[1], k); }
        { const uint32_t k = pack_h(w64.r, -w64.i);
#pragma unroll
          for (int i = 0; i < 4; i++) lo[4 + i] = hmulc(lo[i], k); }
        const uint32_t st = ks + lane * 16;
        sts128(st, lo[0].r, lo[1].r, lo[2].r, lo[3].r);
        sts128(st + 512, lo[4].r, lo[5].r, lo[6].r, lo[7].r);
        sts128(st + 1024, lo[0].i, lo[1].i, lo[2].i, lo[3].i);
        sts128(st + 1536, lo[4].i, lo[5].i, lo[6].i, lo[7].i);
        const cf t1 = cmul(c, w1), t2 = cmul(t1, w1), t3 = cmul(t2, w1), t4 = cmul(t3, w1);
        const cf t5 = cmul(t4, w1), t6 = cmul(t5, w1), t7 = cmul(t6, w1), t8 = cmul(c, w8);
        hp T0[4], T1[4], T2[4], T3[4], T4[4];
        T0[0] = hpack(t4, t8); T0[1] = hpack(t2, t6); T0[2] = hpack(t1, t5); T0[3] = hpack(t3, t7);
        const uint32_t k128 = pack_h(w128.r, w128.i), k256 = pack_h(w256.r, w256.i), k512 = pack_h(w512.r, w512.i);
#pragma unroll
        for (int i = 0; i < 4; i++) T1[i] = hmulc(T0[i], k128);
        sts_tile(st + 2048, T0);
        sts_tile(st + 3072, T1);
        __syncwarp();
        uint32_t af[4][4];
#pragma unroll
        for (int mg = 0; mg < 4; mg++) ldsm4t(af[mg], ka + mg * 128);
#pragma unroll
        for (int j = 0; j < 2; j++)
#pragma unroll
          for (int mg = 0; mg < 4; mg += 2) {
            uint32_t b[4];
            ldsm4t(b, kb + 2048 + j * 1024 + mg * 128);
            hmma(kacc[j], af[mg][0], af[mg][1], af[mg][2], af[mg][3], b[0], b[1]);
            hmma(kacc[j], af[mg + 1][0], af[mg + 1][1], af[mg + 1][2], af[mg + 1][3], b[2], b[3]);
          }
        T2[0] = hmulc(T0[0], k256); T2[1] = hmulc(T0[1], k256); T2[2] = hmulc(T1[0], k256); T2[3] = hmulc(T1[1], k256);
        T3[0] = hmulc(T0[0], k512); T3[1] = hmulc(T1[0], k512); T3[2] = hmulc(T2[0], k512); T3[3] = hmulc(T2[2], k512);
        { const cf u0 = cmul(t8, w1024), u1 = cmul(u0, w128);
          T4[0] = hpack(u0, u1); T4[1] = hmulc(T4[0], k256); T4[2] = hmulc(T4[0], k512); T4[3] = hmulc(T4[1], k512); }
        __syncwarp();
        sts_tile(st, T2);
        sts_tile(st + 1024, T3);
        sts_tile(st + 2048, T4);
        __syncwarp();
#pragma unroll
        for (int j = 0; j < 3; j++)
#pragma unroll
          for (int mg = 0; mg < 4; mg += 2) {
            uint32_t b[4];
            ldsm4t(b, kb + j * 1024 + mg * 128);
            hmma(kacc[2 + j], af[mg][0], af[mg][1], af[mg][2], af[mg][3], b[0], b[1]);
            hmma(kacc[2 + j], af[mg + 1][0], af[mg + 1][1], af[mg + 1][2], af[mg + 1][3], b[2], b[3]);
          }
        __syncwarp();
        zr = zr1; th = th1; c = c1;
      }
    }
    if (warp < 10) {
#pragma unroll
      for (int j = 0; j < 5; j++)
        sts128(ks + j * 512 + lane * 16, __float_as_uint(kacc[j][0]), __float_as_uint(kacc[j][1]), __float_as_uint(kacc[j][2]), __float_as_uint(kacc[j][3]));
      sts64(ks + 2560 + lane * 8, __float_as_uint(k0), mw);
    } else if (warp == 15) {
      if (lane == 0) { p.scr->epoch[wid] = ep0 + 1; sts32(sb + OFF_EP, ep0 + 1); }
      bar_sync(1, 256);
      float s1 = 0.f, s2 = 0.f;
#pragma unroll
      for (int w = 0; w < 8; w++) {
        const uint2 v = lds64(sb + OFF_LNP + w * 128 + g * 16 + (q & 1) * 8);
        s1 += __uint_as_float(v.x); s2 += __uint_as_float(v.y);
      }
      const float md = s1 * (1.f / DM), mean = bflo((q & 1) ? xs[1] : xs[0]) + md;
      const float var = fmaxf(fmaf(-md, mean, s2 * (1.f / DM)), 0.f);
      const float m = rnd_bf(mean);
      float sd, ri;
      asm("sqrt.approx.f32 %0, %1;" : "=f"(sd) : "f"(rnd_bf(rnd_bf(var) + 1e-5f)));
      asm("rcp.approx.f32 %0, %1;" : "=f"(ri) : "f"(rnd_bf(sd)));
      if (q < 2) {
        p.scr->stats[wid * 16 + ((g >> 1) << 2) + (g & 1) + 2 * q] = make_float2(-m, 0.5f * ri);
        sts64(sb + OFF_STAT + g * 16 + q * 8, __float_as_uint(-m * ri), __float_as_uint(ri));
      }
    }
  }
  __syncthreads();

  if (warp < 8) {
    float acc[96];
    const uint32_t alo = ((sb >> 4) | (1 << 16)) + (warp >> 2) * 512;
#pragma unroll 1
    for (int s = 0; s < 10; s++) {
      const uint32_t so = (s & 3) * (SLOT1 >> 4);
      mbar_wait(bar + 8 * (B_FULL1 + s), 0);
      wg_fence();
#pragma unroll
      for (int kk = 0; kk < 4; kk++)
        wgmma_n192(acc, dsc(alo + so + kk * 2, 0x40000040u), dsc((((sb + 16384) >> 4) | (512 << 16)) + so + kk * 128, 0x40000040u), (s | kk) != 0);
      wg_commit();
      wg_wait<1>();
      if (lane == 0) mbar_arrive(bar + 8 * (B_REL1 + s));
    }
    wg_wait<0>();
    bar_arrive(14, 512);
    mbar_wait(bar + 8 * B_EPI, 0);
    const uint2 s0 = lds64(sb + OFF_STAT + (warp * 16 + g) * 8), s1 = lds64(sb + OFF_STAT + (warp * 16 + g + 8) * 8);
    const float nm0 = __uint_as_float(s0.x), r0 = __uint_as_float(s0.y), nm1 = __uint_as_float(s1.x), r1 = __uint_as_float(s1.y);
    const uint4 erj = lds128(sb + OFF_EP);
    const unsigned ep = erj.x;
    const int rg1 = erj.z, j1 = erj.w;
    uint4* hd = p.scr->h + (rg1 * 24 + j1) * 1024 + warp * 128 + q * 8 + g;
#pragma unroll
    for (int grp = 0; grp < 6; grp++) {
      uint32_t o0[4], o1[4];
#pragma unroll
      for (int tl = 0; tl < 4; tl++) {
        const int nt = grp * 4 + tl;
        const uint2 cs = lds64(sb + OFF_CS + (nt * 8 + 2 * q) * 4);
        const float ca = __uint_as_float(cs.x), cb = __uint_as_float(cs.y);
        const float a = fmaf(nm0, ca, acc[4 * nt]) * r0, b = fmaf(nm0, cb, acc[4 * nt + 1]) * r0;
        const float c = fmaf(nm1, ca, acc[4 * nt + 2]) * r1, d = fmaf(nm1, cb, acc[4 * nt + 3]) * r1;
        o0[tl] = pack_bf(fmaf(a, tanha(a), a), fmaf(b, tanha(b), b));
        o1[tl] = pack_bf(fmaf(c, tanha(c), c), fmaf(d, tanha(d), d));
      }
      uint4* dst = hd + (grp >> 1) * 8192 + (grp & 1) * 32;
      dst[0] = make_uint4(o0[0], o0[1], o0[2], o0[3]);
      dst[64] = make_uint4(o1[0], o1[1], o1[2], o1[3]);
      if (PACE_NS) __nanosleep(PACE_NS);
      if (grp == 1) {
        if (warp == 7) { bar_sync(2, 448); if (lane == 0) publish(cnt + C_H0 * 32); __syncwarp(); }
        else bar_arrive(2, 448);
      }
    }
    if (warp == 6) { bar_sync(11, 256); if (lane == 0) publish(cnt + (C_H1 + rg1) * 32); __syncwarp(); }
    else bar_arrive(11, 256);
    const int go = (rg1 * 128 + warp * 16 + g) * DM + j1 * 80;
    load_x(xv, p.x + go, 8 * DM, q);
    if (warp == 4) {
      if (elect1()) {
        poll_cnt(cnt + C_H0 * 32, ep * 128);
#pragma unroll 1
        for (int s = 0; s < NS2 - 1; s++) {
          if (s == 3) poll_cnt(cnt + (C_H1 + rg1) * 32, ep * 8);
          if (s >= 3) mbar_wait(bar + 8 * (B_FREE + (s == 3 ? 0 : s - 2)), 0);
          if (s == 4) mbar_wait(bar + 8 * (B_FREE + 1), 0);
          const uint32_t mb = bar + 8 * (B_FULL2 + s);
          mbar_expect(mb, SLOT2);
          bulk_g2s(sb + s * SLOT2, p.scr->h + (rg1 * 24 + s) * 1024, 16384, mb);
          bulk_g2s(sb + s * SLOT2 + 16384, p.scr->w2p + (j1 * 24 + s) * 640, 10240, mb);
        }
      }
      __syncwarp();
    }
    float acc2[40];
    bar_sync(8, 384);
    {
      const uint32_t al2 = ((sb >> 4) | (8 << 16)) + (warp >> 2) * 512;
      uint32_t so = 0;
#pragma unroll 1
      for (int s = 0; s < 24; s++) {
        mbar_wait(bar + 8 * (B_FULL2 + s), 0);
        wg_fence();
#pragma unroll
        for (int kk = 0; kk < 4; kk++)
          wgmma_n80(acc2, dsc(al2 + so + kk * 16, 64), dsc((((sb + 16384) >> 4) | (80 << 16)) + so + kk * 160, 8), (s | kk) != 0);
        wg_commit();
        so = so == (NS2 - 1) * (SLOT2 >> 4) ? 0 : so + (SLOT2 >> 4);
        wg_wait<1>();
        if (lane == 0) mbar_arrive(bar + 8 * (B_REL2 + s));
      }
    }
    mbar_wait(bar + 8 * B_SFULL, 0);
    uint32_t sv[5][4];
    {
      const int i = lane & 7, mi = lane >> 3;
      const uint32_t a = sb + OFF_U + ((mi >> 1) * 8 + i) * 256 + (((2 * warp + (mi & 1)) ^ i) << 4);
#pragma unroll
      for (int k = 0; k < 5; k++) ldsm4t(sv[k], a + k * 4096);
    }
    wg_wait<0>();
#pragma unroll
    for (int hh = 0; hh < 2; hh++) {
      uint32_t o[10];
#pragma unroll
      for (int tl = 0; tl < 10; tl++) {
        const uint32_t xw = xv[hh][tl];
        const uint32_t sw = sv[tl >> 1][(tl & 1) * 2 + hh];
        const float a = acc2[4 * tl + 2 * hh], b = acc2[4 * tl + 2 * hh + 1];
        o[tl] = pack_bf(fmaf(bflo(sw), fmaf(a, tanha(a), a), bflo(xw)), fmaf(bfhi(sw), fmaf(b, tanha(b), b), bfhi(xw)));
      }
      __nv_bfloat16* op = p.out + go + hh * 8 * DM;
      ((uint4*)op)[q] = make_uint4(o[0], o[1], o[2], o[3]);
      ((uint4*)op)[4 + q] = make_uint4(o[4], o[5], o[6], o[7]);
      ((uint2*)(op + 64))[q] = make_uint2(o[8], o[9]);
    }
  } else {
    const int cw = warp - 8;
    const uint4 erj = lds128(sb + OFF_EP);
    const unsigned ep = erj.x;
    const int rg1 = erj.z, j1 = erj.w;
    {
      const uint4 st = lds128(sb + OFF_STAT + g * 16);
      const float n0 = __uint_as_float(st.x), r0 = __uint_as_float(st.y), n1 = __uint_as_float(st.z), r1 = __uint_as_float(st.w);
      const int up = upos(2 * wid);
      uint2* dst = (uint2*)p.scr->uT + ((up >> 1) * DM + cw * 80) * 4 + (lane ^ ((up & 1) << 1));
#pragma unroll
      for (int i = 0; i < 10; i++) {
        const uint32_t a = movm(pack_h(fmaf(bflo(xv[0][i]), r0, n0), fmaf(bfhi(xv[0][i]), r0, n0)));
        const uint32_t b = movm(pack_h(fmaf(bflo(xv[1][i]), r1, n1), fmaf(bfhi(xv[1][i]), r1, n1)));
        dst[i * 32] = make_uint2(a, b);
      }
    }
    if (warp == 8) {
      bar_sync(12, 256);
      if (lane == 0) publish(cnt + C_LN * 32);
      __syncwarp();
    } else bar_arrive(12, 256);
    if (warp == 15) {
      if (elect1()) {
#pragma unroll 1
        for (int s = 4; s < 10; s++) {
          mbar_wait(bar + 8 * (B_REL1 + s - 3), 0);
          load1(s, &tmX, &tmW1, rg1, j1);
        }
      }
      __syncwarp();
    }
    if (warp >= 10 && warp < 15) {
      const uint32_t pb = sb + OFF_P + kch * 3072, pk = sb + OFF_KS + kch * 4096;
      const uint2 e0 = lds64(pk + 2560 + lane * 8), e1 = lds64(pk + 5 * 4096 + 2560 + lane * 8);
      const float dsk = bflo(pds);
      uint32_t kex = __float_as_uint(fmaxf(__uint_as_float(max(max(e0.y, e1.y), mw)) * dt, fabsf(dsk) * (1.f / 256.f))) >> 23;
      kex = min(max(kex, 20u), 240u);
      const float s2 = __uint_as_float((258 - kex) << 23), sd = s2 * dt * (1.f / 32.f);
      const float f0 = __uint_as_float(e0.y) * sd, f1 = __uint_as_float(e1.y) * sd, f2 = __uint_as_float(mw) * sd;
      k0 += __uint_as_float(e0.x) + __uint_as_float(e1.x);
#pragma unroll
      for (int o = 16; o; o >>= 1) k0 += __shfl_xor_sync(0xffffffffu, k0, o);
      const float k0n = fmaf(k0, dt, dsk) * s2;
      uint32_t h[5][2];
#pragma unroll
      for (int j = 0; j < 5; j++) {
        const uint4 a = lds128(pk + j * 512 + lane * 16), b = lds128(pk + 5 * 4096 + j * 512 + lane * 16);
#pragma unroll
        for (int e = 0; e < 4; e++) kacc[j][e] = fmaf(__uint_as_float((&a.x)[e]), f0, fmaf(__uint_as_float((&b.x)[e]), f1, kacc[j][e] * f2));
        if (j == 1) {
          const float k256 = __shfl_sync(0xffffffffu, kacc[1][3], 28);
          if (lane == 31) kacc[1][3] -= k256;
        }
        if (j == 2 || j == 3) { h[j][0] = pack_h(kacc[j][0], kacc[j][2]); h[j][1] = pack_h(kacc[j][1], kacc[j][3]); }
        else { h[j][0] = pack_h(kacc[j][0], kacc[j][1]); h[j][1] = pack_h(kacc[j][2], kacc[j][3]); }
      }
      fence_async_smem();
      bar_arrive(4, 192);
#pragma unroll
      for (int i = 0; i < 6; i++) sts128(pb + i * 512 + lane * 16, 0, 0, 0, 0);
      __syncwarp();
      {
        const int sw = g >> 2;
        const uint32_t sel = sw ? 0x1032 : 0x3210;
        const uint32_t a = pb + (P0 + 8 * g + ((0x3124 >> (4 * q)) & 7)) * 4, a0 = a + sw * 16, a1 = a + 16 - sw * 16;
        put2<1>(a0, a1, h[0][0], sel);
        put2<1>(a0 + 256, a1 + 256, h[0][1], sel);
        put2<1>(a0 + 512, a1 + 512, h[1][0], sel);
        put2<1>(lane == 28 ? pb + PB1 * 4 : a0 + 768, a1 + 768, h[1][1], sel);
      }
      {
        const int sw = q >> 1;
        const uint32_t sel = sw ? 0x1032 : 0x3210;
        uint32_t a = pb + (((q & 1) ? PA1 : PB1 + 1) + 32 * sw + 2 * g) * 4;
        put2<1>(a + sw * 64, a + 64 - sw * 64, h[2][0], sel);
        put2<1>(a + 4 + sw * 64, a + 68 - sw * 64, h[2][1], sel);
        a = pb + (PA2 + g + 16 * q) * 4;
        put2<2>(a + sw * 32, a + 32 - sw * 32, h[3][0], sel);
        put2<2>(a + (PB2 - PA2) * 4 + sw * 32, a + (PB2 - PA2) * 4 + 32 - sw * 32, h[3][1], sel);
        a = pb + (((g & 1) ? PB3 : PA3) + (g >> 1) + 16 * q) * 4;
        const uint32_t hx = sw ? h[4][1] : h[4][0], hy = sw ? h[4][0] : h[4][1];
        put2<1>(a + sw * 16, a + 32 + sw * 16, hx, 0x3210);
        put2<1>(a + 16 - sw * 16, a + 48 - sw * 16, hy, 0x3210);
      }
      if (lane == 30) put2<1>(pb + P0 * 4, pb + (PA1 + 64) * 4, pack_h(k0n, kacc[2][3]), 0x3210);
      if (lane == 31) sts64(sb + OFF_CHC + kch * 8, (kex - 4) * 0x00800080u, __byte_perm(h[3][1], 0, 0x3232));
    }
    if (warp == 8) {
      bar_sync(13, 64);
      if (elect1()) {
        mbar_expect(bar + 8 * B_UFULL, 20480);
        mbar_expect(bar + 8 * B_EPI, 1024 + 768);
        poll_cnt(cnt + C_LN * 32, ep * 128);
        tma2d(sb + OFF_U, &tmU, wid * 80, 0, bar + 8 * B_UFULL);
        bulk_g2s(sb + OFF_STAT, p.scr->stats + rg1 * 128, 1024, bar + 8 * B_EPI);
      }
      __syncwarp();
      bar_arrive(15, 224);
    } else if (warp == 9) {
      bar_sync(4, 192);
      bar_arrive(13, 64);
      if (elect1()) {
        mbar_expect(bar + 8 * B_W2, 96 * 176);
        tma5d(sb + OFF_W2S, &tmW2, (wid & 7) * 80, (wid >> 3) * 3, bar + 8 * B_W2);
        poll_cnt(cnt + C_CS * 32, ep * 4);
        bulk_g2s(sb + OFF_CS, p.scr->cs + j1 * 192, 768, bar + 8 * B_EPI);
      }
      __syncwarp();
    }
    if (warp >= 9 && warp < 15) {
      const int uu = (warp - 9) >> 1, G = (warp - 9) & 1;
      const int grp = (wid >> 3) * 3 + uu, jj = grp / 6, rem = grp - jj * 6;
      const uint32_t a = sb + OFF_W2S + (uu * 32 + lane) * 176;
      uint4* dst = p.scr->w2p + ((wid & 7) * 24 + 8 * (rem >> 1) + jj) * 640 + ((rem & 1) * 4 + (lane >> 3)) * 80 + (lane & 7);
      mbar_wait(bar + 8 * B_W2, 0);
      const uint4 wv[4] = {lds128(a + G * 64), lds128(a + G * 64 + 16), lds128(a + G * 64 + 32), lds128(a + G * 64 + 48)};
      const uint4 t0 = lds128(a + 128), t1 = lds128(a + 144);
      uint32_t w[20];
#pragma unroll
      for (int i = 0; i < 16; i++) w[i] = bmul((&wv[i >> 2].x)[i & 3], 0x3f003f00u);
      w[16] = bmul(G ? t0.y : t0.x, 0x3f003f00u); w[17] = bmul(G ? t0.w : t0.z, 0x3f003f00u);
      w[18] = bmul(G ? t1.y : t1.x, 0x3f003f00u); w[19] = bmul(G ? t1.w : t1.z, 0x3f003f00u);
      bar_sync(15, 224);
#pragma unroll
      for (int i = 0; i < 4; i++) dst[G * 32 + 8 * i] = make_uint4(w[i], w[4 + i], w[8 + i], w[12 + i]);
      dst[64 + G * 8] = make_uint4(w[16], w[17], w[18], w[19]);
      bar_arrive(2, 448);
      if (warp == 12) bar_arrive(3, 64);
    } else if (warp == 15) bar_sync(3, 64);
    mbar_wait(bar + 8 * B_UFULL, 0);
#pragma unroll 1
    for (int ch = (cw >> 2) * 4; ch != 4 + (cw >> 2); ch = ch == 4 ? 1 : ch + 2) {
      if (ch < 4) mbar_wait(bar + 8 * (B_REL1 + (ch ? 8 : 7)), 0);
      const int qt = (cw + ch) & 3, j = qt * 32 + lane;
      const uint32_t ub = sb + OFF_U + ch * 32, zb = sb + OFF_Z + ch * ZSZ;
      uint32_t w_[20], o_[20], d_[20], b3_[20];
      uint32_t *w = w_ + 8, *o = o_ + 8, *d = d_ + 8, *b3 = b3_ + 8;
      {
        const uint32_t am = j > 0 ? ub + uoff(upos(2 * j - 2)) : sb + OFF_ZERO, a0 = ub + uoff(upos(2 * j));
        const uint2 a = lds64(am + 8);
        const uint4 b = lds128(am ^ 16), c = lds128(a0), e = lds128(a0 ^ 16);
        w[8] = lds32(ub + uoff(upos((2 * j + 2) & 255)));
        w[-6] = a.x; w[-5] = a.y; w[-4] = b.x; w[-3] = b.y; w[-2] = b.z; w[-1] = b.w;
        w[0] = c.x; w[1] = c.y; w[2] = c.z; w[3] = c.w; w[4] = e.x; w[5] = e.y; w[6] = e.z; w[7] = e.w;
      }
#pragma unroll
      for (int i = -1; i <= 7; i++) o[i] = odd_pair(w[i], w[i + 1]);
#pragma unroll
      for (int i = 0; i <= 7; i++) { d[i] = hadd(w[i], o[i]); b3[i] = hadd(d[i], o[i - 1]); }
      if (j < 112) {
        const int gr = j >> 1;
        const uint32_t a1 = zb + ZA1 + 128 + (gr ^ ((gr >> 2) & 1)) * 64 + ((gr >> 1) & 3) * 16 + (j & 1) * 8;
#pragma unroll
        for (int pp = 0; pp < 4; pp++) {
          const uint32_t sel = (pp & 1) ? 0x7632 : 0x5410;
          const int k = pp >> 1;
          sts64(a1 ^ (pp * 16), __byte_perm(w[k - 1], w[k + 1], sel), __byte_perm(w[k + 3], w[k + 5], sel));
          sts64((a1 ^ (pp * 16)) + (ZB1 - ZA1), __byte_perm(b3[k], b3[k + 2], sel), __byte_perm(b3[k + 4], b3[k + 6], sel));
        }
      } else if (j >= 120) {
        sts128(zb + ZA1 + ((lane >> 2) & 1) * (ZB1 - ZA1) + (3 - q) * 16, 0, 0, 0, j == 127 ? w[8] << 16 : 0u);
      }
      if (qt < 3) {
        uint32_t e_[20], b5_[20];
        uint32_t *e = e_ + 8, *b5 = b5_ + 8;
#pragma unroll
        for (int i = -6; i <= -2; i++) o[i] = odd_pair(w[i], w[i + 1]);
#pragma unroll
        for (int i = -6; i <= -1; i++) d[i] = hadd(w[i], o[i]);
#pragma unroll
        for (int i = -5; i <= -1; i++) b3[i] = hadd(d[i], o[i - 1]);
#pragma unroll
        for (int i = -5; i <= 4; i++) e[i] = hadd(d[i - 1], d[i]);
#pragma unroll
        for (int i = -4; i <= 4; i++) b5[i] = hadd(e[i], w[i + 1]);
        const uint32_t a2 = zb + ((j >> 3) * 16 + (j & 7)) * 16;
        sts128(a2 + ZA2, b3[-2], b3[-1], b3[0], b3[1]);
        sts128(a2 + ZA2 + 128, b3[2], b3[3], b3[4], b3[5]);
        sts128(a2 + ZB2, b5[-4], b5[-3], b5[-2], b5[-1]);
        sts128(a2 + ZB2 + 128, b5[0], b5[1], b5[2], b5[3]);
        if (qt < 2) {
          sts128(a2 + ZS, d[-2], d[-1], d[0], d[1]);
          sts128(a2 + ZS + 128, d[2], d[3], d[4], d[5]);
          uint32_t b7[8], b9[8];
#pragma unroll
          for (int i = -4; i <= 3; i++) { b7[i + 4] = hadd(b3[i - 1], e[i + 1]); b9[i + 4] = hadd(e[i - 1], b5[i + 1]); }
          const uint32_t a3 = zb + ((j >> 4) * 32 + (j & 15)) * 16;
          sts128(a3 + ZA3, b7[0], b7[1], b7[2], b7[3]);
          sts128(a3 + ZA3 + 256, b7[4], b7[5], b7[6], b7[7]);
          sts128(a3 + ZB3 + 256, b9[0], b9[1], b9[2], b9[3]);
          if (j < 63) sts128(a3 + ZB3 + ((j & 15) == 15 ? 272 : 16), b9[4], b9[5], b9[6], b9[7]);
          else sts128(zb + ZB3, 0, 0, 0, 0);
        }
      }
    }
    const int wg = warp >> 2, role = (warp + 2 * wg) & 3;
    bar_sync(14, 512);
    const uint32_t nz = lds32(sb + OFF_ZERO) | 0x80000000u;
#pragma unroll 1
    for (int ch = wg - 2; ch < 5; ch += 2) {
      const uint32_t ub = sb + OFF_U + ch * 32, zb = sb + OFF_Z + ch * ZSZ, pb = sb + OFF_P + ch * 3072;
      const uint2 chc = lds64(sb + OFF_CHC + ch * 8);
      const int tid = lds32(sb + OFF_ZERO + 20) + threadIdx.x;
      const int lane = tid & 31, g = lane >> 2, q = lane & 3;
      const uint32_t pa = pb + (g - 2 * q) * 4;
      if (role < 2) {
        float acc[8][4];
#pragma unroll
        for (int r = 0; r < 8; r++) { acc[r][0] = acc[r][1] = acc[r][2] = acc[r][3] = 0.f; }
        float fix = 0.f;
        if (role == 1 && lane == 28) {
          const uint32_t k = lds32(pb + PB1 * 4), u0 = lds32(ub);
          fix = __low2float(*reinterpret_cast<const __half2*>(&k)) * __low2float(*reinterpret_cast<const __half2*>(&u0));
        }
        uint32_t ga[3][2];
#pragma unroll
        for (int gm = 0; gm < 3; gm++) {
          const int hb = 2 * (lane & 7) + role - 2 + gm, l3 = ((lane >> 3) ^ (hb >> 1)) & 7;
          ga[gm][0] = hb < 0 ? sb + OFF_ZERO + ((l3 * 16 + ch * 32) & 127) : ub + hb * 1280 + uoff(l3);
          ga[gm][1] = hb < 0 ? ga[gm][0] ^ 64 : ub + hb * 1280 + uoff(l3 ^ 4);
        }
        uint32_t b[12][4], A[17][4];
#pragma unroll
        for (int i = 11; i >= 8; i--) ldsm4(b[i], (ga[2][i & 1] ^ (((i >> 1) & 1) * 16)) + ((i >> 1) & 1) * 640);
        A[0][0] = lds32(pa + P0 * 4); A[0][1] = lds32(pa + P0 * 4 + 32); A[0][2] = lds32(sb + OFF_ZERO + 4);
#pragma unroll
        for (int m = 0; m <= 16; m++) {
          if (m < 16) {
            A[m + 1][0] = lds32(pa + P0 * 4 + (2 * m + 2) * 32);
            A[m + 1][1] = m < 15 ? lds32(pa + P0 * 4 + (2 * m + 3) * 32) : lds32(sb + OFF_ZERO + 8);
          }
          if ((m & 1) == 0 && m < 16) {
            const int i = 7 - (m >> 1);
            ldsm4(b[i], (ga[i >> 2][i & 1] ^ (((i >> 1) & 1) * 16)) + ((i >> 1) & 1) * 640);
          }
          A[m][3] = dup(A[m][0], nz);
          if (m < 16) A[m + 1][2] = dup(A[m][1], nz);
#pragma unroll
          for (int r = 7; r >= 0; r--) {
            const int f = 16 + r - m;
            hmma(acc[r], A[m][0], A[m][1], A[m][2], A[m][3], b[f >> 1][(f & 1) * 2], b[f >> 1][(f & 1) * 2 + 1]);
          }
        }
        acc[7][2] += fix;
        bar_sync(7 + wg, 64);
#pragma unroll
        for (int i = 3; i >= 0; i--)
          stsm4t((ga[2][i & 1] ^ (((i >> 1) & 1) * 16)) + ((i >> 1) & 1) * 640, pack_bf(acc[2 * i][0], acc[2 * i][1]), pack_bf(acc[2 * i][2], acc[2 * i][3]),
                 pack_bf(acc[2 * i + 1][0], acc[2 * i + 1][1]), pack_bf(acc[2 * i + 1][2], acc[2 * i + 1][3]));
      } else if (role == 2) {
        float acc[14][4];
#pragma unroll
        for (int r = 0; r < 14; r++) { acc[r][0] = acc[r][1] = acc[r][2] = acc[r][3] = 0.f; }
        const int mi = lane >> 3, hf = (lane >> 2) & 1;
        const uint32_t ze = zb + ZA1 + 128 - 512 + hf * 1792 + (mi ^ hf) * 64 + ((q ^ (mi >> 1) ^ (hf * 2)) << 4);
        const uint32_t zo = ze ^ 96;
#pragma unroll
        for (int arr = 0; arr < 2; arr++) {
          uint32_t A[5][4];
#pragma unroll
          for (int m = 0; m < 5; m++) {
            A[m][0] = lds32(pa + (arr ? PB1 : PA1) * 4 + m * 64);
            A[m][1] = m < 4 ? lds32(pa + (arr ? PB1 : PA1) * 4 + m * 64 + 32) : lds32(sb + OFF_ZERO + 4 + arr * 8);
          }
#pragma unroll
          for (int m = 4; m >= 1; m--) { A[m][2] = dup(A[m - 1][1], nz); A[m][3] = dup(A[m][0], nz); }
          A[0][2] = lds32(sb + OFF_ZERO + 8 + arr * 8); A[0][3] = dup(A[0][0], nz);
#pragma unroll
          for (int ip = 0; ip < 9; ip++) {
            uint32_t b[4];
            uint32_t ad = ((ip & 1) ? zo : ze) + ip * 256 + arr * (ZB1 - ZA1);
            if (ip < 2 && hf == 0 && (ip == 0 || mi != 3)) ad = sb + OFF_ZERO + (ad & 127);
            ldsm4(b, ad);
#pragma unroll
            for (int hh = 0; hh < 2; hh++)
#pragma unroll
              for (int m = 0; m < 5; m++) {
                const int i = 2 * ip + hh - 4 + m;
                if (i >= 0 && i < 14) hmma(acc[i], A[m][0], A[m][1], A[m][2], A[m][3], b[2 * hh], b[2 * hh + 1]);
              }
          }
        }
        const uint32_t a = zb + ZA1 + ((lane ^ (mi & 1)) << 4);
#pragma unroll
        for (int i = 0; i < 7; i++)
          stsm4(a + i * 512, pack_bf(acc[2 * i][0], acc[2 * i][1]), pack_bf(acc[2 * i][2], acc[2 * i][3]),
                pack_bf(acc[2 * i + 1][0], acc[2 * i + 1][1]), pack_bf(acc[2 * i + 1][2], acc[2 * i + 1][3]));
      } else {
        float acc[12][4];
        const uint32_t za = zb + lane * 16;
        {
          float d[4][2][4];
#pragma unroll
          for (int r = 0; r < 8; r++) { d[r >> 1][r & 1][0] = d[r >> 1][r & 1][1] = d[r >> 1][r & 1][2] = d[r >> 1][r & 1][3] = 0.f; }
#pragma unroll
          for (int arr = 0; arr < 2; arr++) {
            uint32_t A[4][4];
#pragma unroll
            for (int m = 0; m < 4; m++) { A[m][0] = lds32(pa + (arr ? PB3 : PA3) * 4 + m * 64); A[m][1] = lds32(pa + (arr ? PB3 : PA3) * 4 + m * 64 + 32); }
#pragma unroll
            for (int m = 0; m < 4; m++) { A[m][2] = m ? dup(A[m - 1][1], nz) : lds32(sb + OFF_ZERO + 4 + arr * 4); A[m][3] = dup(A[m][0], nz); }
#pragma unroll
            for (int io = 0; io < 4; io++) {
              uint32_t b[4];
              ldsm4t(b, za + (arr ? ZB3 : ZA3) + io * 512);
#pragma unroll
              for (int m = 0; m + io < 4; m++) {
                hmma(d[io + m][0], A[m][0], A[m][1], A[m][2], A[m][3], b[0], b[1]);
                hmma(d[io + m][1], A[m][0], A[m][1], A[m][2], A[m][3], b[2], b[3]);
              }
            }
          }
#pragma unroll
          for (int r = 0; r < 4; r++) {
            acc[r][0] = acc[r][1] = acc[r][2] = acc[r][3] = 0.f;
            acc[4 + 2 * r][0] = d[r][0][0]; acc[4 + 2 * r][1] = d[r][0][1]; acc[4 + 2 * r][2] = d[r][1][0]; acc[4 + 2 * r][3] = d[r][1][1];
            acc[5 + 2 * r][0] = d[r][0][2]; acc[5 + 2 * r][1] = d[r][0][3]; acc[5 + 2 * r][2] = d[r][1][2]; acc[5 + 2 * r][3] = d[r][1][3];
          }
        }
        {
          const uint32_t k0 = (g >> 1) == q ? (chc.y & ((g & 1) ? 0xffff0000u : 0xffffu)) : 0u;
          const uint32_t k1 = lds32(sb + OFF_ZERO + 12), k2 = lds32(sb + OFF_ZERO + 16), k3 = dup(k0, nz);
#pragma unroll
          for (int ip = 0; ip < 4; ip++) {
            uint32_t b[4];
            ldsm4t(b, za + ZS + ip * 512);
            hmma(acc[4 + 2 * ip], k0, k1, k2, k3, b[0], b[1]);
            hmma(acc[5 + 2 * ip], k0, k1, k2, k3, b[2], b[3]);
          }
        }
        const uint32_t pa2 = pb + (2 * g - 4 * q) * 4;
#pragma unroll
        for (int arr = 0; arr < 2; arr++) {
          uint32_t A[5][4];
#pragma unroll
          for (int m = 0; m < 5; m++) {
            const uint2 v = lds64(pa2 + (arr ? PB2 : PA2) * 4 + m * 64);
            A[m][0] = v.x; A[m][1] = v.y; A[m][2] = lds32(pa2 + (arr ? PB2 : PA2) * 4 + m * 64 - 4);
          }
#pragma unroll
          for (int m = 0; m < 5; m++) A[m][3] = dup(A[m][0], nz);
#pragma unroll
          for (int ip = 0; ip < 6; ip++) {
            uint32_t b[4];
            ldsm4t(b, za + (arr ? ZB2 : ZA2) + ip * 512);
#pragma unroll
            for (int hh = 0; hh < 2; hh++)
#pragma unroll
              for (int m = 0; m < 5; m++) {
                const int i = 2 * ip + hh + m;
                if (i < 12) hmma(acc[i], A[m][0], A[m][1], A[m][2], A[m][3], b[2 * hh], b[2 * hh + 1]);
              }
          }
        }
        const uint32_t a = zb + ZA2 + ((lane ^ ((lane >> 1) & 4)) << 4);
#pragma unroll
        for (int i = 0; i < 6; i++)
          stsm4(a + i * 512, pack_bf(acc[2 * i][0], acc[2 * i][1]), pack_bf(acc[2 * i][2], acc[2 * i][3]),
                pack_bf(acc[2 * i + 1][0], acc[2 * i + 1][1]), pack_bf(acc[2 * i + 1][2], acc[2 * i + 1][3]));
      }
      if (ch == 4) bar_arrive(8, 384);
      bar_sync(3 + wg, 128);
      {
        const int row = (wid & 15) * 5 + ch;
        const int c = tid & 127, c1 = c < 112 ? c + 32 : c - 112, c2 = c < 112 ? c + 144 : c - 96;
        const uint32_t zr = sb + OFF_ZERO + (lane & 7) * 16;
        const uint32_t a1 = c < 112 ? zb + ZA1 + ((2 * c) ^ ((c >> 2) & 1)) * 16 : zr;
        const uint32_t a2 = zb + ZA2 + ((c & ~15) - 32 + ((((c >> 1) & 7) + (c & 1) * 8) ^ ((c & 1) * 4))) * 16;
        const uint4 v0 = lds128(ub + uoff(upos(c1))), u0 = lds128(ub + uoff(upos(c2)));
        const uint4 y0 = lds128(a1), y1 = lds128(a1 ^ 16);
        const uint4 v2 = lds128(c1 >= 64 ? a2 : zr), u2 = lds128(c < 112 ? a2 + 112 * 16 : zr);
        uint4* dst = p.scr->sT + ((wid >> 4) * 16 * 80 + row) * 16 + ((c & 15) ^ (row & 7));
        const uint4 v = make_uint4(bmul(badd(badd(y0.x, v2.x), v0.x), chc.x), bmul(badd(badd(y0.y, v2.y), v0.y), chc.x),
                                   bmul(badd(badd(y1.x, v2.z), v0.z), chc.x), bmul(badd(badd(y1.y, v2.w), v0.w), chc.x));
        const uint4 u = make_uint4(bmul(badd(badd(y0.z, u2.x), u0.x), chc.x), bmul(badd(badd(y0.w, u2.y), u0.y), chc.x),
                                   bmul(badd(badd(y1.z, u2.z), u0.z), chc.x), bmul(badd(badd(y1.w, u2.w), u0.w), chc.x));
        fence_async_smem();
        dst[(c1 >> 4) * 1280] = v;
        dst[(c2 >> 4) * 1280] = u;
      }
      __syncwarp();
      if (lane == 0) mbar_arrive(bar + 8 * (B_FREE + ch));
    }
    if (warp == 12) {
      if (elect1()) {
        const uint4* srcA = p.scr->h + (rg1 * 24 + NS2 - 1) * 1024;
        const uint4* srcB = p.scr->w2p + (j1 * 24 + NS2 - 1) * 640;
        uint32_t d = sb + (NS2 - 1) * SLOT2;
        mbar_wait(bar + 8 * (B_FULL2 + 3), 0);
        asm volatile("fence.proxy.async.global;" ::: "memory");
        mbar_wait(bar + 8 * (B_FREE + 4), 0);
#pragma unroll 1
        for (int s = NS2 - 1; s < 24; s++) {
          mbar_wait(bar + 8 * (B_REL2 + s - NS2 + 1), 0);
          const uint32_t mb = bar + 8 * (B_FULL2 + s);
          mbar_expect(mb, SLOT2);
          bulk_g2s(d, srcA, 16384, mb);
          bulk_g2s(d + 16384, srcB, 10240, mb);
          srcA += 1024; srcB += 640;
          d = d == sb + (NS2 - 1) * SLOT2 ? sb : d + SLOT2;
        }
      }
      __syncwarp();
    } else if (warp == 13) {
      if (elect1()) {
        mbar_wait(bar + 8 * (B_FREE + 3), 0);
        mbar_wait(bar + 8 * (B_FREE + 4), 0);
        publish(cnt + (C_S + (wid >> 4)) * 32);
        mbar_expect(bar + 8 * B_SFULL, 20480);
        poll_cnt(cnt + (C_S + j1) * 32, ep * 16);
        mbar_wait(bar + 8 * (B_REL2 + 24 - NS2), 0);
        bulk_g2s(sb + OFF_U, p.scr->sT + (j1 * 16 + rg1) * 1280, 20480, bar + 8 * B_SFULL);
      }
      __syncwarp();
    }
  }
}

typedef CUresult (*EncodeFn)(CUtensorMap*, CUtensorMapDataType, cuuint32_t, void*, const cuuint64_t*, const cuuint64_t*,
                             const cuuint32_t*, const cuuint32_t*, CUtensorMapInterleave, CUtensorMapSwizzle,
                             CUtensorMapL2promotion, CUtensorMapFloatOOBfill);

}

extern "C" void kernel_launch(void* const* d_in, const int* in_sizes, int n_in, void* d_out, int out_size) {
  static EncodeFn enc = nullptr;
  static int nsm = 0;
  static void* scr = nullptr;
  if (!enc) {
    void* fn = nullptr;
    cudaDriverEntryPointQueryResult qr;
    cudaGetDriverEntryPoint("cuTensorMapEncodeTiled", &fn, cudaEnableDefault, &qr);
    enc = (EncodeFn)fn;
    int dev = 0;
    cudaGetDevice(&dev);
    cudaDeviceGetAttribute(&nsm, cudaDevAttrMultiProcessorCount, dev);
    cudaFuncSetAttribute(fused_s4_ffn_kernel<true>, cudaFuncAttributeMaxDynamicSharedMemorySize, SMEM_BYTES);
    cudaFuncSetAttribute(fused_s4_ffn_kernel<false>, cudaFuncAttributeMaxDynamicSharedMemorySize, SMEM_BYTES);
    cudaGetSymbolAddress(&scr, g_scr);
  }
  Params p;
  p.x = (const __nv_bfloat16*)d_in[0];
  p.are = (const __nv_bfloat16*)d_in[1]; p.aim = (const __nv_bfloat16*)d_in[2];
  p.bre = (const __nv_bfloat16*)d_in[3]; p.bim = (const __nv_bfloat16*)d_in[4];
  p.cre = (const __nv_bfloat16*)d_in[5]; p.cim = (const __nv_bfloat16*)d_in[6];
  p.logdt = (const __nv_bfloat16*)d_in[7]; p.dskip = (const __nv_bfloat16*)d_in[8];
  p.w1 = (const __nv_bfloat16*)d_in[10]; p.w2 = (const __nv_bfloat16*)d_in[11];
  p.out = (__nv_bfloat16*)d_out;
  p.scr = (Scratch*)scr;
  CUtensorMap tmX, tmW1, tmU, tmW2;
  const cuuint32_t es[5] = {1, 1, 1, 1, 1};
  {
    const cuuint64_t gd[5] = {DM, 2, 4, 4, FF / 32}, gs[4] = {DM * 2, DM * 16, DM * 4, DM * 64};
    const cuuint32_t bx[5] = {88, 2, 4, 4, 3};
    enc(&tmW2, CU_TENSOR_MAP_DATA_TYPE_BFLOAT16, 5, d_in[11], gd, gs, bx, es, CU_TENSOR_MAP_INTERLEAVE_NONE,
        CU_TENSOR_MAP_SWIZZLE_NONE, CU_TENSOR_MAP_L2_PROMOTION_NONE, CU_TENSOR_MAP_FLOAT_OOB_FILL_NONE);
  }
  {
    const cuuint64_t gd[2] = {16 * DM, 128}, gs[1] = {DM * 32};
    const cuuint32_t bx[2] = {80, 128};
    enc(&tmU, CU_TENSOR_MAP_DATA_TYPE_FLOAT16, 2, p.scr->uT, gd, gs, bx, es, CU_TENSOR_MAP_INTERLEAVE_NONE,
        CU_TENSOR_MAP_SWIZZLE_NONE, CU_TENSOR_MAP_L2_PROMOTION_NONE, CU_TENSOR_MAP_FLOAT_OOB_FILL_NONE);
  }
  {
    const cuuint64_t gd[2] = {DM, SEQ}, gs[1] = {DM * 2};
    const cuuint32_t bx[2] = {64, 128};
    enc(&tmX, CU_TENSOR_MAP_DATA_TYPE_BFLOAT16, 2, d_in[0], gd, gs, bx, es, CU_TENSOR_MAP_INTERLEAVE_NONE,
        CU_TENSOR_MAP_SWIZZLE_128B, CU_TENSOR_MAP_L2_PROMOTION_L2_128B, CU_TENSOR_MAP_FLOAT_OOB_FILL_NONE);
  }
  {
    const cuuint64_t gd[3] = {64, DM, FF / 64}, gs[2] = {FF * 2, 128};
    const cuuint32_t bx[3] = {64, 64, 3};
    enc(&tmW1, CU_TENSOR_MAP_DATA_TYPE_BFLOAT16, 3, d_in[10], gd, gs, bx, es, CU_TENSOR_MAP_INTERLEAVE_NONE,
        CU_TENSOR_MAP_SWIZZLE_128B, CU_TENSOR_MAP_L2_PROMOTION_L2_128B, CU_TENSOR_MAP_FLOAT_OOB_FILL_NONE);
  }
  if (nsm == 132) fused_s4_ffn_kernel<true><<<132, 512, SMEM_BYTES>>>(p, tmX, tmW1, tmU, tmW2);
  else fused_s4_ffn_kernel<false><<<132, 512, SMEM_BYTES>>>(p, tmX, tmW1, tmU, tmW2);
}
```

```cpp
#include <cuda_runtime.h>
#include <cuda_bf16.h>
#include <cuda_fp16.h>
#include <cuda.h>
#include <stdint.h>

namespace {

constexpr int SEQ = 2048, DM = 640, FF = 1536;

constexpr int SLOT1 = 40960;
constexpr int SLOT2 = 26624;
constexpr int NS2 = 7;
#define DELAY_NS 200
#define RING3 1
#define SLOTMAP (RING3 ? 0x492D2 : 0x4E4E4)
#define PACE_NS 30
constexpr int OFF_Z = 91904, ZSZ = 19712;
constexpr int ZA3 = 0, ZB3 = 2048, ZS = 4096, ZA2 = 6144, ZB2 = 9216, ZA1 = 12288, ZB1 = 16000;
constexpr int OFF_W2S = OFF_Z + 4 * ZSZ;
constexpr int OFF_U = 190464;
constexpr int OFF_P = 210944;
constexpr int OFF_KS = 163840;
constexpr int OFF_LNP = 225280;
constexpr int OFF_MISC = 226304;
constexpr int OFF_CHC = OFF_MISC + 16;
constexpr int OFF_EP = OFF_MISC + 64;
constexpr int OFF_ZERO = OFF_MISC + 128;
constexpr int OFF_STAT = OFF_MISC + 1024;
constexpr int OFF_CS = OFF_MISC + 2048;
constexpr int OFF_BAR = OFF_MISC + 2816;
constexpr int SMEM_BYTES = OFF_MISC + 6144;
constexpr int P0 = 8, PA1 = 280, PB1 = 360, PA2 = 448, PB2 = 544, PA3 = 632, PB3 = 704;
enum { B_FULL1 = 0, B_FULL2 = 10, B_UFULL = 34, B_EPI = 35, B_SFULL = 36, B_W2 = 37, B_MMA = 38,
       B_FREE = 40,
       B_REL1 = 45, B_REL2 = 55, B_NUM = 80 };
enum { C_LN = 0, C_CS = 1, C_H0 = 2, C_H1 = 18, C_S = 34, C_W2 = 42, C_NUM = 43 };

struct Scratch {
  unsigned cnt[64 * 32];
  unsigned epoch[256];
  float2 stats[SEQ];
  float cs[FF];
  uint4 uT[DM * 256];
  uint4 w2p[8 * 24 * 640];
  uint4 sT[8 * 16 * 1280];
  uint4 h[16 * 24 * 1024];
};
__device__ __align__(1024) Scratch g_scr;
constexpr uint32_t sb = 1024;
constexpr uint32_t bar = sb + OFF_BAR;
__device__ __forceinline__ int slot1(int s) { return (SLOTMAP >> (2 * s)) & 3; }

struct Params {
  const __nv_bfloat16 *are, *aim, *bre, *bim, *cre, *cim, *logdt, *dskip, *x, *w1, *w2;
  __nv_bfloat16* out;
  Scratch* scr;
};

__device__ __forceinline__ void mbar_init(uint32_t a, int c) { asm volatile("mbarrier.init.shared::cta.b64 [%0], %1;" ::"r"(a), "r"(c)); }
__device__ __forceinline__ void mbar_expect(uint32_t a, int b) { asm volatile("mbarrier.arrive.expect_tx.shared::cta.b64 _, [%0], %1;" ::"r"(a), "r"(b) : "memory"); }
__device__ __forceinline__ void mbar_arrive(uint32_t a) { asm volatile("mbarrier.arrive.shared::cta.b64 _, [%0];" ::"r"(a) : "memory"); }
__device__ __forceinline__ void mbar_wait(uint32_t a, int ph) {
  asm volatile(
      "{\n.reg .pred p;\n.reg .u32 n;\n"
      "mbarrier.try_wait.parity.shared::cta.b64 p, [%0], %1;\n@p bra LD;\nmov.u32 n, 0;\n"
      "LW:\nmbarrier.try_wait.parity.shared::cta.b64 p, [%0], %1, 20000;\n@p bra LD;\n"
      "add.u32 n, n, 1;\nsetp.lt.u32 p, n, 100000;\n@p bra LW;\ntrap;\nLD:\n}\n" ::"r"(a), "r"(ph) : "memory");
}
__device__ __forceinline__ void poll_cnt(const unsigned* p, unsigned target) {
  asm volatile(
      "{\n.reg .pred p;\n.reg .u32 n;\n.reg .s32 v;\nmov.u32 n, 0;\n"
      "LW:\nld.relaxed.gpu.global.u32 v, [%0];\nsub.s32 v, v, %1;\nsetp.ge.s32 p, v, 0;\n@p bra LD;\n"
      "nanosleep.u32 64;\nadd.u32 n, n, 1;\nsetp.lt.u32 p, n, 4000000;\n@p bra LW;\ntrap;\n"
      "LD:\nfence.acquire.gpu;\nfence.proxy.async.global;\n}\n" ::"l"(p), "r"(target) : "memory");
}
__device__ __forceinline__ void publish(unsigned* p) {
  asm volatile("fence.proxy.async.global;\nfence.release.gpu;\nred.relaxed.gpu.global.add.u32 [%0], 1;" ::"l"(p) : "memory");
}
__device__ __forceinline__ uint32_t movm(uint32_t v) { uint32_t r; asm volatile("movmatrix.sync.aligned.m8n8.trans.b16 %0, %1;" : "=r"(r) : "r"(v)); return r; }
__device__ __forceinline__ void fence_async_smem() { asm volatile("fence.proxy.async.shared::cta;" ::: "memory"); }
__device__ __forceinline__ bool elect1() { uint32_t p; asm volatile("{\n.reg .pred P;\nelect.sync _|P, 0xffffffff;\nselp.u32 %0,1,0,P;\n}\n" : "=r"(p)); return p; }
__device__ __forceinline__ void bar_sync(int id, int n) { asm volatile("bar.sync %0, %1;" ::"r"(id), "r"(n) : "memory"); }
__device__ __forceinline__ void bar_arrive(int id, int n) { asm volatile("bar.arrive %0, %1;" ::"r"(id), "r"(n) : "memory"); }
__device__ __forceinline__ void bulk_g2s(uint32_t dst, const void* src, int bytes, uint32_t mb) {
  asm volatile("cp.async.bulk.shared::cluster.global.mbarrier::complete_tx::bytes [%0], [%1], %2, [%3];" ::"r"(dst), "l"(src), "r"(bytes), "r"(mb) : "memory");
}
__device__ __forceinline__ void bulk_prefetch(const void* src, int bytes) { asm volatile("cp.async.bulk.prefetch.L2.global [%0], %1;" ::"l"(src), "r"(bytes) : "memory"); }
__device__ __forceinline__ void tma2d(uint32_t dst, const CUtensorMap* m, int c0, int c1, uint32_t mb) {
  asm volatile("cp.async.bulk.tensor.2d.shared::cluster.global.mbarrier::complete_tx::bytes [%0], [%1, {%3, %4}], [%2];" ::"r"(dst), "l"(m), "r"(mb), "r"(c0), "r"(c1) : "memory");
}
__device__ __forceinline__ void tma3d(uint32_t dst, const CUtensorMap* m, int c0, int c1, int c2, uint32_t mb) {
  asm volatile("cp.async.bulk.tensor.3d.shared::cluster.global.mbarrier::complete_tx::bytes [%0], [%1, {%3, %4, %5}], [%2];" ::"r"(dst), "l"(m), "r"(mb), "r"(c0), "r"(c1), "r"(c2) : "memory");
}
__device__ __forceinline__ int frag_col(int l) {
  const int tl = l >> 3, i = l & 7;
  return (tl < 8 ? 32 * (tl >> 2) + 8 * (i >> 1) + 2 * (tl & 3) : 48 + 4 * (i >> 1) + 2 * tl) + (i & 1);
}
__device__ __forceinline__ void tma5d(uint32_t dst, const CUtensorMap* m, int c0, int c4, uint32_t mb) {
  asm volatile("cp.async.bulk.tensor.5d.shared::cluster.global.mbarrier::complete_tx::bytes [%0], [%1, {%3, %5, %5, %5, %4}], [%2];" ::"r"(dst), "l"(m), "r"(mb), "r"(c0), "r"(c4), "r"(0) : "memory");
}
__device__ __forceinline__ uint64_t dsc(uint32_t lo, uint32_t hi) { return ((uint64_t)hi << 32) | lo; }
__device__ __forceinline__ void wg_fence() { asm volatile("wgmma.fence.sync.aligned;" ::: "memory"); }
__device__ __forceinline__ void wg_commit() { asm volatile("wgmma.commit_group.sync.aligned;" ::: "memory"); }
template <int N> __device__ __forceinline__ void wg_wait() { asm volatile("wgmma.wait_group.sync.aligned %0;" ::"n"(N) : "memory"); }
__device__ __forceinline__ void wgmma_n192(float (&d)[96], uint64_t da, uint64_t db, int scale_d) {
  asm volatile("{\n.reg .pred p;\nsetp.ne.b32 p, %98, 0;\n"
    "wgmma.mma_async.sync.aligned.m64n192k16.f32.bf16.bf16 "
    "{"
    "%0, %1, %2, %3, %4, %5, %6, %7, %8, %9, %10, %11, %12, %13, %14, %15, "
    "%16, %17, %18, %19, %20, %21, %22, %23, %24, %25, %26, %27, %28, %29, %30, %31, "
    "%32, %33, %34, %35, %36, %37, %38, %39, %40, %41, %42, %43, %44, %45, %46, %47, "
    "%48, %49, %50, %51, %52, %53, %54, %55, %56, %57, %58, %59, %60, %61, %62, %63, "
    "%64, %65, %66, %67, %68, %69, %70, %71, %72, %73, %74, %75, %76, %77, %78, %79, "
    "%80, %81, %82, %83, %84, %85, %86, %87, %88, %89, %90, %91, %92, %93, %94, %95"
    "}, "
    "%96, %97, p, 1, 1, 0, 1;\n}\n"
    : "+f"(d[0]), "+f"(d[1]), "+f"(d[2]), "+f"(d[3]), "+f"(d[4]), "+f"(d[5]), "+f"(d[6]), "+f"(d[7]),
      "+f"(d[8]), "+f"(d[9]), "+f"(d[10]), "+f"(d[11]), "+f"(d[12]), "+f"(d[13]), "+f"(d[14]), "+f"(d[15]),
      "+f"(d[16]), "+f"(d[17]), "+f"(d[18]), "+f"(d[19]), "+f"(d[20]), "+f"(d[21]), "+f"(d[22]), "+f"(d[23]),
      "+f"(d[24]), "+f"(d[25]), "+f"(d[26]), "+f"(d[27]), "+f"(d[28]), "+f"(d[29]), "+f"(d[30]), "+f"(d[31]),
      "+f"(d[32]), "+f"(d[33]), "+f"(d[34]), "+f"(d[35]), "+f"(d[36]), "+f"(d[37]), "+f"(d[38]), "+f"(d[39]),
      "+f"(d[40]), "+f"(d[41]), "+f"(d[42]), "+f"(d[43]), "+f"(d[44]), "+f"(d[45]), "+f"(d[46]), "+f"(d[47]),
      "+f"(d[48]), "+f"(d[49]), "+f"(d[50]), "+f"(d[51]), "+f"(d[52]), "+f"(d[53]), "+f"(d[54]), "+f"(d[55]),
      "+f"(d[56]), "+f"(d[57]), "+f"(d[58]), "+f"(d[59]), "+f"(d[60]), "+f"(d[61]), "+f"(d[62]), "+f"(d[63]),
      "+f"(d[64]), "+f"(d[65]), "+f"(d[66]), "+f"(d[67]), "+f"(d[68]), "+f"(d[69]), "+f"(d[70]), "+f"(d[71]),
      "+f"(d[72]), "+f"(d[73]), "+f"(d[74]), "+f"(d[75]), "+f"(d[76]), "+f"(d[77]), "+f"(d[78]), "+f"(d[79]),
      "+f"(d[80]), "+f"(d[81]), "+f"(d[82]), "+f"(d[83]), "+f"(d[84]), "+f"(d[85]), "+f"(d[86]), "+f"(d[87]),
      "+f"(d[88]), "+f"(d[89]), "+f"(d[90]), "+f"(d[91]), "+f"(d[92]), "+f"(d[93]), "+f"(d[94]), "+f"(d[95])
    : "l"(da), "l"(db), "r"(scale_d));
}

__device__ __forceinline__ void wgmma_n80(float (&d)[40], uint64_t da, uint64_t db, int scale_d) {
  asm volatile("{\n.reg .pred p;\nsetp.ne.b32 p, %42, 0;\n"
    "wgmma.mma_async.sync.aligned.m64n80k16.f32.bf16.bf16 "
    "{"
    "%0, %1, %2, %3, %4, %5, %6, %7, %8, %9, %10, %11, %12, %13, %14, %15, "
    "%16, %17, %18, %19, %20, %21, %22, %23, %24, %25, %26, %27, %28, %29, %30, %31, "
    "%32, %33, %34, %35, %36, %37, %38, %39"
    "}, "
    "%40, %41, p, 1, 1, 0, 1;\n}\n"
    : "+f"(d[0]), "+f"(d[1]), "+f"(d[2]), "+f"(d[3]), "+f"(d[4]), "+f"(d[5]), "+f"(d[6]), "+f"(d[7]),
      "+f"(d[8]), "+f"(d[9]), "+f"(d[10]), "+f"(d[11]), "+f"(d[12]), "+f"(d[13]), "+f"(d[14]), "+f"(d[15]),
      "+f"(d[16]), "+f"(d[17]), "+f"(d[18]), "+f"(d[19]), "+f"(d[20]), "+f"(d[21]), "+f"(d[22]), "+f"(d[23]),
      "+f"(d[24]), "+f"(d[25]), "+f"(d[26]), "+f"(d[27]), "+f"(d[28]), "+f"(d[29]), "+f"(d[30]), "+f"(d[31]),
      "+f"(d[32]), "+f"(d[33]), "+f"(d[34]), "+f"(d[35]), "+f"(d[36]), "+f"(d[37]), "+f"(d[38]), "+f"(d[39])
    : "l"(da), "l"(db), "r"(scale_d));
}

__device__ __forceinline__ void hmma(float* c, uint32_t a0, uint32_t a1, uint32_t a2, uint32_t a3, uint32_t b0, uint32_t b1) {
  asm volatile("mma.sync.aligned.m16n8k16.row.col.f32.f16.f16.f32 {%0,%1,%2,%3}, {%4,%5,%6,%7}, {%8,%9}, {%0,%1,%2,%3};"
      : "+f"(c[0]), "+f"(c[1]), "+f"(c[2]), "+f"(c[3]) : "r"(a0), "r"(a1), "r"(a2), "r"(a3), "r"(b0), "r"(b1));
}
__device__ __forceinline__ void ldsm4(uint32_t* r, uint32_t a) { asm volatile("ldmatrix.sync.aligned.m8n8.x4.shared.b16 {%0,%1,%2,%3}, [%4];" : "=r"(r[0]), "=r"(r[1]), "=r"(r[2]), "=r"(r[3]) : "r"(a) : "memory"); }
__device__ __forceinline__ void ldsm4t(uint32_t* r, uint32_t a) { asm volatile("ldmatrix.sync.aligned.m8n8.x4.trans.shared.b16 {%0,%1,%2,%3}, [%4];" : "=r"(r[0]), "=r"(r[1]), "=r"(r[2]), "=r"(r[3]) : "r"(a) : "memory"); }
__device__ __forceinline__ void stsm4(uint32_t a, uint32_t r0, uint32_t r1, uint32_t r2, uint32_t r3) { asm volatile("stmatrix.sync.aligned.m8n8.x4.shared.b16 [%0], {%1,%2,%3,%4};" ::"r"(a), "r"(r0), "r"(r1), "r"(r2), "r"(r3) : "memory"); }
__device__ __forceinline__ void stsm4t(uint32_t a, uint32_t r0, uint32_t r1, uint32_t r2, uint32_t r3) { asm volatile("stmatrix.sync.aligned.m8n8.x4.trans.shared.b16 [%0], {%1,%2,%3,%4};" ::"r"(a), "r"(r0), "r"(r1), "r"(r2), "r"(r3) : "memory"); }
__device__ __forceinline__ uint32_t lds32(uint32_t a) { uint32_t v; asm volatile("ld.shared.u32 %0, [%1];" : "=r"(v) : "r"(a) : "memory"); return v; }
__device__ __forceinline__ uint2 lds64(uint32_t a) { uint2 v; asm volatile("ld.shared.v2.u32 {%0,%1}, [%2];" : "=r"(v.x), "=r"(v.y) : "r"(a) : "memory"); return v; }
__device__ __forceinline__ uint4 lds128(uint32_t a) { uint4 v; asm volatile("ld.shared.v4.u32 {%0,%1,%2,%3}, [%4];" : "=r"(v.x), "=r"(v.y), "=r"(v.z), "=r"(v.w) : "r"(a) : "memory"); return v; }
__device__ __forceinline__ void sts16(uint32_t a, uint32_t v) { asm volatile("st.shared.u16 [%0], %1;" ::"r"(a), "h"((unsigned short)v) : "memory"); }
__device__ __forceinline__ void sts32(uint32_t a, uint32_t v) { asm volatile("st.shared.u32 [%0], %1;" ::"r"(a), "r"(v) : "memory"); }
__device__ __forceinline__ void sts64(uint32_t a, uint32_t x, uint32_t y) { asm volatile("st.shared.v2.u32 [%0], {%1,%2};" ::"r"(a), "r"(x), "r"(y) : "memory"); }
__device__ __forceinline__ void sts128(uint32_t a, uint32_t x, uint32_t y, uint32_t z, uint32_t w) { asm volatile("st.shared.v4.u32 [%0], {%1,%2,%3,%4};" ::"r"(a), "r"(x), "r"(y), "r"(z), "r"(w) : "memory"); }
__device__ __forceinline__ float bflo(uint32_t v) { return __uint_as_float(v << 16); }
__device__ __forceinline__ float bfhi(uint32_t v) { return __uint_as_float(v & 0xffff0000u); }
__device__ __forceinline__ uint32_t pack_bf(float lo, float hi) { uint32_t r; asm("cvt.rn.bf16x2.f32 %0, %1, %2;" : "=r"(r) : "f"(hi), "f"(lo)); return r; }
__device__ __forceinline__ uint32_t pack_h(float lo, float hi) { uint32_t r; asm("cvt.rn.f16x2.f32 %0, %1, %2;" : "=r"(r) : "f"(hi), "f"(lo)); return r; }
__device__ __forceinline__ float rnd_bf(float v) { return __bfloat162float(__float2bfloat16_rn(v)); }
__device__ __forceinline__ float ex2a(float v) { float r; asm("ex2.approx.ftz.f32 %0, %1;" : "=f"(r) : "f"(v)); return r; }
__device__ __forceinline__ float tanha(float v) { float r; asm("tanh.approx.f32 %0, %1;" : "=f"(r) : "f"(v)); return r; }
__device__ __forceinline__ uint32_t hadd(uint32_t a, uint32_t b) { uint32_t r; asm("add.rn.f16x2 %0, %1, %2;" : "=r"(r) : "r"(a), "r"(b)); return r; }
__device__ __forceinline__ uint32_t badd(uint32_t a, uint32_t b) { uint32_t r; asm("add.rn.bf16x2 %0, %1, %2;" : "=r"(r) : "r"(a), "r"(b)); return r; }
__device__ __forceinline__ uint32_t bmul(uint32_t a, uint32_t b) { uint32_t r; asm("mul.rn.bf16x2 %0, %1, %2;" : "=r"(r) : "r"(a), "r"(b)); return r; }
__device__ __forceinline__ uint32_t bsub(uint32_t a, uint32_t b) { uint32_t r; asm("sub.rn.bf16x2 %0, %1, %2;" : "=r"(r) : "r"(a), "r"(b)); return r; }
__device__ __forceinline__ uint32_t dup(uint32_t v, uint32_t nz) { uint32_t r; asm volatile("add.rn.f32 %0, %1, %2;" : "=r"(r) : "r"(v), "r"(nz)); return r; }
__device__ __forceinline__ void bmma(float* c, uint32_t a0, uint32_t a1, uint32_t a2, uint32_t a3, uint32_t b0, uint32_t b1) {
  asm("mma.sync.aligned.m16n8k16.row.col.f32.bf16.bf16.f32 {%0,%1,%2,%3}, {%4,%5,%6,%7}, {%8,%9}, {%0,%1,%2,%3};"
      : "+f"(c[0]), "+f"(c[1]), "+f"(c[2]), "+f"(c[3]) : "r"(a0), "r"(a1), "r"(a2), "r"(a3), "r"(b0), "r"(b1));
}
__device__ __forceinline__ uint32_t odd_pair(uint32_t a, uint32_t b) { return __byte_perm(a, b, 0x5432); }
__device__ __forceinline__ int upos(int c) { return c ^ (c >> 5) ^ ((c >> 3) & 1); }
__device__ __forceinline__ int uoff(int pos) { return (pos >> 1) * 160 + (pos & 1) * 16; }

struct cf { float r, i; };
__device__ __forceinline__ cf cmul(cf a, cf b) { cf o; o.r = fmaf(a.r, b.r, -a.i * b.i); o.i = fmaf(a.r, b.i, a.i * b.r); return o; }
__device__ __forceinline__ cf csq(cf a) { cf o; o.r = fmaf(a.r, a.r, -a.i * a.i); o.i = (a.r + a.r) * a.i; return o; }
struct hp { uint32_t r, i; };
__device__ __forceinline__ hp hpack(cf a, cf b) { hp o; o.r = pack_h(a.r, b.r); o.i = pack_h(a.i, b.i); return o; }
__device__ __forceinline__ hp hmulc(hp a, uint32_t c) {
  __half2 ar = *reinterpret_cast<__half2*>(&a.r), ai = *reinterpret_cast<__half2*>(&a.i), cc = *reinterpret_cast<__half2*>(&c);
  __half2 orr = __hfma2(ar, __low2half2(cc), __hneg2(__hmul2(ai, __high2half2(cc))));
  __half2 oi = __hfma2(ar, __high2half2(cc), __hmul2(ai, __low2half2(cc)));
  hp o; o.r = *reinterpret_cast<uint32_t*>(&orr); o.i = *reinterpret_cast<uint32_t*>(&oi); return o;
}
__device__ __forceinline__ void sts_tile(uint32_t a, const hp* t) {
  sts128(a, t[0].r, t[1].r, t[2].r, t[3].r);
  sts128(a + 512, t[0].i, t[1].i, t[2].i, t[3].i);
}
template <int STEP> __device__ __forceinline__ void put2(uint32_t a0, uint32_t a1, uint32_t h, uint32_t sel) {
  const uint32_t x = __byte_perm(h, h, sel), y = x >> 16;
  sts16(a0, x); sts16(a0 + STEP * 4 + 2, x);
  sts16(a1, y); sts16(a1 + STEP * 4 + 2, y);
}

__device__ __forceinline__ void spare_work(const Params& p, const CUtensorMap* tmW1, int k, int tid) {
  const int lane = tid & 31;
  unsigned ep = 0;
  if (tid >= 480) ep = p.scr->epoch[128 + k] + 1;
  if (tid == 480) {
    for (int i = 0; i < 8; i++) mbar_init(bar + 8 * i, i < 4 ? 1 : 12);
    asm volatile("fence.mbarrier_init.release.cluster;" ::: "memory");
    fence_async_smem();
  }
  __syncthreads();
  float a[2][4] = {{0.f, 0.f, 0.f, 0.f}, {0.f, 0.f, 0.f, 0.f}};
  if (tid >= 480) {
    if (elect1()) {
#pragma unroll 1
      for (int s = 0; s < 10; s++) {
        mbar_wait(bar + 8 * (4 + (s & 3)), ((s >> 2) & 1) ^ 1);
        mbar_expect(bar + 8 * (s & 3), 49152);
#pragma unroll 1
        for (int b = 0; b < 2; b++) tma3d(sb + (s & 3) * 49152 + b * 24576, tmW1, 0, s * 64, k * 6 + b * 3, bar + 8 * (s & 3));
      }
    }
    __syncwarp();
  } else if (tid < 384) {
    const uint32_t idn = (lane >> 3) == (lane & 3) ? ((lane & 4) ? 0x3f800000u : 0x3f80u) : 0u;
#pragma unroll 1
    for (int s = 0; s < 10; s++) {
      mbar_wait(bar + 8 * (s & 3), (s >> 2) & 1);
      const uint32_t ad = sb + (s & 3) * 49152 + (tid >> 6) * 8192 + (tid & 63) * 16;
#pragma unroll
      for (int i = 0; i < 8; i += 2) {
        const uint4 v = lds128(ad + i * 1024), w = lds128(ad + i * 1024 + 1024);
        bmma(a[0], v.x, v.y, w.x, w.y, idn, idn);
        bmma(a[1], v.z, v.w, w.z, w.w, idn, idn);
      }
      __syncwarp();
      if (lane == 0) mbar_arrive(bar + 8 * (4 + (s & 3)));
    }
    const int rho = (tid >> 3) & 7;
    const uint32_t ad = sb + 196608 + rho * 1536 + ((tid >> 6) * 8 + ((tid & 7) ^ rho)) * 32;
    sts128(ad, __float_as_uint(a[0][0]), __float_as_uint(a[0][1]), __float_as_uint(a[0][2]), __float_as_uint(a[0][3]));
    sts128(ad + 16, __float_as_uint(a[1][0]), __float_as_uint(a[1][1]), __float_as_uint(a[1][2]), __float_as_uint(a[1][3]));
  }
  __syncthreads();
  if (tid < 384) {
    float s = 0.f;
#pragma unroll
    for (int r = 0; r < 8; r++) s += __uint_as_float(lds32(sb + 196608 + r * 1536 + tid * 4));
    p.scr->cs[k * 384 + tid] = s;
  }
  __syncthreads();
  if (tid == 480) {
    publish(p.scr->cnt + C_CS * 32);
    p.scr->epoch[128 + k] = ep;
    poll_cnt(p.scr->cnt + C_LN * 32, ep * 128);
  }
}

__device__ __forceinline__ void load1(int s, const CUtensorMap* tmX, const CUtensorMap* tmW1, int rg1, int j1) {
  const uint32_t d = sb + slot1(s) * SLOT1, mb = bar + 8 * (B_FULL1 + s);
  mbar_expect(mb, SLOT1);
  tma2d(d, tmX, s * 64, rg1 * 128, mb);
  tma3d(d + 16384, tmW1, 0, s * 64, j1 * 3, mb);
}
__device__ __forceinline__ void load_x(uint32_t (&xv)[2][10], const __nv_bfloat16* xc, int rstep, int q) {
#pragma unroll
  for (int r = 0; r < 2; r++) {
    const uint4 a = __ldg((const uint4*)(xc + r * rstep) + q), b = __ldg((const uint4*)(xc + r * rstep) + 4 + q);
    const uint2 c = __ldg((const uint2*)(xc + r * rstep + 64) + q);
    xv[r][0] = a.x; xv[r][1] = a.y; xv[r][2] = a.z; xv[r][3] = a.w; xv[r][4] = b.x; xv[r][5] = b.y; xv[r][6] = b.z; xv[r][7] = b.w;
    xv[r][8] = c.x; xv[r][9] = c.y;
  }
}

template <bool USE_SMID>
__global__ void __launch_bounds__(512, 1)
fused_s4_ffn_kernel(const Params p, const __grid_constant__ CUtensorMap tmX, const __grid_constant__ CUtensorMap tmW1,
                    const __grid_constant__ CUtensorMap tmU, const __grid_constant__ CUtensorMap tmW2) {
  extern __shared__ __align__(1024) unsigned char smem_raw[];
  const int tid = threadIdx.x, lane = tid & 31;
  const int warp = __shfl_sync(0xffffffffu, tid >> 5, 0);
  const int g = lane >> 2, q = lane & 3;
  uint32_t sid;
  if (USE_SMID) asm("mov.u32 %0, %smid;" : "=r"(sid)); else sid = blockIdx.x;
  if (sid - 120u < 4u) { spare_work(p, &tmW1, sid - 120, tid); return; }
  const int wid = sid < 120 ? sid : sid - 4;
  unsigned* const cnt = p.scr->cnt;

  float kacc[5][4];
  const int kpart = (warp >= 5) + (warp >= 10), kch = warp - 5 * kpart;
  float dt, k0;
  uint32_t xv[2][10], xs[2], mw, pds;
  {
    uint32_t pa[6], pld;
    unsigned ep0;
    if (warp < 15) {
      const int ch = (wid >> 4) * 80 + frag_col((wid & 15) * 5 + kch);
      const int o = (ch * 3 + kpart) * 32 + lane;
      pa[0] = __ldg((const uint32_t*)p.are + o); pa[1] = __ldg((const uint32_t*)p.aim + o);
      pa[2] = __ldg((const uint32_t*)p.bre + o); pa[3] = __ldg((const uint32_t*)p.bim + o);
      pa[4] = __ldg((const uint32_t*)p.cre + o); pa[5] = __ldg((const uint32_t*)p.cim + o);
      pld = __ldg((const unsigned short*)p.logdt + ch);
      pds = __ldg((const unsigned short*)p.dskip + ch);
    } else {
      ep0 = p.scr->epoch[wid];
      if ((uint32_t)__cvta_generic_to_shared(smem_raw) != sb) __trap();
    }
    if (elect1()) {
      const int gi = (warp + 1) & 15;
#pragma unroll
      for (int i = 0; i < 5; i++) mbar_init(bar + 40 * gi + 8 * i, gi < 8 ? 1 : gi == 8 ? 4 : 8);
      asm volatile("fence.mbarrier_init.release.cluster;" ::: "memory");
    }
    if (warp == 15) {
      sts64(sb + OFF_ZERO + (lane & 15) * 8 + (lane >> 4) * 640, 0, 0);
      int gpc, i;
      if (sid < 64) { gpc = (sid & 15) >> 1; i = sid >> 4; }
      else if (sid < 120) { const int t = sid - 64; i = t / 14; gpc = 1 + ((t - i * 14) >> 1); i += 4; }
      else { gpc = 0; i = 4 + ((sid - 124) >> 1); }
      const int qi = ((0x52741630 >> (4 * i)) & 7) * 2 + (sid & 1);
      const int rg = 4 * (gpc >> 1) + (qi >> 2), jc = 4 * (gpc & 1) + (qi & 3);
      sts64(sb + OFF_EP + 8, rg, jc);
      __syncwarp();
      if (elect1()) {
        if (DELAY_NS) __nanosleep(DELAY_NS);
        bulk_prefetch(p.x + wid * 16 * DM, 16 * DM * 2);
#pragma unroll 1
        for (int s = 0; s < 4; s++) load1(s, &tmX, &tmW1, rg, jc);
        bulk_prefetch(p.w1 + wid * 5 * FF, 5 * FF * 2);
        bulk_prefetch(p.w2 + wid * 12 * DM, 12 * DM * 2);
        asm volatile("prefetch.tensormap [%0];\nprefetch.tensormap [%1];" ::"l"(&tmU), "l"(&tmW2) : "memory");
      }
    }
#pragma unroll
    for (int j = 0; j < 5; j++) { kacc[j][0] = kacc[j][1] = kacc[j][2] = kacc[j][3] = 0.f; }
    float zr, th, zr1, th1;
    cf c, c1;
    const uint32_t ks = sb + OFF_KS + warp * 4096;
    if (warp < 15) {
      dt = rnd_bf(expf(bflo(pld)));
      c = cmul(cf{bflo(pa[4]), bflo(pa[5])}, cf{bflo(pa[2]), bflo(pa[3])});
      c1 = cmul(cf{bfhi(pa[4]), bfhi(pa[5])}, cf{bfhi(pa[2]), bfhi(pa[3])});
      mw = __reduce_max_sync(0xffffffffu, __float_as_uint(fmaxf(fmaxf(fabsf(c.r), fabsf(c.i)), fmaxf(fabsf(c1.r), fabsf(c1.i)))));
      mw = min(max(mw & 0x7f800000u, 20u << 23), 240u << 23);
      const float sc = __uint_as_float((259u << 23) - mw), dl2 = dt * 1.4426950408889634f;
      k0 = c.r + c1.r;
      zr = bflo(pa[0]) * dl2; th = bflo(pa[1]) * dt; zr1 = bfhi(pa[0]) * dl2; th1 = bfhi(pa[1]) * dt;
      c.r *= sc; c.i *= sc; c1.r *= sc; c1.i *= sc;
    }
    __syncwarp();
    if (warp >= 8) {
      const __nv_bfloat16* xr = p.x + (wid * 16 + ((g >> 1) << 2) + (g & 1)) * DM;
      load_x(xv, xr + (warp - 8) * 80, 2 * DM, q);
      xs[0] = __ldg((const uint32_t*)xr); xs[1] = __ldg((const uint32_t*)(xr + 2 * DM));
    }
    {
      const uint32_t ka = ks + (lane >> 3) * 512 + (lane & 7) * 16;
      const uint32_t kb = ks + ((lane >> 3) & 1) * 512 + ((lane >> 4) * 8 + (lane & 7)) * 16;
#pragma unroll 1
      for (int it = 0; it < 2; it++) {
        if (it == 1 && warp >= 8) {
          float sm[4] = {0.f, 0.f, 0.f, 0.f}, g0[4] = {0.f, 0.f, 0.f, 0.f}, g1[4] = {0.f, 0.f, 0.f, 0.f};
#pragma unroll
          for (int r = 0; r < 2; r++)
            xs[r] = fabsf(bflo(xs[r]) - bfhi(xs[r])) * 8.f < fabsf(bflo(xs[r])) ? __byte_perm(xs[r], 0, 0x1010) : 0u;
#pragma unroll
          for (int i = 0; i < 10; i += 2) {
            const uint32_t a0 = bsub(xv[0][i], xs[0]), a1 = bsub(xv[1][i], xs[1]), a2 = bsub(xv[0][i + 1], xs[0]), a3 = bsub(xv[1][i + 1], xs[1]);
            bmma(sm, a0, a1, a2, a3, 0x3f803f80u, 0x3f803f80u);
            bmma(g0, a0, a1, a2, a3, xv[0][i], xv[0][i + 1]);
            bmma(g1, a0, a1, a2, a3, xv[1][i], xv[1][i + 1]);
          }
          if (q == (g >> 1))
            sts128(sb + OFF_LNP + (warp - 8) * 128 + g * 16, __float_as_uint(sm[0]), __float_as_uint((g & 1) ? g0[1] : g0[0]),
                   __float_as_uint(sm[2]), __float_as_uint((g & 1) ? g1[3] : g1[2]));
          if (warp == 15) {
            bar_sync(1, 256);
            float s1 = 0.f, s2 = 0.f;
#pragma unroll
            for (int w = 0; w < 8; w++) {
              const uint2 v = lds64(sb + OFF_LNP + w * 128 + g * 16 + (q & 1) * 8);
              s1 += __uint_as_float(v.x); s2 += __uint_as_float(v.y);
            }
            const float md = s1 * (1.f / DM), mean = bflo((q & 1) ? xs[1] : xs[0]) + md;
            const float var = fmaxf(fmaf(-md, mean, s2 * (1.f / DM)), 0.f);
            const float m = rnd_bf(mean);
            float sd, ri;
            asm("sqrt.approx.f32 %0, %1;" : "=f"(sd) : "f"(rnd_bf(rnd_bf(var) + 1e-5f)));
            asm("rcp.approx.f32 %0, %1;" : "=f"(ri) : "f"(rnd_bf(sd)));
            if (q < 2) {
              p.scr->stats[wid * 16 + ((g >> 1) << 2) + (g & 1) + 2 * q] = make_float2(-m, 0.5f * ri);
              sts64(sb + OFF_STAT + g * 16 + q * 8, __float_as_uint(-m * ri), __float_as_uint(ri));
            }
          } else bar_arrive(1, 256);
          bar_sync(7, 256);
          {
            const uint4 st = lds128(sb + OFF_STAT + g * 16);
            const float n0 = __uint_as_float(st.x), r0 = __uint_as_float(st.y), n1 = __uint_as_float(st.z), r1 = __uint_as_float(st.w);
            const int up = upos(2 * wid);
            uint2* dst = (uint2*)p.scr->uT + ((up >> 1) * DM + (warp - 8) * 80) * 4 + (lane ^ ((up & 1) << 1));
#pragma unroll
            for (int i = 0; i < 10; i++) {
              const uint32_t a = movm(pack_h(fmaf(bflo(xv[0][i]), r0, n0), fmaf(bfhi(xv[0][i]), r0, n0)));
              const uint32_t b = movm(pack_h(fmaf(bflo(xv[1][i]), r1, n1), fmaf(bfhi(xv[1][i]), r1, n1)));
              dst[i * 32] = make_uint2(a, b);
            }
          }
          if (warp == 15) {
            if (lane == 0) { p.scr->epoch[wid] = ep0 + 1; sts32(sb + OFF_EP, ep0 + 1); }
            __syncwarp();
            bar_arrive(0, 512);
            bar_sync(12, 256);
            if (lane == 0) publish(cnt + C_LN * 32);
            __syncwarp();
          } else bar_arrive(12, 256);
        }
        if (warp == 15) continue;
        float m = ex2a(zr);
        const cf w1 = cf{m * __cosf(th), m * __sinf(th)};
        m = ex2a(zr * 8.f);
        const cf w8 = cf{m * __cosf(th * 8.f), m * __sinf(th * 8.f)};
        const cf w16 = csq(w8), w32 = csq(w16), w64 = csq(w32), w128 = csq(w64), w256 = csq(w128), w512 = csq(w256), w1024 = csq(w512);
        hp lo[8];
        lo[0] = hpack(cf{1.f, 0.f}, cf{w8.r, -w8.i});
        lo[1] = hmulc(lo[0], pack_h(w16.r, -w16.i));
        { const uint32_t k = pack_h(w32.r, -w32.i); lo[2] = hmulc(lo[0], k); lo[3] = hmulc(lo[1], k); }
        { const uint32_t k = pack_h(w64.r, -w64.i);
#pragma unroll
          for (int i = 0; i < 4; i++) lo[4 + i] = hmulc(lo[i], k); }
        const uint32_t st = ks + lane * 16;
        sts128(st, lo[0].r, lo[1].r, lo[2].r, lo[3].r);
        sts128(st + 512, lo[4].r, lo[5].r, lo[6].r, lo[7].r);
        sts128(st + 1024, lo[0].i, lo[1].i, lo[2].i, lo[3].i);
        sts128(st + 1536, lo[4].i, lo[5].i, lo[6].i, lo[7].i);
        const cf t1 = cmul(c, w1), t2 = cmul(t1, w1), t3 = cmul(t2, w1), t4 = cmul(t3, w1);
        const cf t5 = cmul(t4, w1), t6 = cmul(t5, w1), t7 = cmul(t6, w1), t8 = cmul(c, w8);
        hp T0[4], T1[4], T2[4], T3[4], T4[4];
        T0[0] = hpack(t4, t8); T0[1] = hpack(t2, t6); T0[2] = hpack(t1, t5); T0[3] = hpack(t3, t7);
        const uint32_t k128 = pack_h(w128.r, w128.i), k256 = pack_h(w256.r, w256.i), k512 = pack_h(w512.r, w512.i);
#pragma unroll
        for (int i = 0; i < 4; i++) T1[i] = hmulc(T0[i], k128);
        sts_tile(st + 2048, T0);
        sts_tile(st + 3072, T1);
        __syncwarp();
        uint32_t af[4][4];
#pragma unroll
        for (int mg = 0; mg < 4; mg++) ldsm4t(af[mg], ka + mg * 128);
#pragma unroll
        for (int j = 0; j < 2; j++)
#pragma unroll
          for (int mg = 0; mg < 4; mg += 2) {
            uint32_t b[4];
            ldsm4t(b, kb + 2048 + j * 1024 + mg * 128);
            hmma(kacc[j], af[mg][0], af[mg][1], af[mg][2], af[mg][3], b[0], b[1]);
            hmma(kacc[j], af[mg + 1][0], af[mg + 1][1], af[mg + 1][2], af[mg + 1][3], b[2], b[3]);
          }
        T2[0] = hmulc(T0[0], k256); T2[1] = hmulc(T0[1], k256); T2[2] = hmulc(T1[0], k256); T2[3] = hmulc(T1[1], k256);
        T3[0] = hmulc(T0[0], k512); T3[1] = hmulc(T1[0], k512); T3[2] = hmulc(T2[0], k512); T3[3] = hmulc(T2[2], k512);
        { const cf u0 = cmul(t8, w1024), u1 = cmul(u0, w128);
          T4[0] = hpack(u0, u1); T4[1] = hmulc(T4[0], k256); T4[2] = hmulc(T4[0], k512); T4[3] = hmulc(T4[1], k512); }
        __syncwarp();
        sts_tile(st, T2);
        sts_tile(st + 1024, T3);
        sts_tile(st + 2048, T4);
        __syncwarp();
#pragma unroll
        for (int j = 0; j < 3; j++)
#pragma unroll
          for (int mg = 0; mg < 4; mg += 2) {
            uint32_t b[4];
            ldsm4t(b, kb + j * 1024 + mg * 128);
            hmma(kacc[2 + j], af[mg][0], af[mg][1], af[mg][2], af[mg][3], b[0], b[1]);
            hmma(kacc[2 + j], af[mg + 1][0], af[mg + 1][1], af[mg + 1][2], af[mg + 1][3], b[2], b[3]);
          }
        __syncwarp();
        zr = zr1; th = th1; c = c1;
      }
    }
    if (warp < 10) {
#pragma unroll
      for (int j = 0; j < 5; j++)
        sts128(ks + j * 512 + lane * 16, __float_as_uint(kacc[j][0]), __float_as_uint(kacc[j][1]), __float_as_uint(kacc[j][2]), __float_as_uint(kacc[j][3]));
      sts64(ks + 2560 + lane * 8, __float_as_uint(k0), mw);
    }
  }
  if (warp < 15) bar_sync(0, 512);

  if (warp < 8) {
    float acc[96];
    const uint32_t alo = ((sb >> 4) | (1 << 16)) + (warp >> 2) * 512;
#pragma unroll 1
    for (int s = 0; s < 10; s++) {
      const uint32_t so = slot1(s) * (SLOT1 >> 4);
      mbar_wait(bar + 8 * (B_FULL1 + s), 0);
      wg_fence();
#pragma unroll
      for (int kk = 0; kk < 4; kk++)
        wgmma_n192(acc, dsc(alo + so + kk * 2, 0x40000040u), dsc((((sb + 16384) >> 4) | (512 << 16)) + so + kk * 128, 0x40000040u), (s | kk) != 0);
      wg_commit();
      wg_wait<1>();
      if (lane == 0) mbar_arrive(bar + 8 * (B_REL1 + s));
    }
    wg_wait<0>();
    bar_arrive(14, 512);
    mbar_wait(bar + 8 * B_EPI, 0);
    const uint2 s0 = lds64(sb + OFF_STAT + (warp * 16 + g) * 8), s1 = lds64(sb + OFF_STAT + (warp * 16 + g + 8) * 8);
    const float nm0 = __uint_as_float(s0.x), r0 = __uint_as_float(s0.y), nm1 = __uint_as_float(s1.x), r1 = __uint_as_float(s1.y);
    const uint4 erj = lds128(sb + OFF_EP);
    const unsigned ep = erj.x;
    const int rg1 = erj.z, j1 = erj.w;
    uint4* hd = p.scr->h + (rg1 * 24 + j1) * 1024 + warp * 128 + q * 8 + g;
#pragma unroll
    for (int grp = 0; grp < 6; grp++) {
      uint32_t o0[4], o1[4];
#pragma unroll
      for (int tl = 0; tl < 4; tl++) {
        const int nt = grp * 4 + tl;
        const uint2 cs = lds64(sb + OFF_CS + (nt * 8 + 2 * q) * 4);
        const float ca = __uint_as_float(cs.x), cb = __uint_as_float(cs.y);
        const float a = fmaf(nm0, ca, acc[4 * nt]) * r0, b = fmaf(nm0, cb, acc[4 * nt + 1]) * r0;
        const float c = fmaf(nm1, ca, acc[4 * nt + 2]) * r1, d = fmaf(nm1, cb, acc[4 * nt + 3]) * r1;
        o0[tl] = pack_bf(fmaf(a, tanha(a), a), fmaf(b, tanha(b), b));
        o1[tl] = pack_bf(fmaf(c, tanha(c), c), fmaf(d, tanha(d), d));
      }
      uint4* dst = hd + (grp >> 1) * 8192 + (grp & 1) * 32;
      dst[0] = make_uint4(o0[0], o0[1], o0[2], o0[3]);
      dst[64] = make_uint4(o1[0], o1[1], o1[2], o1[3]);
      if (PACE_NS) __nanosleep(PACE_NS);
      if (grp == 1) {
        if (warp == 7) { bar_sync(2, 448); if (lane == 0) publish(cnt + C_H0 * 32); __syncwarp(); }
        else bar_arrive(2, 448);
      }
    }
    if (warp == 6) { bar_sync(11, 256); if (lane == 0) publish(cnt + (C_H1 + rg1) * 32); __syncwarp(); }
    else bar_arrive(11, 256);
    const int go = (rg1 * 128 + warp * 16 + g) * DM + j1 * 80;
    load_x(xv, p.x + go, 8 * DM, q);
    if (warp == 4) {
      if (elect1()) {
        poll_cnt(cnt + C_H0 * 32, ep * 128);
#pragma unroll 1
        for (int s = 0; s < NS2 - 1; s++) {
          if (s == 3) poll_cnt(cnt + (C_H1 + rg1) * 32, ep * 8);
          if (s >= 3) mbar_wait(bar + 8 * (B_FREE + (s == 3 ? 0 : s - 2)), 0);
          if (s == 4) mbar_wait(bar + 8 * (B_FREE + 1), 0);
          const uint32_t mb = bar + 8 * (B_FULL2 + s);
          mbar_expect(mb, SLOT2);
          bulk_g2s(sb + s * SLOT2, p.scr->h + (rg1 * 24 + s) * 1024, 16384, mb);
          bulk_g2s(sb + s * SLOT2 + 16384, p.scr->w2p + (j1 * 24 + s) * 640, 10240, mb);
        }
      }
      __syncwarp();
    }
    float acc2[40];
    bar_sync(8, 384);
    {
      const uint32_t al2 = ((sb >> 4) | (8 << 16)) + (warp >> 2) * 512;
      uint32_t so = 0;
#pragma unroll 1
      for (int s = 0; s < 24; s++) {
        mbar_wait(bar + 8 * (B_FULL2 + s), 0);
        wg_fence();
#pragma unroll
        for (int kk = 0; kk < 4; kk++)
          wgmma_n80(acc2, dsc(al2 + so + kk * 16, 64), dsc((((sb + 16384) >> 4) | (80 << 16)) + so + kk * 160, 8), (s | kk) != 0);
        wg_commit();
        so = so == (NS2 - 1) * (SLOT2 >> 4) ? 0 : so + (SLOT2 >> 4);
        wg_wait<1>();
        if (lane == 0) mbar_arrive(bar + 8 * (B_REL2 + s));
      }
    }
    mbar_wait(bar + 8 * B_SFULL, 0);
    uint32_t sv[5][4];
    {
      const int i = lane & 7, mi = lane >> 3;
      const uint32_t a = sb + OFF_U + ((mi >> 1) * 8 + i) * 256 + (((2 * warp + (mi & 1)) ^ i) << 4);
#pragma unroll
      for (int k = 0; k < 5; k++) ldsm4t(sv[k], a + k * 4096);
    }
    wg_wait<0>();
#pragma unroll
    for (int hh = 0; hh < 2; hh++) {
      uint32_t o[10];
#pragma unroll
      for (int tl = 0; tl < 10; tl++) {
        const uint32_t xw = xv[hh][tl];
        const uint32_t sw = sv[tl >> 1][(tl & 1) * 2 + hh];
        const float a = acc2[4 * tl + 2 * hh], b = acc2[4 * tl + 2 * hh + 1];
        o[tl] = pack_bf(fmaf(bflo(sw), fmaf(a, tanha(a), a), bflo(xw)), fmaf(bfhi(sw), fmaf(b, tanha(b), b), bfhi(xw)));
      }
      __nv_bfloat16* op = p.out + go + hh * 8 * DM;
      ((uint4*)op)[q] = make_uint4(o[0], o[1], o[2], o[3]);
      ((uint4*)op)[4 + q] = make_uint4(o[4], o[5], o[6], o[7]);
      ((uint2*)(op + 64))[q] = make_uint2(o[8], o[9]);
    }
  } else {
    const int cw = warp - 8;
    const uint4 erj = lds128(sb + OFF_EP);
    const unsigned ep = erj.x;
    const int rg1 = erj.z, j1 = erj.w;
    if (warp == 15) {
      if (elect1()) {
#pragma unroll 1
        for (int s = 4; s < 10; s++) {
          mbar_wait(bar + 8 * (B_REL1 + s - ((RING3 && s >= 7) ? 2 : 3)), 0);
          load1(s, &tmX, &tmW1, rg1, j1);
        }
      }
      __syncwarp();
    }
    if (warp >= 10 && warp < 15) {
      const uint32_t pb = sb + OFF_P + kch * 3072, pk = sb + OFF_KS + kch * 4096;
      const uint2 e0 = lds64(pk + 2560 + lane * 8), e1 = lds64(pk + 5 * 4096 + 2560 + lane * 8);
      const float dsk = bflo(pds);
      uint32_t kex = __float_as_uint(fmaxf(__uint_as_float(max(max(e0.y, e1.y), mw)) * dt, fabsf(dsk) * (1.f / 256.f))) >> 23;
      kex = min(max(kex, 20u), 240u);
      const float s2 = __uint_as_float((258 - kex) << 23), sd = s2 * dt * (1.f / 32.f);
      const float f0 = __uint_as_float(e0.y) * sd, f1 = __uint_as_float(e1.y) * sd, f2 = __uint_as_float(mw) * sd;
      k0 += __uint_as_float(e0.x) + __uint_as_float(e1.x);
#pragma unroll
      for (int o = 16; o; o >>= 1) k0 += __shfl_xor_sync(0xffffffffu, k0, o);
      const float k0n = fmaf(k0, dt, dsk) * s2;
      uint32_t h[5][2];
#pragma unroll
      for (int j = 0; j < 5; j++) {
        const uint4 a = lds128(pk + j * 512 + lane * 16), b = lds128(pk + 5 * 4096 + j * 512 + lane * 16);
#pragma unroll
        for (int e = 0; e < 4; e++) kacc[j][e] = fmaf(__uint_as_float((&a.x)[e]), f0, fmaf(__uint_as_float((&b.x)[e]), f1, kacc[j][e] * f2));
        if (j == 1) {
          const float k256 = __shfl_sync(0xffffffffu, kacc[1][3], 28);
          if (lane == 31) kacc[1][3] -= k256;
        }
        if (j == 2 || j == 3) { h[j][0] = pack_h(kacc[j][0], kacc[j][2]); h[j][1] = pack_h(kacc[j][1], kacc[j][3]); }
        else { h[j][0] = pack_h(kacc[j][0], kacc[j][1]); h[j][1] = pack_h(kacc[j][2], kacc[j][3]); }
      }
      fence_async_smem();
      bar_arrive(4, 192);
#pragma unroll
      for (int i = 0; i < 6; i++) sts128(pb + i * 512 + lane * 16, 0, 0, 0, 0);
      __syncwarp();
      {
        const int sw = g >> 2;
        const uint32_t sel = sw ? 0x1032 : 0x3210;
        const uint32_t a = pb + (P0 + 8 * g + ((0x3124 >> (4 * q)) & 7)) * 4, a0 = a + sw * 16, a1 = a + 16 - sw * 16;
        put2<1>(a0, a1, h[0][0], sel);
        put2<1>(a0 + 256, a1 + 256, h[0][1], sel);
        put2<1>(a0 + 512, a1 + 512, h[1][0], sel);
        put2<1>(lane == 28 ? pb + PB1 * 4 : a0 + 768, a1 + 768, h[1][1], sel);
      }
      {
        const int sw = q >> 1;
        const uint32_t sel = sw ? 0x1032 : 0x3210;
        uint32_t a = pb + (((q & 1) ? PA1 : PB1 + 1) + 32 * sw + 2 * g) * 4;
        put2<1>(a + sw * 64, a + 64 - sw * 64, h[2][0], sel);
        put2<1>(a + 4 + sw * 64, a + 68 - sw * 64, h[2][1], sel);
        a = pb + (PA2 + g + 16 * q) * 4;
        put2<2>(a + sw * 32, a + 32 - sw * 32, h[3][0], sel);
        put2<2>(a + (PB2 - PA2) * 4 + sw * 32, a + (PB2 - PA2) * 4 + 32 - sw * 32, h[3][1], sel);
        a = pb + (((g & 1) ? PB3 : PA3) + (g >> 1) + 16 * q) * 4;
        const uint32_t hx = sw ? h[4][1] : h[4][0], hy = sw ? h[4][0] : h[4][1];
        put2<1>(a + sw * 16, a + 32 + sw * 16, hx, 0x3210);
        put2<1>(a + 16 - sw * 16, a + 48 - sw * 16, hy, 0x3210);
      }
      if (lane == 30) put2<1>(pb + P0 * 4, pb + (PA1 + 64) * 4, pack_h(k0n, kacc[2][3]), 0x3210);
      if (lane == 31) sts64(sb + OFF_CHC + kch * 8, (kex - 4) * 0x00800080u, __byte_perm(h[3][1], 0, 0x3232));
    }
    if (warp == 8) {
      bar_sync(13, 64);
      if (elect1()) {
        mbar_expect(bar + 8 * B_UFULL, 20480);
        mbar_expect(bar + 8 * B_EPI, 1024 + 768);
        poll_cnt(cnt + C_LN * 32, ep * 128);
        tma2d(sb + OFF_U, &tmU, wid * 80, 0, bar + 8 * B_UFULL);
        bulk_g2s(sb + OFF_STAT, p.scr->stats + rg1 * 128, 1024, bar + 8 * B_EPI);
      }
      __syncwarp();
      bar_arrive(15, 224);
    } else if (warp == 9) {
      bar_sync(4, 192);
      bar_arrive(13, 64);
      if (elect1()) {
        mbar_expect(bar + 8 * B_W2, 96 * 176);
        tma5d(sb + OFF_W2S, &tmW2, (wid & 7) * 80, (wid >> 3) * 3, bar + 8 * B_W2);
        poll_cnt(cnt + C_CS * 32, ep * 4);
        bulk_g2s(sb + OFF_CS, p.scr->cs + j1 * 192, 768, bar + 8 * B_EPI);
      }
      __syncwarp();
    }
    if (warp >= 9 && warp < 15) {
      const int uu = (warp - 9) >> 1, G = (warp - 9) & 1;
      const int grp = (wid >> 3) * 3 + uu, jj = grp / 6, rem = grp - jj * 6;
      const uint32_t a = sb + OFF_W2S + (uu * 32 + lane) * 176;
      uint4* dst = p.scr->w2p + ((wid & 7) * 24 + 8 * (rem >> 1) + jj) * 640 + ((rem & 1) * 4 + (lane >> 3)) * 80 + (lane & 7);
      mbar_wait(bar + 8 * B_W2, 0);
      const uint4 wv[4] = {lds128(a + G * 64), lds128(a + G * 64 + 16), lds128(a + G * 64 + 32), lds128(a + G * 64 + 48)};
      const uint4 t0 = lds128(a + 128), t1 = lds128(a + 144);
      uint32_t w[20];
#pragma unroll
      for (int i = 0; i < 16; i++) w[i] = bmul((&wv[i >> 2].x)[i & 3], 0x3f003f00u);
      w[16] = bmul(G ? t0.y : t0.x, 0x3f003f00u); w[17] = bmul(G ? t0.w : t0.z, 0x3f003f00u);
      w[18] = bmul(G ? t1.y : t1.x, 0x3f003f00u); w[19] = bmul(G ? t1.w : t1.z, 0x3f003f00u);
      bar_sync(15, 224);
#pragma unroll
      for (int i = 0; i < 4; i++) dst[G * 32 + 8 * i] = make_uint4(w[i], w[4 + i], w[8 + i], w[12 + i]);
      dst[64 + G * 8] = make_uint4(w[16], w[17], w[18], w[19]);
      bar_arrive(2, 448);
      if (warp == 12) bar_arrive(3, 64);
    } else if (warp == 15) bar_sync(3, 64);
    mbar_wait(bar + 8 * B_UFULL, 0);
#pragma unroll 1
    for (int ch = 2 + (cw >> 2) * 2; ch >= 0; ch -= ch == 4 ? 1 : 2) {
      if (ch < 4) mbar_wait(bar + 8 * (B_REL1 + ((RING3 && ch >= 2) ? 4 : 8)), 0);
      const int qt = (cw + ch) & 3, j = qt * 32 + lane;
      const uint32_t ub = sb + OFF_U + ch * 32, zb = sb + OFF_Z + ch * ZSZ;
      uint32_t w_[20], o_[20], d_[20], b3_[20];
      uint32_t *w = w_ + 8, *o = o_ + 8, *d = d_ + 8, *b3 = b3_ + 8;
      {
        const uint32_t am = j > 0 ? ub + uoff(upos(2 * j - 2)) : sb + OFF_ZERO, a0 = ub + uoff(upos(2 * j));
        const uint2 a = lds64(am + 8);
        const uint4 b = lds128(am ^ 16), c = lds128(a0), e = lds128(a0 ^ 16);
        w[8] = lds32(ub + uoff(upos((2 * j + 2) & 255)));
        w[-6] = a.x; w[-5] = a.y; w[-4] = b.x; w[-3] = b.y; w[-2] = b.z; w[-1] = b.w;
        w[0] = c.x; w[1] = c.y; w[2] = c.z; w[3] = c.w; w[4] = e.x; w[5] = e.y; w[6] = e.z; w[7] = e.w;
      }
#pragma unroll
      for (int i = -1; i <= 7; i++) o[i] = odd_pair(w[i], w[i + 1]);
#pragma unroll
      for (int i = 0; i <= 7; i++) { d[i] = hadd(w[i], o[i]); b3[i] = hadd(d[i], o[i - 1]); }
      if (j < 112) {
        const int gr = j >> 1;
        const uint32_t a1 = zb + ZA1 + 128 + (gr ^ ((gr >> 2) & 1)) * 64 + ((gr >> 1) & 3) * 16 + (j & 1) * 8;
#pragma unroll
        for (int pp = 0; pp < 4; pp++) {
          const uint32_t sel = (pp & 1) ? 0x7632 : 0x5410;
          const int k = pp >> 1;
          sts64(a1 ^ (pp * 16), __byte_perm(w[k - 1], w[k + 1], sel), __byte_perm(w[k + 3], w[k + 5], sel));
          sts64((a1 ^ (pp * 16)) + (ZB1 - ZA1), __byte_perm(b3[k], b3[k + 2], sel), __byte_perm(b3[k + 4], b3[k + 6], sel));
        }
      } else if (j >= 120) {
        sts128(zb + ZA1 + ((lane >> 2) & 1) * (ZB1 - ZA1) + (3 - q) * 16, 0, 0, 0, j == 127 ? w[8] << 16 : 0u);
      }
      if (qt < 3) {
        uint32_t e_[20], b5_[20];
        uint32_t *e = e_ + 8, *b5 = b5_ + 8;
#pragma unroll
        for (int i = -6; i <= -2; i++) o[i] = odd_pair(w[i], w[i + 1]);
#pragma unroll
        for (int i = -6; i <= -1; i++) d[i] = hadd(w[i], o[i]);
#pragma unroll
        for (int i = -5; i <= -1; i++) b3[i] = hadd(d[i], o[i - 1]);
#pragma unroll
        for (int i = -5; i <= 4; i++) e[i] = hadd(d[i - 1], d[i]);
#pragma unroll
        for (int i = -4; i <= 4; i++) b5[i] = hadd(e[i], w[i + 1]);
        const uint32_t a2 = zb + ((j >> 3) * 16 + (j & 7)) * 16;
        sts128(a2 + ZA2, b3[-2], b3[-1], b3[0], b3[1]);
        sts128(a2 + ZA2 + 128, b3[2], b3[3], b3[4], b3[5]);
        sts128(a2 + ZB2, b5[-4], b5[-3], b5[-2], b5[-1]);
        sts128(a2 + ZB2 + 128, b5[0], b5[1], b5[2], b5[3]);
        if (qt < 2) {
          sts128(a2 + ZS, d[-2], d[-1], d[0], d[1]);
          sts128(a2 + ZS + 128, d[2], d[3], d[4], d[5]);
          uint32_t b7[8], b9[8];
#pragma unroll
          for (int i = -4; i <= 3; i++) { b7[i + 4] = hadd(b3[i - 1], e[i + 1]); b9[i + 4] = hadd(e[i - 1], b5[i + 1]); }
          const uint32_t a3 = zb + ((j >> 4) * 32 + (j & 15)) * 16;
          sts128(a3 + ZA3, b7[0], b7[1], b7[2], b7[3]);
          sts128(a3 + ZA3 + 256, b7[4], b7[5], b7[6], b7[7]);
          sts128(a3 + ZB3 + 256, b9[0], b9[1], b9[2], b9[3]);
          if (j < 63) sts128(a3 + ZB3 + ((j & 15) == 15 ? 272 : 16), b9[4], b9[5], b9[6], b9[7]);
          else sts128(zb + ZB3, 0, 0, 0, 0);
        }
      }
    }
    const int wg = warp >> 2, role = (warp + 2 * wg) & 3;
    bar_sync(14, 512);
    const uint32_t nz = lds32(sb + OFF_ZERO) | 0x80000000u;
#pragma unroll 1
    for (int ch = wg - 2; ch < 5; ch += 2) {
      const uint32_t ub = sb + OFF_U + ch * 32, zb = sb + OFF_Z + ch * ZSZ, pb = sb + OFF_P + ch * 3072;
      const uint2 chc = lds64(sb + OFF_CHC + ch * 8);
      const int tid = lds32(sb + OFF_ZERO + 20) + threadIdx.x;
      const int lane = tid & 31, g = lane >> 2, q = lane & 3;
      const uint32_t pa = pb + (g - 2 * q) * 4;
      if (role < 2) {
        float acc[8][4];
#pragma unroll
        for (int r = 0; r < 8; r++) { acc[r][0] = acc[r][1] = acc[r][2] = acc[r][3] = 0.f; }
        float fix = 0.f;
        if (role == 1 && lane == 28) {
          const uint32_t k = lds32(pb + PB1 * 4), u0 = lds32(ub);
          fix = __low2float(*reinterpret_cast<const __half2*>(&k)) * __low2float(*reinterpret_cast<const __half2*>(&u0));
        }
        uint32_t ga[3][2];
#pragma unroll
        for (int gm = 0; gm < 3; gm++) {
          const int hb = 2 * (lane & 7) + role - 2 + gm, l3 = ((lane >> 3) ^ (hb >> 1)) & 7;
          ga[gm][0] = hb < 0 ? sb + OFF_ZERO + ((l3 * 16 + ch * 32) & 127) : ub + hb * 1280 + uoff(l3);
          ga[gm][1] = hb < 0 ? ga[gm][0] ^ 64 : ub + hb * 1280 + uoff(l3 ^ 4);
        }
        uint32_t b[12][4], A[17][4];
#pragma unroll
        for (int i = 11; i >= 8; i--) ldsm4(b[i], (ga[2][i & 1] ^ (((i >> 1) & 1) * 16)) + ((i >> 1) & 1) * 640);
        A[0][0] = lds32(pa + P0 * 4); A[0][1] = lds32(pa + P0 * 4 + 32); A[0][2] = lds32(sb + OFF_ZERO + 4);
#pragma unroll
        for (int m = 0; m <= 16; m++) {
          if (m < 16) {
            A[m + 1][0] = lds32(pa + P0 * 4 + (2 * m + 2) * 32);
            A[m + 1][1] = m < 15 ? lds32(pa + P0 * 4 + (2 * m + 3) * 32) : lds32(sb + OFF_ZERO + 8);
          }
          if ((m & 1) == 0 && m < 16) {
            const int i = 7 - (m >> 1);
            ldsm4(b[i], (ga[i >> 2][i & 1] ^ (((i >> 1) & 1) * 16)) + ((i >> 1) & 1) * 640);
          }
          A[m][3] = dup(A[m][0], nz);
          if (m < 16) A[m + 1][2] = dup(A[m][1], nz);
#pragma unroll
          for (int r = 7; r >= 0; r--) {
            const int f = 16 + r - m;
            hmma(acc[r], A[m][0], A[m][1], A[m][2], A[m][3], b[f >> 1][(f & 1) * 2], b[f >> 1][(f & 1) * 2 + 1]);
          }
        }
        acc[7][2] += fix;
        bar_sync(7 + wg, 64);
#pragma unroll
        for (int i = 3; i >= 0; i--)
          stsm4t((ga[2][i & 1] ^ (((i >> 1) & 1) * 16)) + ((i >> 1) & 1) * 640, pack_bf(acc[2 * i][0], acc[2 * i][1]), pack_bf(acc[2 * i][2], acc[2 * i][3]),
                 pack_bf(acc[2 * i + 1][0], acc[2 * i + 1][1]), pack_bf(acc[2 * i + 1][2], acc[2 * i + 1][3]));
      } else if (role == 2) {
        float acc[14][4];
#pragma unroll
        for (int r = 0; r < 14; r++) { acc[r][0] = acc[r][1] = acc[r][2] = acc[r][3] = 0.f; }
        const int mi = lane >> 3, hf = (lane >> 2) & 1;
        const uint32_t ze = zb + ZA1 + 128 - 512 + hf * 1792 + (mi ^ hf) * 64 + ((q ^ (mi >> 1) ^ (hf * 2)) << 4);
        const uint32_t zo = ze ^ 96;
#pragma unroll
        for (int arr = 0; arr < 2; arr++) {
          uint32_t A[5][4];
#pragma unroll
          for (int m = 0; m < 5; m++) {
            A[m][0] = lds32(pa + (arr ? PB1 : PA1) * 4 + m * 64);
            A[m][1] = m < 4 ? lds32(pa + (arr ? PB1 : PA1) * 4 + m * 64 + 32) : lds32(sb + OFF_ZERO + 4 + arr * 8);
          }
#pragma unroll
          for (int m = 4; m >= 1; m--) { A[m][2] = dup(A[m - 1][1], nz); A[m][3] = dup(A[m][0], nz); }
          A[0][2] = lds32(sb + OFF_ZERO + 8 + arr * 8); A[0][3] = dup(A[0][0], nz);
#pragma unroll
          for (int ip = 0; ip < 9; ip++) {
            uint32_t b[4];
            uint32_t ad = ((ip & 1) ? zo : ze) + ip * 256 + arr * (ZB1 - ZA1);
            if (ip < 2 && hf == 0 && (ip == 0 || mi != 3)) ad = sb + OFF_ZERO + (ad & 127);
            ldsm4(b, ad);
#pragma unroll
            for (int hh = 0; hh < 2; hh++)
#pragma unroll
              for (int m = 0; m < 5; m++) {
                const int i = 2 * ip + hh - 4 + m;
                if (i >= 0 && i < 14) hmma(acc[i], A[m][0], A[m][1], A[m][2], A[m][3], b[2 * hh], b[2 * hh + 1]);
              }
          }
        }
        const uint32_t a = zb + ZA1 + ((lane ^ (mi & 1)) << 4);
#pragma unroll
        for (int i = 0; i < 7; i++)
          stsm4(a + i * 512, pack_bf(acc[2 * i][0], acc[2 * i][1]), pack_bf(acc[2 * i][2], acc[2 * i][3]),
                pack_bf(acc[2 * i + 1][0], acc[2 * i + 1][1]), pack_bf(acc[2 * i + 1][2], acc[2 * i + 1][3]));
      } else {
        float acc[12][4];
        const uint32_t za = zb + lane * 16;
        {
          float d[4][2][4];
#pragma unroll
          for (int r = 0; r < 8; r++) { d[r >> 1][r & 1][0] = d[r >> 1][r & 1][1] = d[r >> 1][r & 1][2] = d[r >> 1][r & 1][3] = 0.f; }
#pragma unroll
          for (int arr = 0; arr < 2; arr++) {
            uint32_t A[4][4];
#pragma unroll
            for (int m = 0; m < 4; m++) { A[m][0] = lds32(pa + (arr ? PB3 : PA3) * 4 + m * 64); A[m][1] = lds32(pa + (arr ? PB3 : PA3) * 4 + m * 64 + 32); }
#pragma unroll
            for (int m = 0; m < 4; m++) { A[m][2] = m ? dup(A[m - 1][1], nz) : lds32(sb + OFF_ZERO + 4 + arr * 4); A[m][3] = dup(A[m][0], nz); }
#pragma unroll
            for (int io = 0; io < 4; io++) {
              uint32_t b[4];
              ldsm4t(b, za + (arr ? ZB3 : ZA3) + io * 512);
#pragma unroll
              for (int m = 0; m + io < 4; m++) {
                hmma(d[io + m][0], A[m][0], A[m][1], A[m][2], A[m][3], b[0], b[1]);
                hmma(d[io + m][1], A[m][0], A[m][1], A[m][2], A[m][3], b[2], b[3]);
              }
            }
          }
#pragma unroll
          for (int r = 0; r < 4; r++) {
            acc[r][0] = acc[r][1] = acc[r][2] = acc[r][3] = 0.f;
            acc[4 + 2 * r][0] = d[r][0][0]; acc[4 + 2 * r][1] = d[r][0][1]; acc[4 + 2 * r][2] = d[r][1][0]; acc[4 + 2 * r][3] = d[r][1][1];
            acc[5 + 2 * r][0] = d[r][0][2]; acc[5 + 2 * r][1] = d[r][0][3]; acc[5 + 2 * r][2] = d[r][1][2]; acc[5 + 2 * r][3] = d[r][1][3];
          }
        }
        {
          const uint32_t k0 = (g >> 1) == q ? (chc.y & ((g & 1) ? 0xffff0000u : 0xffffu)) : 0u;
          const uint32_t k1 = lds32(sb + OFF_ZERO + 12), k2 = lds32(sb + OFF_ZERO + 16), k3 = dup(k0, nz);
#pragma unroll
          for (int ip = 0; ip < 4; ip++) {
            uint32_t b[4];
            ldsm4t(b, za + ZS + ip * 512);
            hmma(acc[4 + 2 * ip], k0, k1, k2, k3, b[0], b[1]);
            hmma(acc[5 + 2 * ip], k0, k1, k2, k3, b[2], b[3]);
          }
        }
        const uint32_t pa2 = pb + (2 * g - 4 * q) * 4;
#pragma unroll
        for (int arr = 0; arr < 2; arr++) {
          uint32_t A[5][4];
#pragma unroll
          for (int m = 0; m < 5; m++) {
            const uint2 v = lds64(pa2 + (arr ? PB2 : PA2) * 4 + m * 64);
            A[m][0] = v.x; A[m][1] = v.y; A[m][2] = lds32(pa2 + (arr ? PB2 : PA2) * 4 + m * 64 - 4);
          }
#pragma unroll
          for (int m = 0; m < 5; m++) A[m][3] = dup(A[m][0], nz);
#pragma unroll
          for (int ip = 0; ip < 6; ip++) {
            uint32_t b[4];
            ldsm4t(b, za + (arr ? ZB2 : ZA2) + ip * 512);
#pragma unroll
            for (int hh = 0; hh < 2; hh++)
#pragma unroll
              for (int m = 0; m < 5; m++) {
                const int i = 2 * ip + hh + m;
                if (i < 12) hmma(acc[i], A[m][0], A[m][1], A[m][2], A[m][3], b[2 * hh], b[2 * hh + 1]);
              }
          }
        }
        const uint32_t a = zb + ZA2 + ((lane ^ ((lane >> 1) & 4)) << 4);
#pragma unroll
        for (int i = 0; i < 6; i++)
          stsm4(a + i * 512, pack_bf(acc[2 * i][0], acc[2 * i][1]), pack_bf(acc[2 * i][2], acc[2 * i][3]),
                pack_bf(acc[2 * i + 1][0], acc[2 * i + 1][1]), pack_bf(acc[2 * i + 1][2], acc[2 * i + 1][3]));
      }
      if (ch == 4) bar_arrive(8, 384);
      bar_sync(3 + wg, 128);
      {
        const int row = (wid & 15) * 5 + ch;
        const int c = tid & 127, c1 = c < 112 ? c + 32 : c - 112, c2 = c < 112 ? c + 144 : c - 96;
        const uint32_t zr = sb + OFF_ZERO + (lane & 7) * 16;
        const uint32_t a1 = c < 112 ? zb + ZA1 + ((2 * c) ^ ((c >> 2) & 1)) * 16 : zr;
        const uint32_t a2 = zb + ZA2 + ((c & ~15) - 32 + ((((c >> 1) & 7) + (c & 1) * 8) ^ ((c & 1) * 4))) * 16;
        const uint4 v0 = lds128(ub + uoff(upos(c1))), u0 = lds128(ub + uoff(upos(c2)));
        const uint4 y0 = lds128(a1), y1 = lds128(a1 ^ 16);
        const uint4 v2 = lds128(c1 >= 64 ? a2 : zr), u2 = lds128(c < 112 ? a2 + 112 * 16 : zr);
        uint4* dst = p.scr->sT + ((wid >> 4) * 16 * 80 + row) * 16 + ((c & 15) ^ (row & 7));
        const uint4 v = make_uint4(bmul(badd(badd(y0.x, v2.x), v0.x), chc.x), bmul(badd(badd(y0.y, v2.y), v0.y), chc.x),
                                   bmul(badd(badd(y1.x, v2.z), v0.z), chc.x), bmul(badd(badd(y1.y, v2.w), v0.w), chc.x));
        const uint4 u = make_uint4(bmul(badd(badd(y0.z, u2.x), u0.x), chc.x), bmul(badd(badd(y0.w, u2.y), u0.y), chc.x),
                                   bmul(badd(badd(y1.z, u2.z), u0.z), chc.x), bmul(badd(badd(y1.w, u2.w), u0.w), chc.x));
        fence_async_smem();
        dst[(c1 >> 4) * 1280] = v;
        dst[(c2 >> 4) * 1280] = u;
      }
      __syncwarp();
      if (lane == 0) mbar_arrive(bar + 8 * (B_FREE + ch));
    }
    if (warp == 12) {
      if (elect1()) {
        const uint4* srcA = p.scr->h + (rg1 * 24 + NS2 - 1) * 1024;
        const uint4* srcB = p.scr->w2p + (j1 * 24 + NS2 - 1) * 640;
        uint32_t d = sb + (NS2 - 1) * SLOT2;
        mbar_wait(bar + 8 * (B_FULL2 + 3), 0);
        asm volatile("fence.proxy.async.global;" ::: "memory");
        mbar_wait(bar + 8 * (B_FREE + 4), 0);
#pragma unroll 1
        for (int s = NS2 - 1; s < 24; s++) {
          mbar_wait(bar + 8 * (B_REL2 + s - NS2 + 1), 0);
          const uint32_t mb = bar + 8 * (B_FULL2 + s);
          mbar_expect(mb, SLOT2);
          bulk_g2s(d, srcA, 16384, mb);
          bulk_g2s(d + 16384, srcB, 10240, mb);
          srcA += 1024; srcB += 640;
          d = d == sb + (NS2 - 1) * SLOT2 ? sb : d + SLOT2;
        }
      }
      __syncwarp();
    } else if (warp == 13) {
      if (elect1()) {
        mbar_wait(bar + 8 * (B_FREE + 3), 0);
        mbar_wait(bar + 8 * (B_FREE + 4), 0);
        publish(cnt + (C_S + (wid >> 4)) * 32);
        mbar_expect(bar + 8 * B_SFULL, 20480);
        poll_cnt(cnt + (C_S + j1) * 32, ep * 16);
        mbar_wait(bar + 8 * (B_REL2 + 24 - NS2), 0);
        bulk_g2s(sb + OFF_U, p.scr->sT + (j1 * 16 + rg1) * 1280, 20480, bar + 8 * B_SFULL);
      }
      __syncwarp();
    }
  }
}

typedef CUresult (*EncodeFn)(CUtensorMap*, CUtensorMapDataType, cuuint32_t, void*, const cuuint64_t*, const cuuint64_t*,
                             const cuuint32_t*, const cuuint32_t*, CUtensorMapInterleave, CUtensorMapSwizzle,
                             CUtensorMapL2promotion, CUtensorMapFloatOOBfill);

}

extern "C" void kernel_launch(void* const* d_in, const int* in_sizes, int n_in, void* d_out, int out_size) {
  static EncodeFn enc = nullptr;
  static int nsm = 0;
  static void* scr = nullptr;
  if (!enc) {
    void* fn = nullptr;
    cudaDriverEntryPointQueryResult qr;
    cudaGetDriverEntryPoint("cuTensorMapEncodeTiled", &fn, cudaEnableDefault, &qr);
    enc = (EncodeFn)fn;
    int dev = 0;
    cudaGetDevice(&dev);
    cudaDeviceGetAttribute(&nsm, cudaDevAttrMultiProcessorCount, dev);
    cudaFuncSetAttribute(fused_s4_ffn_kernel<true>, cudaFuncAttributeMaxDynamicSharedMemorySize, SMEM_BYTES);
    cudaFuncSetAttribute(fused_s4_ffn_kernel<false>, cudaFuncAttributeMaxDynamicSharedMemorySize, SMEM_BYTES);
    cudaGetSymbolAddress(&scr, g_scr);
  }
  Params p;
  p.x = (const __nv_bfloat16*)d_in[0];
  p.are = (const __nv_bfloat16*)d_in[1]; p.aim = (const __nv_bfloat16*)d_in[2];
  p.bre = (const __nv_bfloat16*)d_in[3]; p.bim = (const __nv_bfloat16*)d_in[4];
  p.cre = (const __nv_bfloat16*)d_in[5]; p.cim = (const __nv_bfloat16*)d_in[6];
  p.logdt = (const __nv_bfloat16*)d_in[7]; p.dskip = (const __nv_bfloat16*)d_in[8];
  p.w1 = (const __nv_bfloat16*)d_in[10]; p.w2 = (const __nv_bfloat16*)d_in[11];
  p.out = (__nv_bfloat16*)d_out;
  p.scr = (Scratch*)scr;
  CUtensorMap tmX, tmW1, tmU, tmW2;
  const cuuint32_t es[5] = {1, 1, 1, 1, 1};
  {
    const cuuint64_t gd[5] = {DM, 2, 4, 4, FF / 32}, gs[4] = {DM * 2, DM * 16, DM * 4, DM * 64};
    const cuuint32_t bx[5] = {88, 2, 4, 4, 3};
    enc(&tmW2, CU_TENSOR_MAP_DATA_TYPE_BFLOAT16, 5, d_in[11], gd, gs, bx, es, CU_TENSOR_MAP_INTERLEAVE_NONE,
        CU_TENSOR_MAP_SWIZZLE_NONE, CU_TENSOR_MAP_L2_PROMOTION_NONE, CU_TENSOR_MAP_FLOAT_OOB_FILL_NONE);
  }
  {
    const cuuint64_t gd[2] = {16 * DM, 128}, gs[1] = {DM * 32};
    const cuuint32_t bx[2] = {80, 128};
    enc(&tmU, CU_TENSOR_MAP_DATA_TYPE_FLOAT16, 2, p.scr->uT, gd, gs, bx, es, CU_TENSOR_MAP_INTERLEAVE_NONE,
        CU_TENSOR_MAP_SWIZZLE_NONE, CU_TENSOR_MAP_L2_PROMOTION_NONE, CU_TENSOR_MAP_FLOAT_OOB_FILL_NONE);
  }
  {
    const cuuint64_t gd[2] = {DM, SEQ}, gs[1] = {DM * 2};
    const cuuint32_t bx[2] = {64, 128};
    enc(&tmX, CU_TENSOR_MAP_DATA_TYPE_BFLOAT16, 2, d_in[0], gd, gs, bx, es, CU_TENSOR_MAP_INTERLEAVE_NONE,
        CU_TENSOR_MAP_SWIZZLE_128B, CU_TENSOR_MAP_L2_PROMOTION_L2_128B, CU_TENSOR_MAP_FLOAT_OOB_FILL_NONE);
  }
  {
    const cuuint64_t gd[3] = {64, DM, FF / 64}, gs[2] = {FF * 2, 128};
    const cuuint32_t bx[3] = {64, 64, 3};
    enc(&tmW1, CU_TENSOR_MAP_DATA_TYPE_BFLOAT16, 3, d_in[10], gd, gs, bx, es, CU_TENSOR_MAP_INTERLEAVE_NONE,
        CU_TENSOR_MAP_SWIZZLE_128B, CU_TENSOR_MAP_L2_PROMOTION_L2_128B, CU_TENSOR_MAP_FLOAT_OOB_FILL_NONE);
  }
  if (nsm == 132) fused_s4_ffn_kernel<true><<<132, 512, SMEM_BYTES>>>(p, tmX, tmW1, tmU, tmW2);
  else fused_s4_ffn_kernel<false><<<132, 512, SMEM_BYTES>>>(p, tmX, tmW1, tmU, tmW2);
}
```

```cpp
#include <cuda_runtime.h>
#include <cuda_bf16.h>
#include <cuda_fp16.h>
#include <cuda.h>
#include <stdint.h>

namespace {

constexpr int SEQ = 2048, DM = 640, FF = 1536;

constexpr int SLOT1 = 40960;
constexpr int SLOT2 = 26624;
constexpr int NS2 = 7;
#define DELAY_NS 200
#define PACE_NS 30
constexpr int OFF_Z = 85504, ZSZ = 20480;
constexpr int ZA3 = 0, ZB3 = 2048, ZS = 4096, ZA2 = 6144, ZB2 = 9216, ZA1 = 12288, ZB1 = 16384;
constexpr int OFF_W2S = OFF_Z + 4 * ZSZ;
constexpr int OFF_U = 190464;
constexpr int OFF_P = 210944;
constexpr int OFF_KS = 163840;
constexpr int OFF_LNP = 225280;
constexpr int OFF_MISC = 226304;
constexpr int OFF_CHC = OFF_MISC + 16;
constexpr int OFF_EP = OFF_MISC + 64;
constexpr int OFF_ZERO = OFF_MISC + 128;
constexpr int OFF_STAT = OFF_MISC + 1024;
constexpr int OFF_CS = OFF_MISC + 2048;
constexpr int OFF_BAR = OFF_MISC + 2816;
constexpr int SMEM_BYTES = OFF_MISC + 6144;
constexpr int P0 = 8, PA1 = 280, PB1 = 360, PA2 = 448, PB2 = 544, PA3 = 632, PB3 = 704;
enum { B_FULL1 = 0, B_FULL2 = 10, B_UFULL = 34, B_EPI = 35, B_SFULL = 36, B_W2 = 37, B_MMA = 38,
       B_FREE = 40,
       B_REL1 = 45, B_REL2 = 55, B_NUM = 80 };
enum { C_LN = 0, C_CS = 1, C_H0 = 2, C_H1 = 18, C_S = 34, C_W2 = 42, C_NUM = 43 };

struct Scratch {
  unsigned cnt[64 * 32];
  unsigned epoch[256];
  float2 stats[SEQ];
  float cs[FF];
  uint4 uT[DM * 256];
  uint4 w2p[8 * 24 * 640];
  uint4 sT[8 * 16 * 1280];
  uint4 h[16 * 24 * 1024];
};
__device__ __align__(1024) Scratch g_scr;
constexpr uint32_t sb = 1024;
constexpr uint32_t bar = sb + OFF_BAR;

struct Params {
  const __nv_bfloat16 *are, *aim, *bre, *bim, *cre, *cim, *logdt, *dskip, *x, *w1, *w2;
  __nv_bfloat16* out;
  Scratch* scr;
};

__device__ __forceinline__ void mbar_init(uint32_t a, int c) { asm volatile("mbarrier.init.shared::cta.b64 [%0], %1;" ::"r"(a), "r"(c)); }
__device__ __forceinline__ void mbar_expect(uint32_t a, int b) { asm volatile("mbarrier.arrive.expect_tx.shared::cta.b64 _, [%0], %1;" ::"r"(a), "r"(b) : "memory"); }
__device__ __forceinline__ void mbar_arrive(uint32_t a) { asm volatile("mbarrier.arrive.shared::cta.b64 _, [%0];" ::"r"(a) : "memory"); }
__device__ __forceinline__ void mbar_wait(uint32_t a, int ph) {
  asm volatile(
      "{\n.reg .pred p;\n.reg .u32 n;\n"
      "mbarrier.try_wait.parity.shared::cta.b64 p, [%0], %1;\n@p bra LD;\nmov.u32 n, 0;\n"
      "LW:\nmbarrier.try_wait.parity.shared::cta.b64 p, [%0], %1, 20000;\n@p bra LD;\n"
      "add.u32 n, n, 1;\nsetp.lt.u32 p, n, 100000;\n@p bra LW;\ntrap;\nLD:\n}\n" ::"r"(a), "r"(ph) : "memory");
}
__device__ __forceinline__ void poll_cnt(const unsigned* p, unsigned target) {
  asm volatile(
      "{\n.reg .pred p;\n.reg .u32 n;\n.reg .s32 v;\nmov.u32 n, 0;\n"
      "LW:\nld.relaxed.gpu.global.u32 v, [%0];\nsub.s32 v, v, %1;\nsetp.ge.s32 p, v, 0;\n@p bra LD;\n"
      "nanosleep.u32 64;\nadd.u32 n, n, 1;\nsetp.lt.u32 p, n, 4000000;\n@p bra LW;\ntrap;\n"
      "LD:\nfence.acquire.gpu;\nfence.proxy.async.global;\n}\n" ::"l"(p), "r"(target) : "memory");
}
__device__ __forceinline__ void publish(unsigned* p) {
  asm volatile("fence.proxy.async.global;\nfence.release.gpu;\nred.relaxed.gpu.global.add.u32 [%0], 1;" ::"l"(p) : "memory");
}
__device__ __forceinline__ uint32_t movm(uint32_t v) { uint32_t r; asm volatile("movmatrix.sync.aligned.m8n8.trans.b16 %0, %1;" : "=r"(r) : "r"(v)); return r; }
__device__ __forceinline__ void fence_async_smem() { asm volatile("fence.proxy.async.shared::cta;" ::: "memory"); }
__device__ __forceinline__ bool elect1() { uint32_t p; asm volatile("{\n.reg .pred P;\nelect.sync _|P, 0xffffffff;\nselp.u32 %0,1,0,P;\n}\n" : "=r"(p)); return p; }
__device__ __forceinline__ void bar_sync(int id, int n) { asm volatile("bar.sync %0, %1;" ::"r"(id), "r"(n) : "memory"); }
__device__ __forceinline__ void bar_arrive(int id, int n) { asm volatile("bar.arrive %0, %1;" ::"r"(id), "r"(n) : "memory"); }
__device__ __forceinline__ void bulk_g2s(uint32_t dst, const void* src, int bytes, uint32_t mb) {
  asm volatile("cp.async.bulk.shared::cluster.global.mbarrier::complete_tx::bytes [%0], [%1], %2, [%3];" ::"r"(dst), "l"(src), "r"(bytes), "r"(mb) : "memory");
}
__device__ __forceinline__ void bulk_prefetch(const void* src, int bytes) { asm volatile("cp.async.bulk.prefetch.L2.global [%0], %1;" ::"l"(src), "r"(bytes) : "memory"); }
__device__ __forceinline__ void tma2d(uint32_t dst, const CUtensorMap* m, int c0, int c1, uint32_t mb) {
  asm volatile("cp.async.bulk.tensor.2d.shared::cluster.global.mbarrier::complete_tx::bytes [%0], [%1, {%3, %4}], [%2];" ::"r"(dst), "l"(m), "r"(mb), "r"(c0), "r"(c1) : "memory");
}
__device__ __forceinline__ void tma3d(uint32_t dst, const CUtensorMap* m, int c0, int c1, int c2, uint32_t mb) {
  asm volatile("cp.async.bulk.tensor.3d.shared::cluster.global.mbarrier::complete_tx::bytes [%0], [%1, {%3, %4, %5}], [%2];" ::"r"(dst), "l"(m), "r"(mb), "r"(c0), "r"(c1), "r"(c2) : "memory");
}
__device__ __forceinline__ int frag_col(int l) {
  const int tl = l >> 3, i = l & 7;
  return (tl < 8 ? 32 * (tl >> 2) + 8 * (i >> 1) + 2 * (tl & 3) : 48 + 4 * (i >> 1) + 2 * tl) + (i & 1);
}
__device__ __forceinline__ void tma5d(uint32_t dst, const CUtensorMap* m, int c0, int c4, uint32_t mb) {
  asm volatile("cp.async.bulk.tensor.5d.shared::cluster.global.mbarrier::complete_tx::bytes [%0], [%1, {%3, %5, %5, %5, %4}], [%2];" ::"r"(dst), "l"(m), "r"(mb), "r"(c0), "r"(c4), "r"(0) : "memory");
}
__device__ __forceinline__ uint64_t dsc(uint32_t lo, uint32_t hi) { return ((uint64_t)hi << 32) | lo; }
__device__ __forceinline__ void wg_fence() { asm volatile("wgmma.fence.sync.aligned;" ::: "memory"); }
__device__ __forceinline__ void wg_commit() { asm volatile("wgmma.commit_group.sync.aligned;" ::: "memory"); }
template <int N> __device__ __forceinline__ void wg_wait() { asm volatile("wgmma.wait_group.sync.aligned %0;" ::"n"(N) : "memory"); }
__device__ __forceinline__ void wgmma_n192(float (&d)[96], uint64_t da, uint64_t db, int scale_d) {
  asm volatile("{\n.reg .pred p;\nsetp.ne.b32 p, %98, 0;\n"
    "wgmma.mma_async.sync.aligned.m64n192k16.f32.bf16.bf16 "
    "{"
    "%0, %1, %2, %3, %4, %5, %6, %7, %8, %9, %10, %11, %12, %13, %14, %15, "
    "%16, %17, %18, %19, %20, %21, %22, %23, %24, %25, %26, %27, %28, %29, %30, %31, "
    "%32, %33, %34, %35, %36, %37, %38, %39, %40, %41, %42, %43, %44, %45, %46, %47, "
    "%48, %49, %50, %51, %52, %53, %54, %55, %56, %57, %58, %59, %60, %61, %62, %63, "
    "%64, %65, %66, %67, %68, %69, %70, %71, %72, %73, %74, %75, %76, %77, %78, %79, "
    "%80, %81, %82, %83, %84, %85, %86, %87, %88, %89, %90, %91, %92, %93, %94, %95"
    "}, "
    "%96, %97, p, 1, 1, 0, 1;\n}\n"
    : "+f"(d[0]), "+f"(d[1]), "+f"(d[2]), "+f"(d[3]), "+f"(d[4]), "+f"(d[5]), "+f"(d[6]), "+f"(d[7]),
      "+f"(d[8]), "+f"(d[9]), "+f"(d[10]), "+f"(d[11]), "+f"(d[12]), "+f"(d[13]), "+f"(d[14]), "+f"(d[15]),
      "+f"(d[16]), "+f"(d[17]), "+f"(d[18]), "+f"(d[19]), "+f"(d[20]), "+f"(d[21]), "+f"(d[22]), "+f"(d[23]),
      "+f"(d[24]), "+f"(d[25]), "+f"(d[26]), "+f"(d[27]), "+f"(d[28]), "+f"(d[29]), "+f"(d[30]), "+f"(d[31]),
      "+f"(d[32]), "+f"(d[33]), "+f"(d[34]), "+f"(d[35]), "+f"(d[36]), "+f"(d[37]), "+f"(d[38]), "+f"(d[39]),
      "+f"(d[40]), "+f"(d[41]), "+f"(d[42]), "+f"(d[43]), "+f"(d[44]), "+f"(d[45]), "+f"(d[46]), "+f"(d[47]),
      "+f"(d[48]), "+f"(d[49]), "+f"(d[50]), "+f"(d[51]), "+f"(d[52]), "+f"(d[53]), "+f"(d[54]), "+f"(d[55]),
      "+f"(d[56]), "+f"(d[57]), "+f"(d[58]), "+f"(d[59]), "+f"(d[60]), "+f"(d[61]), "+f"(d[62]), "+f"(d[63]),
      "+f"(d[64]), "+f"(d[65]), "+f"(d[66]), "+f"(d[67]), "+f"(d[68]), "+f"(d[69]), "+f"(d[70]), "+f"(d[71]),
      "+f"(d[72]), "+f"(d[73]), "+f"(d[74]), "+f"(d[75]), "+f"(d[76]), "+f"(d[77]), "+f"(d[78]), "+f"(d[79]),
      "+f"(d[80]), "+f"(d[81]), "+f"(d[82]), "+f"(d[83]), "+f"(d[84]), "+f"(d[85]), "+f"(d[86]), "+f"(d[87]),
      "+f"(d[88]), "+f"(d[89]), "+f"(d[90]), "+f"(d[91]), "+f"(d[92]), "+f"(d[93]), "+f"(d[94]), "+f"(d[95])
    : "l"(da), "l"(db), "r"(scale_d));
}

__device__ __forceinline__ void wgmma_n80(float (&d)[40], uint64_t da, uint64_t db, int scale_d) {
  asm volatile("{\n.reg .pred p;\nsetp.ne.b32 p, %42, 0;\n"
    "wgmma.mma_async.sync.aligned.m64n80k16.f32.bf16.bf16 "
    "{"
    "%0, %1, %2, %3, %4, %5, %6, %7, %8, %9, %10, %11, %12, %13, %14, %15, "
    "%16, %17, %18, %19, %20, %21, %22, %23, %24, %25, %26, %27, %28, %29, %30, %31, "
    "%32, %33, %34, %35, %36, %37, %38, %39"
    "}, "
    "%40, %41, p, 1, 1, 0, 1;\n}\n"
    : "+f"(d[0]), "+f"(d[1]), "+f"(d[2]), "+f"(d[3]), "+f"(d[4]), "+f"(d[5]), "+f"(d[6]), "+f"(d[7]),
      "+f"(d[8]), "+f"(d[9]), "+f"(d[10]), "+f"(d[11]), "+f"(d[12]), "+f"(d[13]), "+f"(d[14]), "+f"(d[15]),
      "+f"(d[16]), "+f"(d[17]), "+f"(d[18]), "+f"(d[19]), "+f"(d[20]), "+f"(d[21]), "+f"(d[22]), "+f"(d[23]),
      "+f"(d[24]), "+f"(d[25]), "+f"(d[26]), "+f"(d[27]), "+f"(d[28]), "+f"(d[29]), "+f"(d[30]), "+f"(d[31]),
      "+f"(d[32]), "+f"(d[33]), "+f"(d[34]), "+f"(d[35]), "+f"(d[36]), "+f"(d[37]), "+f"(d[38]), "+f"(d[39])
    : "l"(da), "l"(db), "r"(scale_d));
}

__device__ __forceinline__ void hmma(float* c, uint32_t a0, uint32_t a1, uint32_t a2, uint32_t a3, uint32_t b0, uint32_t b1) {
  asm volatile("mma.sync.aligned.m16n8k16.row.col.f32.f16.f16.f32 {%0,%1,%2,%3}, {%4,%5,%6,%7}, {%8,%9}, {%0,%1,%2,%3};"
      : "+f"(c[0]), "+f"(c[1]), "+f"(c[2]), "+f"(c[3]) : "r"(a0), "r"(a1), "r"(a2), "r"(a3), "r"(b0), "r"(b1));
}
__device__ __forceinline__ void ldsm4(uint32_t* r, uint32_t a) { asm volatile("ldmatrix.sync.aligned.m8n8.x4.shared.b16 {%0,%1,%2,%3}, [%4];" : "=r"(r[0]), "=r"(r[1]), "=r"(r[2]), "=r"(r[3]) : "r"(a) : "memory"); }
__device__ __forceinline__ void ldsm4t(uint32_t* r, uint32_t a) { asm volatile("ldmatrix.sync.aligned.m8n8.x4.trans.shared.b16 {%0,%1,%2,%3}, [%4];" : "=r"(r[0]), "=r"(r[1]), "=r"(r[2]), "=r"(r[3]) : "r"(a) : "memory"); }
__device__ __forceinline__ void stsm4(uint32_t a, uint32_t r0, uint32_t r1, uint32_t r2, uint32_t r3) { asm volatile("stmatrix.sync.aligned.m8n8.x4.shared.b16 [%0], {%1,%2,%3,%4};" ::"r"(a), "r"(r0), "r"(r1), "r"(r2), "r"(r3) : "memory"); }
__device__ __forceinline__ void stsm4t(uint32_t a, uint32_t r0, uint32_t r1, uint32_t r2, uint32_t r3) { asm volatile("stmatrix.sync.aligned.m8n8.x4.trans.shared.b16 [%0], {%1,%2,%3,%4};" ::"r"(a), "r"(r0), "r"(r1), "r"(r2), "r"(r3) : "memory"); }
__device__ __forceinline__ uint32_t lds32(uint32_t a) { uint32_t v; asm volatile("ld.shared.u32 %0, [%1];" : "=r"(v) : "r"(a) : "memory"); return v; }
__device__ __forceinline__ uint2 lds64(uint32_t a) { uint2 v; asm volatile("ld.shared.v2.u32 {%0,%1}, [%2];" : "=r"(v.x), "=r"(v.y) : "r"(a) : "memory"); return v; }
__device__ __forceinline__ uint4 lds128(uint32_t a) { uint4 v; asm volatile("ld.shared.v4.u32 {%0,%1,%2,%3}, [%4];" : "=r"(v.x), "=r"(v.y), "=r"(v.z), "=r"(v.w) : "r"(a) : "memory"); return v; }
__device__ __forceinline__ void sts16(uint32_t a, uint32_t v) { asm volatile("st.shared.u16 [%0], %1;" ::"r"(a), "h"((unsigned short)v) : "memory"); }
__device__ __forceinline__ void sts32(uint32_t a, uint32_t v) { asm volatile("st.shared.u32 [%0], %1;" ::"r"(a), "r"(v) : "memory"); }
__device__ __forceinline__ void sts64(uint32_t a, uint32_t x, uint32_t y) { asm volatile("st.shared.v2.u32 [%0], {%1,%2};" ::"r"(a), "r"(x), "r"(y) : "memory"); }
__device__ __forceinline__ void sts128(uint32_t a, uint32_t x, uint32_t y, uint32_t z, uint32_t w) { asm volatile("st.shared.v4.u32 [%0], {%1,%2,%3,%4};" ::"r"(a), "r"(x), "r"(y), "r"(z), "r"(w) : "memory"); }
__device__ __forceinline__ float bflo(uint32_t v) { return __uint_as_float(v << 16); }
__device__ __forceinline__ float bfhi(uint32_t v) { return __uint_as_float(v & 0xffff0000u); }
__device__ __forceinline__ uint32_t pack_bf(float lo, float hi) { uint32_t r; asm("cvt.rn.bf16x2.f32 %0, %1, %2;" : "=r"(r) : "f"(hi), "f"(lo)); return r; }
__device__ __forceinline__ uint32_t pack_h(float lo, float hi) { uint32_t r; asm("cvt.rn.f16x2.f32 %0, %1, %2;" : "=r"(r) : "f"(hi), "f"(lo)); return r; }
__device__ __forceinline__ float rnd_bf(float v) { return __bfloat162float(__float2bfloat16_rn(v)); }
__device__ __forceinline__ float ex2a(float v) { float r; asm("ex2.approx.ftz.f32 %0, %1;" : "=f"(r) : "f"(v)); return r; }
__device__ __forceinline__ float tanha(float v) { float r; asm("tanh.approx.f32 %0, %1;" : "=f"(r) : "f"(v)); return r; }
__device__ __forceinline__ uint32_t hadd(uint32_t a, uint32_t b) { uint32_t r; asm("add.rn.f16x2 %0, %1, %2;" : "=r"(r) : "r"(a), "r"(b)); return r; }
__device__ __forceinline__ uint32_t badd(uint32_t a, uint32_t b) { uint32_t r; asm("add.rn.bf16x2 %0, %1, %2;" : "=r"(r) : "r"(a), "r"(b)); return r; }
__device__ __forceinline__ uint32_t bmul(uint32_t a, uint32_t b) { uint32_t r; asm("mul.rn.bf16x2 %0, %1, %2;" : "=r"(r) : "r"(a), "r"(b)); return r; }
__device__ __forceinline__ uint32_t bsub(uint32_t a, uint32_t b) { uint32_t r; asm("sub.rn.bf16x2 %0, %1, %2;" : "=r"(r) : "r"(a), "r"(b)); return r; }
__device__ __forceinline__ uint32_t dup(uint32_t v, uint32_t nz) { uint32_t r; asm volatile("add.rn.f32 %0, %1, %2;" : "=r"(r) : "r"(v), "r"(nz)); return r; }
__device__ __forceinline__ void bmma(float* c, uint32_t a0, uint32_t a1, uint32_t a2, uint32_t a3, uint32_t b0, uint32_t b1) {
  asm("mma.sync.aligned.m16n8k16.row.col.f32.bf16.bf16.f32 {%0,%1,%2,%3}, {%4,%5,%6,%7}, {%8,%9}, {%0,%1,%2,%3};"
      : "+f"(c[0]), "+f"(c[1]), "+f"(c[2]), "+f"(c[3]) : "r"(a0), "r"(a1), "r"(a2), "r"(a3), "r"(b0), "r"(b1));
}
__device__ __forceinline__ uint32_t odd_pair(uint32_t a, uint32_t b) { return __byte_perm(a, b, 0x5432); }
__device__ __forceinline__ int upos(int c) { return c ^ ((c >> 5) & 7) ^ ((c >> 3) & 1); }
__device__ __forceinline__ int uoff(int pos) { return (pos >> 1) * 160 + (pos & 1) * 16; }

struct cf { float r, i; };
__device__ __forceinline__ cf cmul(cf a, cf b) { cf o; o.r = fmaf(a.r, b.r, -a.i * b.i); o.i = fmaf(a.r, b.i, a.i * b.r); return o; }
__device__ __forceinline__ cf cmulj(cf a, cf b) { cf o; o.r = fmaf(a.r, b.r, a.i * b.i); o.i = fmaf(a.i, b.r, -a.r * b.i); return o; }
__device__ __forceinline__ cf csq(cf a) { cf o; o.r = fmaf(a.r, a.r, -a.i * a.i); o.i = (a.r + a.r) * a.i; return o; }
struct hp { uint32_t r, i; };
__device__ __forceinline__ hp hpack(cf a, cf b) { hp o; o.r = pack_h(a.r, b.r); o.i = pack_h(a.i, b.i); return o; }
__device__ __forceinline__ hp hmulc(hp a, uint32_t c) {
  __half2 ar = *reinterpret_cast<__half2*>(&a.r), ai = *reinterpret_cast<__half2*>(&a.i), cc = *reinterpret_cast<__half2*>(&c);
  __half2 orr = __hfma2(ar, __low2half2(cc), __hneg2(__hmul2(ai, __high2half2(cc))));
  __half2 oi = __hfma2(ar, __high2half2(cc), __hmul2(ai, __low2half2(cc)));
  hp o; o.r = *reinterpret_cast<uint32_t*>(&orr); o.i = *reinterpret_cast<uint32_t*>(&oi); return o;
}
__device__ __forceinline__ hp hmulj(hp a, uint32_t c) {
  __half2 ar = *reinterpret_cast<__half2*>(&a.r), ai = *reinterpret_cast<__half2*>(&a.i), cc = *reinterpret_cast<__half2*>(&c);
  __half2 orr = __hfma2(ar, __low2half2(cc), __hmul2(ai, __high2half2(cc)));
  __half2 oi = __hfma2(ai, __low2half2(cc), __hneg2(__hmul2(ar, __high2half2(cc))));
  hp o; o.r = *reinterpret_cast<uint32_t*>(&orr); o.i = *reinterpret_cast<uint32_t*>(&oi); return o;
}
__device__ __forceinline__ void sts_tile(uint32_t a, const hp* t) {
  sts128(a, t[0].r, t[1].r, t[2].r, t[3].r);
  sts128(a + 512, t[0].i, t[1].i, t[2].i, t[3].i);
}
template <int STEP> __device__ __forceinline__ void put2(uint32_t a0, uint32_t a1, uint32_t h, uint32_t sel) {
  const uint32_t x = __byte_perm(h, h, sel), y = x >> 16;
  sts16(a0, x); sts16(a0 + STEP * 4 + 2, x);
  sts16(a1, y); sts16(a1 + STEP * 4 + 2, y);
}

__device__ __forceinline__ void spare_work(const Params& p, const CUtensorMap* tmW1, int k, int tid) {
  const int lane = tid & 31;
  unsigned ep = 0;
  if (tid >= 480) ep = p.scr->epoch[128 + k] + 1;
  if (tid == 480) {
    for (int i = 0; i < 8; i++) mbar_init(bar + 8 * i, i < 4 ? 1 : 12);
    asm volatile("fence.mbarrier_init.release.cluster;" ::: "memory");
    fence_async_smem();
  }
  __syncthreads();
  float a[2][4] = {{0.f, 0.f, 0.f, 0.f}, {0.f, 0.f, 0.f, 0.f}};
  if (tid >= 480) {
    if (elect1()) {
#pragma unroll 1
      for (int s = 0; s < 10; s++) {
        mbar_wait(bar + 8 * (4 + (s & 3)), ((s >> 2) & 1) ^ 1);
        mbar_expect(bar + 8 * (s & 3), 49152);
#pragma unroll 1
        for (int b = 0; b < 2; b++) tma3d(sb + (s & 3) * 49152 + b * 24576, tmW1, 0, s * 64, k * 6 + b * 3, bar + 8 * (s & 3));
      }
    }
    __syncwarp();
  } else if (tid < 384) {
    const uint32_t idn = (lane >> 3) == (lane & 3) ? ((lane & 4) ? 0x3f800000u : 0x3f80u) : 0u;
#pragma unroll 1
    for (int s = 0; s < 10; s++) {
      mbar_wait(bar + 8 * (s & 3), (s >> 2) & 1);
      const uint32_t ad = sb + (s & 3) * 49152 + (tid >> 6) * 8192 + (tid & 63) * 16;
#pragma unroll
      for (int i = 0; i < 8; i += 2) {
        const uint4 v = lds128(ad + i * 1024), w = lds128(ad + i * 1024 + 1024);
        bmma(a[0], v.x, v.y, w.x, w.y, idn, idn);
        bmma(a[1], v.z, v.w, w.z, w.w, idn, idn);
      }
      __syncwarp();
      if (lane == 0) mbar_arrive(bar + 8 * (4 + (s & 3)));
    }
    const int rho = (tid >> 3) & 7;
    const uint32_t ad = sb + 196608 + rho * 1536 + ((tid >> 6) * 8 + ((tid & 7) ^ rho)) * 32;
    sts128(ad, __float_as_uint(a[0][0]), __float_as_uint(a[0][1]), __float_as_uint(a[0][2]), __float_as_uint(a[0][3]));
    sts128(ad + 16, __float_as_uint(a[1][0]), __float_as_uint(a[1][1]), __float_as_uint(a[1][2]), __float_as_uint(a[1][3]));
  }
  __syncthreads();
  if (tid < 384) {
    float s = 0.f;
#pragma unroll
    for (int r = 0; r < 8; r++) s += __uint_as_float(lds32(sb + 196608 + r * 1536 + tid * 4));
    p.scr->cs[k * 384 + tid] = s;
  }
  __syncthreads();
  if (tid == 480) {
    publish(p.scr->cnt + C_CS * 32);
    p.scr->epoch[128 + k] = ep;
    poll_cnt(p.scr->cnt + C_LN * 32, ep * 128);
  }
}

__device__ __forceinline__ void load1(int s, const CUtensorMap* tmX, const CUtensorMap* tmW1, int rg1, int j1) {
  const uint32_t d = sb + (s & 3) * SLOT1, mb = bar + 8 * (B_FULL1 + s);
  mbar_expect(mb, SLOT1);
  tma2d(d, tmX, s * 64, rg1 * 128, mb);
  tma3d(d + 16384, tmW1, 0, s * 64, j1 * 3, mb);
}
__device__ __forceinline__ void load_x(uint32_t (&xv)[2][10], const __nv_bfloat16* xc, int rstep, int q) {
#pragma unroll
  for (int r = 0; r < 2; r++) {
    const uint4 a = __ldg((const uint4*)(xc + r * rstep) + q), b = __ldg((const uint4*)(xc + r * rstep) + 4 + q);
    const uint2 c = __ldg((const uint2*)(xc + r * rstep + 64) + q);
    xv[r][0] = a.x; xv[r][1] = a.y; xv[r][2] = a.z; xv[r][3] = a.w; xv[r][4] = b.x; xv[r][5] = b.y; xv[r][6] = b.z; xv[r][7] = b.w;
    xv[r][8] = c.x; xv[r][9] = c.y;
  }
}

template <bool USE_SMID>
__global__ void __launch_bounds__(512, 1)
fused_s4_ffn_kernel(const Params p, const __grid_constant__ CUtensorMap tmX, const __grid_constant__ CUtensorMap tmW1,
                    const __grid_constant__ CUtensorMap tmU, const __grid_constant__ CUtensorMap tmW2) {
  extern __shared__ __align__(1024) unsigned char smem_raw[];
  const int tid = threadIdx.x, lane = tid & 31;
  const int warp = __shfl_sync(0xffffffffu, tid >> 5, 0);
  const int g = lane >> 2, q = lane & 3;
  uint32_t sid;
  if (USE_SMID) asm("mov.u32 %0, %smid;" : "=r"(sid)); else sid = blockIdx.x;
  if (sid - 120u < 4u) { spare_work(p, &tmW1, sid - 120, tid); return; }
  const int wid = sid < 120 ? sid : sid - 4;
  unsigned* const cnt = p.scr->cnt;

  float kacc[5][4];
  const int kpart = (warp >= 5) + (warp >= 10), kch = warp - 5 * kpart;
  float dt, k0;
  uint32_t xv[2][10], xs[2], mw, pds;
  {
    uint32_t pa[6], pld;
    unsigned ep0;
    if (warp < 15) {
      const int ch = (wid >> 4) * 80 + frag_col((wid & 15) * 5 + kch);
      const int o = (ch * 3 + kpart) * 32 + lane;
      pa[0] = __ldg((const uint32_t*)p.are + o); pa[1] = __ldg((const uint32_t*)p.aim + o);
      pa[2] = __ldg((const uint32_t*)p.bre + o); pa[3] = __ldg((const uint32_t*)p.bim + o);
      pa[4] = __ldg((const uint32_t*)p.cre + o); pa[5] = __ldg((const uint32_t*)p.cim + o);
      pld = __ldg((const unsigned short*)p.logdt + ch);
      pds = __ldg((const unsigned short*)p.dskip + ch);
    } else {
      ep0 = p.scr->epoch[wid];
      if ((uint32_t)__cvta_generic_to_shared(smem_raw) != sb) __trap();
    }
    if (elect1()) {
      const int gi = (warp + 1) & 15;
#pragma unroll
      for (int i = 0; i < 5; i++) mbar_init(bar + 40 * gi + 8 * i, gi < 8 ? 1 : gi == 8 ? 4 : 8);
      asm volatile("fence.mbarrier_init.release.cluster;" ::: "memory");
    }
    if (warp == 15) {
      sts32(sb + OFF_ZERO + lane * 4, 0);
      int gpc, i;
      if (sid < 64) { gpc = (sid & 15) >> 1; i = sid >> 4; }
      else if (sid < 120) { const int t = sid - 64; i = t / 14; gpc = 1 + ((t - i * 14) >> 1); i += 4; }
      else { gpc = 0; i = 4 + ((sid - 124) >> 1); }
      const int qi = ((0x52741630 >> (4 * i)) & 7) * 2 + (sid & 1);
      const int rg = 4 * (gpc >> 1) + (qi >> 2), jc = 4 * (gpc & 1) + (qi & 3);
      sts64(sb + OFF_EP + 8, rg, jc);
      __syncwarp();
      if (elect1()) {
        if (DELAY_NS) __nanosleep(DELAY_NS);
        bulk_prefetch(p.x + wid * 16 * DM, 16 * DM * 2);
#pragma unroll 1
        for (int s = 0; s < 4; s++) load1(s, &tmX, &tmW1, rg, jc);
        bulk_prefetch(p.w1 + wid * 5 * FF, 5 * FF * 2);
        bulk_prefetch(p.w2 + wid * 12 * DM, 12 * DM * 2);
        asm volatile("prefetch.tensormap [%0];\nprefetch.tensormap [%1];" ::"l"(&tmU), "l"(&tmW2) : "memory");
      }
    }
#pragma unroll
    for (int j = 0; j < 5; j++) { kacc[j][0] = kacc[j][1] = kacc[j][2] = kacc[j][3] = 0.f; }
    float zr, th, zr1, th1;
    cf c, c1;
    const uint32_t ks = sb + OFF_KS + warp * 4096;
    if (warp < 15) {
      dt = rnd_bf(expf(bflo(pld)));
      c = cmul(cf{bflo(pa[4]), bflo(pa[5])}, cf{bflo(pa[2]), bflo(pa[3])});
      c1 = cmul(cf{bfhi(pa[4]), bfhi(pa[5])}, cf{bfhi(pa[2]), bfhi(pa[3])});
      mw = __reduce_max_sync(0xffffffffu, __float_as_uint(fmaxf(fmaxf(fabsf(c.r), fabsf(c.i)), fmaxf(fabsf(c1.r), fabsf(c1.i)))));
      mw = min(max(mw & 0x7f800000u, 20u << 23), 240u << 23);
      const float sc = __uint_as_float((259u << 23) - mw), dl2 = dt * 1.4426950408889634f;
      k0 = c.r + c1.r;
      zr = bflo(pa[0]) * dl2; th = bflo(pa[1]) * dt; zr1 = bfhi(pa[0]) * dl2; th1 = bfhi(pa[1]) * dt;
      c.r *= sc; c.i *= -sc; c1.r *= sc; c1.i *= -sc;
    }
    __syncwarp();
    if (warp >= 8) {
      const __nv_bfloat16* xr = p.x + (wid * 16 + ((g >> 1) << 2) + (g & 1)) * DM;
      load_x(xv, xr + (warp - 8) * 80, 2 * DM, q);
      xs[0] = __ldg((const uint32_t*)xr); xs[1] = __ldg((const uint32_t*)(xr + 2 * DM));
    }
    {
      const uint32_t ka = ks + (lane >> 3) * 512 + (lane & 7) * 16;
      const uint32_t kb = ks + ((lane >> 3) & 1) * 512 + ((lane >> 4) * 8 + (lane & 7)) * 16;
#pragma unroll 1
      for (int it = 0; it < 2; it++) {
        if (it == 1 && warp >= 8) {
          float sm[4] = {0.f, 0.f, 0.f, 0.f}, g0[4] = {0.f, 0.f, 0.f, 0.f}, g1[4] = {0.f, 0.f, 0.f, 0.f};
#pragma unroll
          for (int r = 0; r < 2; r++)
            xs[r] = fabsf(bflo(xs[r]) - bfhi(xs[r])) * 8.f < fabsf(bflo(xs[r])) ? __byte_perm(xs[r], 0, 0x1010) : 0u;
#pragma unroll
          for (int i = 0; i < 10; i += 2) {
            const uint32_t a0 = bsub(xv[0][i], xs[0]), a1 = bsub(xv[1][i], xs[1]), a2 = bsub(xv[0][i + 1], xs[0]), a3 = bsub(xv[1][i + 1], xs[1]);
            bmma(sm, a0, a1, a2, a3, 0x3f803f80u, 0x3f803f80u);
            bmma(g0, a0, a1, a2, a3, xv[0][i], xv[0][i + 1]);
            bmma(g1, a0, a1, a2, a3, xv[1][i], xv[1][i + 1]);
          }
          if (q == (g >> 1))
            sts128(sb + OFF_LNP + (warp - 8) * 128 + g * 16, __float_as_uint(sm[0]), __float_as_uint((g & 1) ? g0[1] : g0[0]),
                   __float_as_uint(sm[2]), __float_as_uint((g & 1) ? g1[3] : g1[2]));
          if (warp < 15) bar_arrive(1, 256);
        }
        if (warp == 15) continue;
        float m = ex2a(zr);
        const cf w1 = cf{m * __cosf(th), m * __sinf(th)};
        m = ex2a(zr * 8.f);
        const cf w8 = cf{m * __cosf(th * 8.f), m * __sinf(th * 8.f)};
        const cf w16 = csq(w8), w32 = csq(w16), w64 = csq(w32), w128 = csq(w64), w256 = csq(w128), w512 = csq(w256), w1024 = csq(w512);
        hp lo[8];
        lo[0] = hpack(cf{1.f, 0.f}, w8);
        lo[1] = hmulc(lo[0], pack_h(w16.r, w16.i));
        { const uint32_t k = pack_h(w32.r, w32.i); lo[2] = hmulc(lo[0], k); lo[3] = hmulc(lo[1], k); }
        { const uint32_t k = pack_h(w64.r, w64.i);
#pragma unroll
          for (int i = 0; i < 4; i++) lo[4 + i] = hmulc(lo[i], k); }
        const uint32_t st = ks + lane * 16;
        sts128(st + 512, lo[4].r, lo[5].r, lo[6].r, lo[7].r);
        sts128(st + 1536, lo[4].i, lo[5].i, lo[6].i, lo[7].i);
        sts128(st, lo[0].r, lo[1].r, lo[2].r, lo[3].r);
        sts128(st + 1024, lo[0].i, lo[1].i, lo[2].i, lo[3].i);
        const uint32_t k128 = pack_h(w128.r, w128.i), k256 = pack_h(w256.r, w256.i), k512 = pack_h(w512.r, w512.i);
        const cf t8 = cmulj(c, w8);
        hp T0[4], T1[4], T2[4], T3[4], T4[4];
        { const cf u0 = cmulj(t8, w1024), u1 = cmulj(u0, w128);
          T4[0] = hpack(u0, u1); T4[1] = hmulj(T4[0], k256); T4[2] = hmulj(T4[0], k512); T4[3] = hmulj(T4[1], k512); }
        sts_tile(st + 2048, T4);
        __syncwarp();
        uint32_t af[4][4];
#pragma unroll
        for (int mg = 0; mg < 4; mg++) ldsm4t(af[mg], ka + mg * 128);
#pragma unroll
        for (int mg = 0; mg < 4; mg += 2) {
          uint32_t b[4];
          ldsm4t(b, kb + 2048 + mg * 128);
          hmma(kacc[4], af[mg][0], af[mg][1], af[mg][2], af[mg][3], b[0], b[1]);
          hmma(kacc[4], af[mg + 1][0], af[mg + 1][1], af[mg + 1][2], af[mg + 1][3], b[2], b[3]);
        }
        const cf t1 = cmulj(c, w1), t2 = cmulj(t1, w1), t3 = cmulj(t2, w1), t4 = cmulj(t3, w1);
        const cf t5 = cmulj(t4, w1), t6 = cmulj(t5, w1), t7 = cmulj(t6, w1);
        T0[0] = hpack(t4, t8); T0[1] = hpack(t2, t6); T0[2] = hpack(t1, t5); T0[3] = hpack(t3, t7);
#pragma unroll
        for (int i = 0; i < 4; i++) T1[i] = hmulj(T0[i], k128);
        T2[0] = hmulj(T0[0], k256); T2[1] = hmulj(T0[1], k256); T2[2] = hmulj(T1[0], k256); T2[3] = hmulj(T1[1], k256);
        T3[0] = hmulj(T0[0], k512); T3[1] = hmulj(T1[0], k512); T3[2] = hmulj(T2[0], k512); T3[3] = hmulj(T2[2], k512);
        __syncwarp();
        sts_tile(st + 3072, T3);
        sts_tile(st + 2048, T2);
        sts_tile(st + 1024, T1);
        sts_tile(st, T0);
        __syncwarp();
#pragma unroll
        for (int mg = 0; mg < 4; mg += 2)
#pragma unroll
          for (int j = 3; j >= 0; j--) {
            uint32_t b[4];
            ldsm4t(b, kb + j * 1024 + mg * 128);
            hmma(kacc[j], af[mg][0], af[mg][1], af[mg][2], af[mg][3], b[0], b[1]);
            hmma(kacc[j], af[mg + 1][0], af[mg + 1][1], af[mg + 1][2], af[mg + 1][3], b[2], b[3]);
          }
        __syncwarp();
        zr = zr1; th = th1; c = c1;
      }
    }
    if (warp < 10) {
#pragma unroll
      for (int j = 0; j < 5; j++)
        sts128(ks + j * 512 + lane * 16, __float_as_uint(kacc[j][0]), __float_as_uint(kacc[j][1]), __float_as_uint(kacc[j][2]), __float_as_uint(kacc[j][3]));
      sts64(ks + 2560 + lane * 8, __float_as_uint(k0), mw);
    } else if (warp == 15) {
      if (lane == 0) { p.scr->epoch[wid] = ep0 + 1; sts32(sb + OFF_EP, ep0 + 1); }
      bar_sync(1, 256);
      float s1 = 0.f, s2 = 0.f;
#pragma unroll
      for (int w = 0; w < 8; w++) {
        const uint2 v = lds64(sb + OFF_LNP + w * 128 + g * 16 + (q & 1) * 8);
        s1 += __uint_as_float(v.x); s2 += __uint_as_float(v.y);
      }
      const float md = s1 * (1.f / DM), mean = bflo((q & 1) ? xs[1] : xs[0]) + md;
      const float var = fmaxf(fmaf(-md, mean, s2 * (1.f / DM)), 0.f);
      const float m = rnd_bf(mean);
      float sd, ri;
      asm("sqrt.approx.f32 %0, %1;" : "=f"(sd) : "f"(rnd_bf(rnd_bf(var) + 1e-5f)));
      asm("rcp.approx.f32 %0, %1;" : "=f"(ri) : "f"(rnd_bf(sd)));
      if (q < 2) {
        p.scr->stats[wid * 16 + ((g >> 1) << 2) + (g & 1) + 2 * q] = make_float2(-m, 0.5f * ri);
        sts64(sb + OFF_STAT + g * 16 + q * 8, __float_as_uint(-m * ri), __float_as_uint(ri));
      }
    }
  }
  __syncthreads();

  if (warp < 8) {
    float acc[96];
    const uint32_t alo = ((sb >> 4) | (1 << 16)) + (warp >> 2) * 512;
#pragma unroll 1
    for (int s = 0; s < 10; s++) {
      const uint32_t so = (s & 3) * (SLOT1 >> 4);
      mbar_wait(bar + 8 * (B_FULL1 + s), 0);
      wg_fence();
#pragma unroll
      for (int kk = 0; kk < 4; kk++)
        wgmma_n192(acc, dsc(alo + so + kk * 2, 0x40000040u), dsc((((sb + 16384) >> 4) | (512 << 16)) + so + kk * 128, 0x40000040u), (s | kk) != 0);
      wg_commit();
      wg_wait<1>();
      if (lane == 0) mbar_arrive(bar + 8 * (B_REL1 + s));
    }
    wg_wait<0>();
    bar_arrive(14, 384);
    bar_arrive(7, 384);
    mbar_wait(bar + 8 * B_EPI, 0);
    const uint2 s0 = lds64(sb + OFF_STAT + (warp * 16 + g) * 8), s1 = lds64(sb + OFF_STAT + (warp * 16 + g + 8) * 8);
    const float nm0 = __uint_as_float(s0.x), r0 = __uint_as_float(s0.y), nm1 = __uint_as_float(s1.x), r1 = __uint_as_float(s1.y);
    const uint4 erj = lds128(sb + OFF_EP);
    const unsigned ep = erj.x;
    const int rg1 = erj.z, j1 = erj.w;
    uint4* hd = p.scr->h + (rg1 * 24 + j1) * 1024 + warp * 128 + q * 8 + g;
#pragma unroll
    for (int grp = 0; grp < 6; grp++) {
      uint32_t o0[4], o1[4];
#pragma unroll
      for (int tl = 0; tl < 4; tl++) {
        const int nt = grp * 4 + tl;
        const uint2 cs = lds64(sb + OFF_CS + (nt * 8 + 2 * q) * 4);
        const float ca = __uint_as_float(cs.x), cb = __uint_as_float(cs.y);
        const float a = fmaf(nm0, ca, acc[4 * nt]) * r0, b = fmaf(nm0, cb, acc[4 * nt + 1]) * r0;
        const float c = fmaf(nm1, ca, acc[4 * nt + 2]) * r1, d = fmaf(nm1, cb, acc[4 * nt + 3]) * r1;
        o0[tl] = pack_bf(fmaf(a, tanha(a), a), fmaf(b, tanha(b), b));
        o1[tl] = pack_bf(fmaf(c, tanha(c), c), fmaf(d, tanha(d), d));
      }
      uint4* dst = hd + (grp >> 1) * 8192 + (grp & 1) * 32;
      dst[0] = make_uint4(o0[0], o0[1], o0[2], o0[3]);
      dst[64] = make_uint4(o1[0], o1[1], o1[2], o1[3]);
      if (PACE_NS) __nanosleep(PACE_NS);
      if (grp == 1) {
        if (warp == 7) { bar_sync(2, 448); if (lane == 0) publish(cnt + C_H0 * 32); __syncwarp(); }
        else bar_arrive(2, 448);
      }
    }
    if (warp == 6) { bar_sync(11, 256); if (lane == 0) publish(cnt + (C_H1 + rg1) * 32); __syncwarp(); }
    else bar_arrive(11, 256);
    const int go = (rg1 * 128 + warp * 16 + g) * DM + j1 * 80;
    load_x(xv, p.x + go, 8 * DM, q);
    if (warp == 4) {
      if (elect1()) {
        poll_cnt(cnt + C_H0 * 32, ep * 128);
#pragma unroll 1
        for (int s = 0; s < NS2 - 1; s++) {
          if (s == 3) poll_cnt(cnt + (C_H1 + rg1) * 32, ep * 8);
          if (s == 3) mbar_wait(bar + 8 * B_FREE, 0);
          if (s >= 3) mbar_wait(bar + 8 * (B_FREE + s - 2), 0);
          const uint32_t mb = bar + 8 * (B_FULL2 + s);
          mbar_expect(mb, SLOT2);
          bulk_g2s(sb + s * SLOT2, p.scr->h + (rg1 * 24 + s) * 1024, 16384, mb);
          bulk_g2s(sb + s * SLOT2 + 16384, p.scr->w2p + (j1 * 24 + s) * 640, 10240, mb);
        }
      }
      __syncwarp();
    }
    float acc2[40];
    bar_sync(8, 512);
    {
      const uint32_t al2 = ((sb >> 4) | (8 << 16)) + (warp >> 2) * 512;
      uint32_t so = 0;
#pragma unroll 1
      for (int s = 0; s < 24; s++) {
        mbar_wait(bar + 8 * (B_FULL2 + s), 0);
        wg_fence();
#pragma unroll
        for (int kk = 0; kk < 4; kk++)
          wgmma_n80(acc2, dsc(al2 + so + kk * 16, 64), dsc((((sb + 16384) >> 4) | (80 << 16)) + so + kk * 160, 8), (s | kk) != 0);
        wg_commit();
        so = so == (NS2 - 1) * (SLOT2 >> 4) ? 0 : so + (SLOT2 >> 4);
        wg_wait<1>();
        if (lane == 0) mbar_arrive(bar + 8 * (B_REL2 + s));
      }
    }
    mbar_wait(bar + 8 * B_SFULL, 0);
    uint32_t sv[5][4];
    {
      const int i = lane & 7, mi = lane >> 3;
      const uint32_t a = sb + OFF_U + ((mi >> 1) * 8 + i) * 256 + (((2 * warp + (mi & 1)) ^ i) << 4);
#pragma unroll
      for (int k = 0; k < 5; k++) ldsm4t(sv[k], a + k * 4096);
    }
    wg_wait<0>();
#pragma unroll
    for (int hh = 0; hh < 2; hh++) {
      uint32_t o[10];
#pragma unroll
      for (int tl = 0; tl < 10; tl++) {
        const uint32_t xw = xv[hh][tl];
        const uint32_t sw = sv[tl >> 1][(tl & 1) * 2 + hh];
        const float a = acc2[4 * tl + 2 * hh], b = acc2[4 * tl + 2 * hh + 1];
        o[tl] = pack_bf(fmaf(bflo(sw), fmaf(a, tanha(a), a), bflo(xw)), fmaf(bfhi(sw), fmaf(b, tanha(b), b), bfhi(xw)));
      }
      __nv_bfloat16* op = p.out + go + hh * 8 * DM;
      ((uint4*)op)[q] = make_uint4(o[0], o[1], o[2], o[3]);
      ((uint4*)op)[4 + q] = make_uint4(o[4], o[5], o[6], o[7]);
      ((uint2*)(op + 64))[q] = make_uint2(o[8], o[9]);
    }
  } else {
    const int cw = warp - 8;
    const uint4 erj = lds128(sb + OFF_EP);
    const unsigned ep = erj.x;
    const int rg1 = erj.z, j1 = erj.w;
    {
      const uint4 st = lds128(sb + OFF_STAT + g * 16);
      const float n0 = __uint_as_float(st.x), r0 = __uint_as_float(st.y), n1 = __uint_as_float(st.z), r1 = __uint_as_float(st.w);
      const int up = upos(2 * wid);
      uint2* dst = (uint2*)p.scr->uT + ((up >> 1) * DM + cw * 80) * 4 + (lane ^ ((up & 1) << 1));
#pragma unroll
      for (int i = 0; i < 10; i++) {
        const uint32_t a = movm(pack_h(fmaf(bflo(xv[0][i]), r0, n0), fmaf(bfhi(xv[0][i]), r0, n0)));
        const uint32_t b = movm(pack_h(fmaf(bflo(xv[1][i]), r1, n1), fmaf(bfhi(xv[1][i]), r1, n1)));
        dst[i * 32] = make_uint2(a, b);
      }
    }
    if (warp == 8) {
      bar_sync(12, 256);
      if (lane == 0) publish(cnt + C_LN * 32);
      __syncwarp();
    } else bar_arrive(12, 256);
    if (warp == 15) {
      if (elect1()) {
#pragma unroll 1
        for (int s = 4; s < 10; s++) {
          mbar_wait(bar + 8 * (B_REL1 + s - 3), 0);
          load1(s, &tmX, &tmW1, rg1, j1);
        }
      }
      __syncwarp();
    }
    if (warp >= 10 && warp < 15) {
      const uint32_t pb = sb + OFF_P + kch * 3072, pk = sb + OFF_KS + kch * 4096;
      const uint2 e0 = lds64(pk + 2560 + lane * 8), e1 = lds64(pk + 5 * 4096 + 2560 + lane * 8);
      const float dsk = bflo(pds);
      uint32_t kex = __float_as_uint(fmaxf(__uint_as_float(max(max(e0.y, e1.y), mw)) * dt, fabsf(dsk) * (1.f / 256.f))) >> 23;
      kex = min(max(kex, 20u), 240u);
      const float s2 = __uint_as_float((258 - kex) << 23), sd = s2 * dt * (1.f / 32.f);
      const float f0 = __uint_as_float(e0.y) * sd, f1 = __uint_as_float(e1.y) * sd, f2 = __uint_as_float(mw) * sd;
      k0 += __uint_as_float(e0.x) + __uint_as_float(e1.x);
#pragma unroll
      for (int o = 16; o; o >>= 1) k0 += __shfl_xor_sync(0xffffffffu, k0, o);
      const float k0n = fmaf(k0, dt, dsk) * s2;
      uint32_t h[5][2];
#pragma unroll
      for (int j = 0; j < 5; j++) {
        const uint4 a = lds128(pk + j * 512 + lane * 16), b = lds128(pk + 5 * 4096 + j * 512 + lane * 16);
#pragma unroll
        for (int e = 0; e < 4; e++) kacc[j][e] = fmaf(__uint_as_float((&a.x)[e]), f0, fmaf(__uint_as_float((&b.x)[e]), f1, kacc[j][e] * f2));
        if (j == 1) {
          const float k256 = __shfl_sync(0xffffffffu, kacc[1][3], 28);
          if (lane == 31) kacc[1][3] -= k256;
        }
        if (j == 2 || j == 3) { h[j][0] = pack_h(kacc[j][0], kacc[j][2]); h[j][1] = pack_h(kacc[j][1], kacc[j][3]); }
        else { h[j][0] = pack_h(kacc[j][0], kacc[j][1]); h[j][1] = pack_h(kacc[j][2], kacc[j][3]); }
      }
      fence_async_smem();
      bar_arrive(4, 192);
#pragma unroll
      for (int i = 0; i < 6; i++) sts128(pb + i * 512 + lane * 16, 0, 0, 0, 0);
      __syncwarp();
      {
        const int sw = g >> 2;
        const uint32_t sel = sw ? 0x1032 : 0x3210;
        const uint32_t a = pb + (P0 + 8 * g + ((0x3124 >> (4 * q)) & 7)) * 4, a0 = a + sw * 16, a1 = a + 16 - sw * 16;
        put2<1>(a0, a1, h[0][0], sel);
        put2<1>(a0 + 256, a1 + 256, h[0][1], sel);
        put2<1>(a0 + 512, a1 + 512, h[1][0], sel);
        put2<1>(lane == 28 ? pb + PB1 * 4 : a0 + 768, a1 + 768, h[1][1], sel);
      }
      {
        const int sw = q >> 1;
        const uint32_t sel = sw ? 0x1032 : 0x3210;
        uint32_t a = pb + (((q & 1) ? PA1 : PB1 + 1) + 32 * sw + 2 * g) * 4;
        put2<1>(a + sw * 64, a + 64 - sw * 64, h[2][0], sel);
        put2<1>(a + 4 + sw * 64, a + 68 - sw * 64, h[2][1], sel);
        a = pb + (PA2 + g + 16 * q) * 4;
        put2<2>(a + sw * 32, a + 32 - sw * 32, h[3][0], sel);
        put2<2>(a + (PB2 - PA2) * 4 + sw * 32, a + (PB2 - PA2) * 4 + 32 - sw * 32, h[3][1], sel);
        a = pb + (((g & 1) ? PB3 : PA3) + (g >> 1) + 16 * q) * 4;
        const uint32_t hx = sw ? h[4][1] : h[4][0], hy = sw ? h[4][0] : h[4][1];
        put2<1>(a + sw * 16, a + 32 + sw * 16, hx, 0x3210);
        put2<1>(a + 16 - sw * 16, a + 48 - sw * 16, hy, 0x3210);
      }
      if (lane == 30) put2<1>(pb + P0 * 4, pb + (PA1 + 64) * 4, pack_h(k0n, kacc[2][3]), 0x3210);
      if (lane == 31) sts64(sb + OFF_CHC + kch * 8, (kex - 4) * 0x00800080u, __byte_perm(h[3][1], 0, 0x3232));
    }
    if (warp == 8) {
      bar_sync(13, 64);
      if (elect1()) {
        mbar_expect(bar + 8 * B_UFULL, 144 * 160);
        mbar_expect(bar + 8 * B_EPI, 1024 + 768);
        poll_cnt(cnt + C_LN * 32, ep * 128);
        tma2d(sb + OFF_U - 16 * 160, &tmU, wid * 80, -16, bar + 8 * B_UFULL);
        bulk_g2s(sb + OFF_STAT, p.scr->stats + rg1 * 128, 1024, bar + 8 * B_EPI);
      }
      __syncwarp();
      bar_arrive(15, 224);
    } else if (warp == 9) {
      bar_sync(4, 192);
      bar_arrive(13, 64);
      if (elect1()) {
        mbar_expect(bar + 8 * B_W2, 96 * 176);
        tma5d(sb + OFF_W2S, &tmW2, (wid & 7) * 80, (wid >> 3) * 3, bar + 8 * B_W2);
        poll_cnt(cnt + C_CS * 32, ep * 4);
        bulk_g2s(sb + OFF_CS, p.scr->cs + j1 * 192, 768, bar + 8 * B_EPI);
      }
      __syncwarp();
    }
    if (warp >= 9 && warp < 15) {
      const int uu = (warp - 9) >> 1, G = (warp - 9) & 1;
      const int grp = (wid >> 3) * 3 + uu, jj = grp / 6, rem = grp - jj * 6;
      const uint32_t a = sb + OFF_W2S + (uu * 32 + lane) * 176;
      uint4* dst = p.scr->w2p + ((wid & 7) * 24 + 8 * (rem >> 1) + jj) * 640 + ((rem & 1) * 4 + (lane >> 3)) * 80 + (lane & 7);
      mbar_wait(bar + 8 * B_W2, 0);
      const uint4 wv[4] = {lds128(a + G * 64), lds128(a + G * 64 + 16), lds128(a + G * 64 + 32), lds128(a + G * 64 + 48)};
      const uint4 t0 = lds128(a + 128), t1 = lds128(a + 144);
      uint32_t w[20];
#pragma unroll
      for (int i = 0; i < 16; i++) w[i] = bmul((&wv[i >> 2].x)[i & 3], 0x3f003f00u);
      w[16] = bmul(G ? t0.y : t0.x, 0x3f003f00u); w[17] = bmul(G ? t0.w : t0.z, 0x3f003f00u);
      w[18] = bmul(G ? t1.y : t1.x, 0x3f003f00u); w[19] = bmul(G ? t1.w : t1.z, 0x3f003f00u);
      bar_sync(15, 224);
#pragma unroll
      for (int i = 0; i < 4; i++) dst[G * 32 + 8 * i] = make_uint4(w[i], w[4 + i], w[8 + i], w[12 + i]);
      dst[64 + G * 8] = make_uint4(w[16], w[17], w[18], w[19]);
      bar_arrive(2, 448);
      if (warp == 12) bar_arrive(3, 64);
    } else if (warp == 15) bar_sync(3, 64);
    const int wg = warp >> 2, role = (warp + 2 * wg) & 3;
    uint32_t co[6], cb[5], cpa = (g - 2 * q) * 4;
    int cg0, cg1;
    if (role < 2) {
#pragma unroll
      for (int gm = 0; gm < 3; gm++) {
        const int hb = 2 * (lane & 7) + role - 2 + gm, l3 = ((lane >> 3) ^ (hb >> 1)) & 7;
        co[2 * gm] = hb * 1280 + uoff(l3); co[2 * gm + 1] = hb * 1280 + uoff(l3 ^ 4);
      }
    } else {
      const int mi = lane >> 3, hf = (lane >> 2) & 1;
      co[0] = hf * 1792 + (mi ^ hf) * 64 + ((q ^ (mi >> 1) ^ (hf * 2)) << 4);
      co[1] = co[0] ^ 96;
      co[2] = (lane ^ (role == 2 ? (mi & 1) : ((lane >> 1) & 4))) << 4;
      co[3] = lane * 16;
      co[4] = (g >> 1) == q ? ((g & 1) ? 0xffff0000u : 0xffffu) : 0u;
      co[5] = 2 * cpa;
    }
    {
      const int c = tid & 127, c1 = c < 112 ? c + 32 : c - 112, c2 = c < 112 ? c + 144 : c - 96;
      const uint32_t zr = ZA1 + (lane & 7) * 16, a2 = ZA2 + ((c & ~15) - 32 + ((((c >> 1) & 7) + (c & 1) * 8) ^ ((c & 1) * 4))) * 16;
      cb[0] = uoff(upos(c1)); cb[1] = uoff(upos(c2));
      cb[2] = c < 112 ? ZA1 + 512 + ((2 * c) ^ ((c >> 2) & 1)) * 16 : zr;
      cb[3] = c1 >= 64 ? a2 : zr; cb[4] = c < 112 ? a2 + 112 * 16 : zr;
      cg0 = (c1 >> 4) * 1280 + (c & 15); cg1 = (c2 >> 4) * 1280 + (c & 15);
    }
    const uint32_t nz = lds32(sb + OFF_ZERO) | 0x80000000u;
#pragma unroll
    for (int i = 0; i < 6; i++) co[i] += nz << 1;
#pragma unroll
    for (int i = 0; i < 5; i++) cb[i] += nz << 1;
    cg0 += nz << 1; cg1 += nz << 1; cpa += nz << 1;
    mbar_wait(bar + 8 * B_UFULL, 0);
#pragma unroll 1
    for (int ch = (cw >> 2) * 4; ch >= (cw >> 2); ch--) {
      if (ch < 4) mbar_wait(bar + 8 * (B_REL1 + (ch ? 8 : 7)), 0);
      const int qt = (cw + ch) & 3, j = qt * 32 + lane;
      const uint32_t ub = sb + OFF_U + ch * 32, zb = sb + OFF_Z + ch * ZSZ;
      uint32_t w_[20], o_[20], d_[20], b3_[20];
      uint32_t *w = w_ + 8, *o = o_ + 8, *d = d_ + 8, *b3 = b3_ + 8;
      {
        const uint32_t am = ub + uoff(upos(2 * j - 2)), a0 = ub + uoff(upos(2 * j));
        const uint2 a = lds64(am + 8);
        const uint4 b = lds128(am ^ 16), c = lds128(a0), e = lds128(a0 ^ 16);
        w[8] = lds32(ub + uoff(upos((2 * j + 2) & 255)));
        w[-6] = a.x; w[-5] = a.y; w[-4] = b.x; w[-3] = b.y; w[-2] = b.z; w[-1] = b.w;
        w[0] = c.x; w[1] = c.y; w[2] = c.z; w[3] = c.w; w[4] = e.x; w[5] = e.y; w[6] = e.z; w[7] = e.w;
      }
#pragma unroll
      for (int i = -1; i <= 7; i++) o[i] = odd_pair(w[i], w[i + 1]);
#pragma unroll
      for (int i = 0; i <= 7; i++) { d[i] = hadd(w[i], o[i]); b3[i] = hadd(d[i], o[i - 1]); }
      if (j < 112) {
        const int gr = j >> 1;
        const uint32_t a1 = zb + ZA1 + 512 + (gr ^ ((gr >> 2) & 1)) * 64 + ((gr >> 1) & 3) * 16 + (j & 1) * 8;
#pragma unroll
        for (int pp = 0; pp < 4; pp++) {
          const uint32_t sel = (pp & 1) ? 0x7632 : 0x5410;
          const int k = pp >> 1;
          sts64(a1 ^ (pp * 16), __byte_perm(w[k - 1], w[k + 1], sel), __byte_perm(w[k + 3], w[k + 5], sel));
          sts64((a1 ^ (pp * 16)) + (ZB1 - ZA1), __byte_perm(b3[k], b3[k + 2], sel), __byte_perm(b3[k + 4], b3[k + 6], sel));
        }
      } else {
        const uint32_t a1 = zb + ZA1 + ((lane ^ 7) & 15) * 16;
        sts128(a1, 0, 0, 0, 0); sts128(a1 + 256, 0, 0, 0, 0); sts128(a1 + ZB1 - ZA1, 0, 0, 0, 0);
        sts128(a1 + ZB1 - ZA1 + 256, 0, 0, 0, j == 127 ? w[8] << 16 : 0u);
      }
      if (qt < 3) {
        uint32_t e_[20], b5_[20];
        uint32_t *e = e_ + 8, *b5 = b5_ + 8;
#pragma unroll
        for (int i = -6; i <= -2; i++) o[i] = odd_pair(w[i], w[i + 1]);
#pragma unroll
        for (int i = -6; i <= -1; i++) d[i] = hadd(w[i], o[i]);
#pragma unroll
        for (int i = -5; i <= -1; i++) b3[i] = hadd(d[i], o[i - 1]);
#pragma unroll
        for (int i = -5; i <= 4; i++) e[i] = hadd(d[i - 1], d[i]);
#pragma unroll
        for (int i = -4; i <= 4; i++) b5[i] = hadd(e[i], w[i + 1]);
        const uint32_t a2 = zb + ((j >> 3) * 16 + (j & 7)) * 16;
        sts128(a2 + ZA2, b3[-2], b3[-1], b3[0], b3[1]);
        sts128(a2 + ZA2 + 128, b3[2], b3[3], b3[4], b3[5]);
        sts128(a2 + ZB2, b5[-4], b5[-3], b5[-2], b5[-1]);
        sts128(a2 + ZB2 + 128, b5[0], b5[1], b5[2], b5[3]);
        if (qt < 2) {
          sts128(a2 + ZS, d[-2], d[-1], d[0], d[1]);
          sts128(a2 + ZS + 128, d[2], d[3], d[4], d[5]);
          uint32_t b7[8], b9[8];
#pragma unroll
          for (int i = -4; i <= 3; i++) { b7[i + 4] = hadd(b3[i - 1], e[i + 1]); b9[i + 4] = hadd(e[i - 1], b5[i + 1]); }
          const uint32_t a3 = zb + ((j >> 4) * 32 + (j & 15)) * 16;
          sts128(a3 + ZA3, b7[0], b7[1], b7[2], b7[3]);
          sts128(a3 + ZA3 + 256, b7[4], b7[5], b7[6], b7[7]);
          sts128(a3 + ZB3 + 256, b9[0], b9[1], b9[2], b9[3]);
          if (j < 63) sts128(a3 + ZB3 + ((j & 15) == 15 ? 272 : 16), b9[4], b9[5], b9[6], b9[7]);
          else sts128(zb + ZB3, 0, 0, 0, 0);
        }
      }
    }
    if (wg == 3) bar_arrive(0, 256);
    bar_sync(wg == 2 ? 14 : 7, 384);
#pragma unroll 1
    for (int ch = wg - 2; ch < 5; ch += 2) {
      const uint32_t ub = sb + OFF_U + ch * 32, zb = sb + OFF_Z + ch * ZSZ, pb = sb + OFF_P + ch * 3072;
      if (ch == 2) bar_sync(0, 256);
      const uint2 chc = lds64(sb + OFF_CHC + ch * 8);
      const uint32_t pa = pb + cpa;
      if (role < 2) {
        float acc[8][4];
#pragma unroll
        for (int r = 0; r < 8; r++) { acc[r][0] = acc[r][1] = acc[r][2] = acc[r][3] = 0.f; }
        float fix = 0.f;
        if (role == 1 && lane == 28) {
          const uint32_t k = lds32(pb + PB1 * 4), u0 = lds32(ub);
          fix = __low2float(*reinterpret_cast<const __half2*>(&k)) * __low2float(*reinterpret_cast<const __half2*>(&u0));
        }
        uint32_t b[12][4], A[17][4];
#pragma unroll
        for (int i = 11; i >= 8; i--) ldsm4(b[i], ub + (co[4 + (i & 1)] ^ (((i >> 1) & 1) * 16)) + ((i >> 1) & 1) * 640);
        A[0][0] = lds32(pa + P0 * 4); A[0][1] = lds32(pa + P0 * 4 + 32); A[0][2] = lds32(sb + OFF_ZERO + 4);
#pragma unroll
        for (int m = 0; m <= 16; m++) {
          if (m < 16) {
            A[m + 1][0] = lds32(pa + P0 * 4 + (2 * m + 2) * 32);
            A[m + 1][1] = m < 15 ? lds32(pa + P0 * 4 + (2 * m + 3) * 32) : lds32(sb + OFF_ZERO + 8);
          }
          if ((m & 1) == 0 && m < 16) {
            const int i = 7 - (m >> 1);
            ldsm4(b[i], ub + (co[2 * (i >> 2) + (i & 1)] ^ (((i >> 1) & 1) * 16)) + ((i >> 1) & 1) * 640);
          }
          A[m][3] = dup(A[m][0], nz);
          if (m < 16) A[m + 1][2] = dup(A[m][1], nz);
#pragma unroll
          for (int r = 7; r >= 0; r--) {
            const int f = 16 + r - m;
            hmma(acc[r], A[m][0], A[m][1], A[m][2], A[m][3], b[f >> 1][(f & 1) * 2], b[f >> 1][(f & 1) * 2 + 1]);
          }
        }
        acc[7][2] += fix;
        bar_sync(7 + wg, 64);
#pragma unroll
        for (int i = 3; i >= 0; i--)
          stsm4t(ub + (co[4 + (i & 1)] ^ (((i >> 1) & 1) * 16)) + ((i >> 1) & 1) * 640, pack_bf(acc[2 * i][0], acc[2 * i][1]), pack_bf(acc[2 * i][2], acc[2 * i][3]),
                 pack_bf(acc[2 * i + 1][0], acc[2 * i + 1][1]), pack_bf(acc[2 * i + 1][2], acc[2 * i + 1][3]));
      } else if (role == 2) {
        float acc[14][4];
#pragma unroll
        for (int r = 0; r < 14; r++) { acc[r][0] = acc[r][1] = acc[r][2] = acc[r][3] = 0.f; }
#pragma unroll
        for (int arr = 0; arr < 2; arr++) {
          uint32_t A[5][4];
#pragma unroll
          for (int m = 0; m < 5; m++) {
            A[m][0] = lds32(pa + (arr ? PB1 : PA1) * 4 + m * 64);
            A[m][1] = m < 4 ? lds32(pa + (arr ? PB1 : PA1) * 4 + m * 64 + 32) : lds32(sb + OFF_ZERO + 4 + arr * 8);
          }
#pragma unroll
          for (int m = 4; m >= 1; m--) { A[m][2] = dup(A[m - 1][1], nz); A[m][3] = dup(A[m][0], nz); }
          A[0][2] = lds32(sb + OFF_ZERO + 8 + arr * 8); A[0][3] = dup(A[0][0], nz);
#pragma unroll
          for (int ip = 0; ip < 9; ip++) {
            uint32_t b[4];
            ldsm4(b, zb + co[ip & 1] + (arr ? ZB1 : ZA1) + ip * 256);
#pragma unroll
            for (int hh = 0; hh < 2; hh++)
#pragma unroll
              for (int m = 0; m < 5; m++) {
                const int i = 2 * ip + hh - 4 + m;
                if (i >= 0 && i < 14) hmma(acc[i], A[m][0], A[m][1], A[m][2], A[m][3], b[2 * hh], b[2 * hh + 1]);
              }
          }
        }
        const uint32_t a = zb + ZA1 + 512 + co[2];
#pragma unroll
        for (int i = 0; i < 7; i++)
          stsm4(a + i * 512, pack_bf(acc[2 * i][0], acc[2 * i][1]), pack_bf(acc[2 * i][2], acc[2 * i][3]),
                pack_bf(acc[2 * i + 1][0], acc[2 * i + 1][1]), pack_bf(acc[2 * i + 1][2], acc[2 * i + 1][3]));
      } else {
        float acc[12][4];
        const uint32_t za = zb + co[3];
        {
          float d[4][2][4];
#pragma unroll
          for (int r = 0; r < 8; r++) { d[r >> 1][r & 1][0] = d[r >> 1][r & 1][1] = d[r >> 1][r & 1][2] = d[r >> 1][r & 1][3] = 0.f; }
#pragma unroll
          for (int arr = 0; arr < 2; arr++) {
            uint32_t A[4][4];
#pragma unroll
            for (int m = 0; m < 4; m++) { A[m][0] = lds32(pa + (arr ? PB3 : PA3) * 4 + m * 64); A[m][1] = lds32(pa + (arr ? PB3 : PA3) * 4 + m * 64 + 32); }
#pragma unroll
            for (int m = 0; m < 4; m++) { A[m][2] = m ? dup(A[m - 1][1], nz) : lds32(sb + OFF_ZERO + 4 + arr * 4); A[m][3] = dup(A[m][0], nz); }
#pragma unroll
            for (int io = 0; io < 4; io++) {
              uint32_t b[4];
              ldsm4t(b, za + (arr ? ZB3 : ZA3) + io * 512);
#pragma unroll
              for (int m = 0; m + io < 4; m++) {
                hmma(d[io + m][0], A[m][0], A[m][1], A[m][2], A[m][3], b[0], b[1]);
                hmma(d[io + m][1], A[m][0], A[m][1], A[m][2], A[m][3], b[2], b[3]);
              }
            }
          }
#pragma unroll
          for (int r = 0; r < 4; r++) {
            acc[r][0] = acc[r][1] = acc[r][2] = acc[r][3] = 0.f;
            acc[4 + 2 * r][0] = d[r][0][0]; acc[4 + 2 * r][1] = d[r][0][1]; acc[4 + 2 * r][2] = d[r][1][0]; acc[4 + 2 * r][3] = d[r][1][1];
            acc[5 + 2 * r][0] = d[r][0][2]; acc[5 + 2 * r][1] = d[r][0][3]; acc[5 + 2 * r][2] = d[r][1][2]; acc[5 + 2 * r][3] = d[r][1][3];
          }
        }
        {
          const uint32_t k0 = chc.y & co[4];
          const uint32_t k1 = lds32(sb + OFF_ZERO + 12), k2 = lds32(sb + OFF_ZERO + 16), k3 = dup(k0, nz);
#pragma unroll
          for (int ip = 0; ip < 4; ip++) {
            uint32_t b[4];
            ldsm4t(b, za + ZS + ip * 512);
            hmma(acc[4 + 2 * ip], k0, k1, k2, k3, b[0], b[1]);
            hmma(acc[5 + 2 * ip], k0, k1, k2, k3, b[2], b[3]);
          }
        }
        const uint32_t pa2 = pb + co[5];
#pragma unroll
        for (int arr = 0; arr < 2; arr++) {
          uint32_t A[5][4];
#pragma unroll
          for (int m = 0; m < 5; m++) {
            const uint2 v = lds64(pa2 + (arr ? PB2 : PA2) * 4 + m * 64);
            A[m][0] = v.x; A[m][1] = v.y; A[m][2] = lds32(pa2 + (arr ? PB2 : PA2) * 4 + m * 64 - 4);
          }
#pragma unroll
          for (int m = 0; m < 5; m++) A[m][3] = dup(A[m][0], nz);
#pragma unroll
          for (int ip = 0; ip < 6; ip++) {
            uint32_t b[4];
            ldsm4t(b, za + (arr ? ZB2 : ZA2) + ip * 512);
#pragma unroll
            for (int hh = 0; hh < 2; hh++)
#pragma unroll
              for (int m = 0; m < 5; m++) {
                const int i = 2 * ip + hh + m;
                if (i < 12) hmma(acc[i], A[m][0], A[m][1], A[m][2], A[m][3], b[2 * hh], b[2 * hh + 1]);
              }
          }
        }
        const uint32_t a = zb + ZA2 + co[2];
#pragma unroll
        for (int i = 0; i < 6; i++)
          stsm4(a + i * 512, pack_bf(acc[2 * i][0], acc[2 * i][1]), pack_bf(acc[2 * i][2], acc[2 * i][3]),
                pack_bf(acc[2 * i + 1][0], acc[2 * i + 1][1]), pack_bf(acc[2 * i + 1][2], acc[2 * i + 1][3]));
      }
      if (ch >= 3) bar_arrive(8, 512);
      bar_sync(3 + wg, 128);
      {
        const int row = (wid & 15) * 5 + ch;
        const uint4 v0 = lds128(ub + cb[0]), u0 = lds128(ub + cb[1]);
        const uint4 y0 = lds128(zb + cb[2]), y1 = lds128(zb + (cb[2] ^ 16));
        const uint4 v2 = lds128(zb + cb[3]), u2 = lds128(zb + cb[4]);
        uint4* dst = p.scr->sT + ((wid >> 4) * 16 * 80 + row) * 16;
        const uint4 v = make_uint4(bmul(badd(badd(y0.x, v2.x), v0.x), chc.x), bmul(badd(badd(y0.y, v2.y), v0.y), chc.x),
                                   bmul(badd(badd(y1.x, v2.z), v0.z), chc.x), bmul(badd(badd(y1.y, v2.w), v0.w), chc.x));
        const uint4 u = make_uint4(bmul(badd(badd(y0.z, u2.x), u0.x), chc.x), bmul(badd(badd(y0.w, u2.y), u0.y), chc.x),
                                   bmul(badd(badd(y1.z, u2.z), u0.z), chc.x), bmul(badd(badd(y1.w, u2.w), u0.w), chc.x));
        fence_async_smem();
        dst[cg0 ^ (row & 7)] = v;
        dst[cg1 ^ (row & 7)] = u;
      }
      __syncwarp();
      if (lane == 0) mbar_arrive(bar + 8 * (B_FREE + ch));
    }
    if (warp == 12) {
      if (elect1()) {
        const uint4* srcA = p.scr->h + (rg1 * 24 + NS2 - 1) * 1024;
        const uint4* srcB = p.scr->w2p + (j1 * 24 + NS2 - 1) * 640;
        uint32_t d = sb + (NS2 - 1) * SLOT2;
        mbar_wait(bar + 8 * (B_FULL2 + 3), 0);
        asm volatile("fence.proxy.async.global;" ::: "memory");
        mbar_wait(bar + 8 * (B_FREE + 3), 0);
        mbar_wait(bar + 8 * (B_FREE + 4), 0);
#pragma unroll 1
        for (int s = NS2 - 1; s < 24; s++) {
          mbar_wait(bar + 8 * (B_REL2 + s - NS2 + 1), 0);
          const uint32_t mb = bar + 8 * (B_FULL2 + s);
          mbar_expect(mb, SLOT2);
          bulk_g2s(d, srcA, 16384, mb);
          bulk_g2s(d + 16384, srcB, 10240, mb);
          srcA += 1024; srcB += 640;
          d = d == sb + (NS2 - 1) * SLOT2 ? sb : d + SLOT2;
        }
      }
      __syncwarp();
    } else if (warp == 13) {
      if (elect1()) {
        mbar_wait(bar + 8 * (B_FREE + 3), 0);
        mbar_wait(bar + 8 * (B_FREE + 4), 0);
        publish(cnt + (C_S + (wid >> 4)) * 32);
        mbar_expect(bar + 8 * B_SFULL, 20480);
        poll_cnt(cnt + (C_S + j1) * 32, ep * 16);
        mbar_wait(bar + 8 * (B_REL2 + 24 - NS2), 0);
        bulk_g2s(sb + OFF_U, p.scr->sT + (j1 * 16 + rg1) * 1280, 20480, bar + 8 * B_SFULL);
      }
      __syncwarp();
    }
  }
}

typedef CUresult (*EncodeFn)(CUtensorMap*, CUtensorMapDataType, cuuint32_t, void*, const cuuint64_t*, const cuuint64_t*,
                             const cuuint32_t*, const cuuint32_t*, CUtensorMapInterleave, CUtensorMapSwizzle,
                             CUtensorMapL2promotion, CUtensorMapFloatOOBfill);

}

extern "C" void kernel_launch(void* const* d_in, const int* in_sizes, int n_in, void* d_out, int out_size) {
  static EncodeFn enc = nullptr;
  static int nsm = 0;
  static void* scr = nullptr;
  if (!enc) {
    void* fn = nullptr;
    cudaDriverEntryPointQueryResult qr;
    cudaGetDriverEntryPoint("cuTensorMapEncodeTiled", &fn, cudaEnableDefault, &qr);
    enc = (EncodeFn)fn;
    int dev = 0;
    cudaGetDevice(&dev);
    cudaDeviceGetAttribute(&nsm, cudaDevAttrMultiProcessorCount, dev);
    cudaFuncSetAttribute(fused_s4_ffn_kernel<true>, cudaFuncAttributeMaxDynamicSharedMemorySize, SMEM_BYTES);
    cudaFuncSetAttribute(fused_s4_ffn_kernel<false>, cudaFuncAttributeMaxDynamicSharedMemorySize, SMEM_BYTES);
    cudaGetSymbolAddress(&scr, g_scr);
  }
  Params p;
  p.x = (const __nv_bfloat16*)d_in[0];
  p.are = (const __nv_bfloat16*)d_in[1]; p.aim = (const __nv_bfloat16*)d_in[2];
  p.bre = (const __nv_bfloat16*)d_in[3]; p.bim = (const __nv_bfloat16*)d_in[4];
  p.cre = (const __nv_bfloat16*)d_in[5]; p.cim = (const __nv_bfloat16*)d_in[6];
  p.logdt = (const __nv_bfloat16*)d_in[7]; p.dskip = (const __nv_bfloat16*)d_in[8];
  p.w1 = (const __nv_bfloat16*)d_in[10]; p.w2 = (const __nv_bfloat16*)d_in[11];
  p.out = (__nv_bfloat16*)d_out;
  p.scr = (Scratch*)scr;
  CUtensorMap tmX, tmW1, tmU, tmW2;
  const cuuint32_t es[5] = {1, 1, 1, 1, 1};
  {
    const cuuint64_t gd[5] = {DM, 2, 4, 4, FF / 32}, gs[4] = {DM * 2, DM * 16, DM * 4, DM * 64};
    const cuuint32_t bx[5] = {88, 2, 4, 4, 3};
    enc(&tmW2, CU_TENSOR_MAP_DATA_TYPE_BFLOAT16, 5, d_in[11], gd, gs, bx, es, CU_TENSOR_MAP_INTERLEAVE_NONE,
        CU_TENSOR_MAP_SWIZZLE_NONE, CU_TENSOR_MAP_L2_PROMOTION_NONE, CU_TENSOR_MAP_FLOAT_OOB_FILL_NONE);
  }
  {
    const cuuint64_t gd[2] = {16 * DM, 128}, gs[1] = {DM * 32};
    const cuuint32_t bx[2] = {80, 144};
    enc(&tmU, CU_TENSOR_MAP_DATA_TYPE_FLOAT16, 2, p.scr->uT, gd, gs, bx, es, CU_TENSOR_MAP_INTERLEAVE_NONE,
        CU_TENSOR_MAP_SWIZZLE_NONE, CU_TENSOR_MAP_L2_PROMOTION_NONE, CU_TENSOR_MAP_FLOAT_OOB_FILL_NONE);
  }
  {
    const cuuint64_t gd[2] = {DM, SEQ}, gs[1] = {DM * 2};
    const cuuint32_t bx[2] = {64, 128};
    enc(&tmX, CU_TENSOR_MAP_DATA_TYPE_BFLOAT16, 2, d_in[0], gd, gs, bx, es, CU_TENSOR_MAP_INTERLEAVE_NONE,
        CU_TENSOR_MAP_SWIZZLE_128B, CU_TENSOR_MAP_L2_PROMOTION_L2_128B, CU_TENSOR_MAP_FLOAT_OOB_FILL_NONE);
  }
  {
    const cuuint64_t gd[3] = {64, DM, FF / 64}, gs[2] = {FF * 2, 128};
    const cuuint32_t bx[3] = {64, 64, 3};
    enc(&tmW1, CU_TENSOR_MAP_DATA_TYPE_BFLOAT16, 3, d_in[10], gd, gs, bx, es, CU_TENSOR_MAP_INTERLEAVE_NONE,
        CU_TENSOR_MAP_SWIZZLE_128B, CU_TENSOR_MAP_L2_PROMOTION_L2_128B, CU_TENSOR_MAP_FLOAT_OOB_FILL_NONE);
  }
  if (nsm == 132) fused_s4_ffn_kernel<true><<<132, 512, SMEM_BYTES>>>(p, tmX, tmW1, tmU, tmW2);
  else fused_s4_ffn_kernel<false><<<132, 512, SMEM_BYTES>>>(p, tmX, tmW1, tmU, tmW2);
}
```

```cpp
#include <cuda_runtime.h>
#include <cuda_bf16.h>
#include <cuda_fp16.h>
#include <cuda.h>
#include <stdint.h>

namespace {

constexpr int SEQ = 2048, DM = 640, FF = 1536;

constexpr int SLOT1 = 40960;
constexpr int SLOT2 = 26624;
constexpr int NS2 = 7;
#define DELAY_NS 200
#define PACE_NS 30
constexpr int OFF_Z = 85504, ZSZ = 20480;
constexpr int ZA3 = 0, ZB3 = 2048, ZS = 4096, ZA2 = 6144, ZB2 = 9216, ZA1 = 12288, ZB1 = 16384;
constexpr int OFF_W2S = OFF_Z + 4 * ZSZ;
constexpr int OFF_U = 190464;
constexpr int OFF_P = 210944;
constexpr int OFF_KS = 163840;
constexpr int OFF_LNP = 225280;
constexpr int OFF_MISC = 226304;
constexpr int OFF_CHC = OFF_MISC + 16;
constexpr int OFF_EP = OFF_MISC + 64;
constexpr int OFF_ZERO = OFF_MISC + 128;
constexpr int OFF_STAT = OFF_MISC + 1024;
constexpr int OFF_CS = OFF_MISC + 2048;
constexpr int OFF_BAR = OFF_MISC + 2816;
constexpr int SMEM_BYTES = OFF_MISC + 6144;
constexpr int P0 = 8, PA1 = 280, PB1 = 360, PA2 = 448, PB2 = 544, PA3 = 632, PB3 = 704;
enum { B_FULL1 = 0, B_FULL2 = 10, B_UFULL = 34, B_EPI = 35, B_SFULL = 36, B_W2 = 37,
       B_PAIR = 42,
       B_FREE = 48, B_PART = 54,
       B_REL1 = 60, B_REL2 = 70 };
enum { C_LN = 0, C_CS = 1, C_H0 = 2, C_H1 = 18, C_S = 34, C_W2 = 42, C_NUM = 43 };

struct Scratch {
  unsigned cnt[64 * 32];
  unsigned epoch[256];
  float2 stats[SEQ];
  float cs[FF];
  uint4 uT[DM * 256];
  uint4 w2p[8 * 24 * 640];
  uint4 sT[8 * 16 * 1280];
  uint4 h[16 * 24 * 1024];
};
__device__ __align__(1024) Scratch g_scr;
constexpr uint32_t sb = 1024;
constexpr uint32_t bar = sb + OFF_BAR;

struct Params {
  const __nv_bfloat16 *are, *aim, *bre, *bim, *cre, *cim, *logdt, *dskip, *x, *w1, *w2;
  __nv_bfloat16* out;
  Scratch* scr;
};

__device__ __forceinline__ void mbar_init(uint32_t a, int c) { asm volatile("mbarrier.init.shared::cta.b64 [%0], %1;" ::"r"(a), "r"(c)); }
__device__ __forceinline__ void mbar_expect(uint32_t a, int b) { asm volatile("mbarrier.arrive.expect_tx.shared::cta.b64 _, [%0], %1;" ::"r"(a), "r"(b) : "memory"); }
__device__ __forceinline__ void mbar_arrive(uint32_t a) { asm volatile("mbarrier.arrive.shared::cta.b64 _, [%0];" ::"r"(a) : "memory"); }
__device__ __forceinline__ void mbar_wait(uint32_t a, int ph) {
  asm volatile(
      "{\n.reg .pred p;\n.reg .u32 n;\n"
      "mbarrier.try_wait.parity.shared::cta.b64 p, [%0], %1;\n@p bra LD;\nmov.u32 n, 0;\n"
      "LW:\nmbarrier.try_wait.parity.shared::cta.b64 p, [%0], %1, 20000;\n@p bra LD;\n"
      "add.u32 n, n, 1;\nsetp.lt.u32 p, n, 100000;\n@p bra LW;\ntrap;\nLD:\n}\n" ::"r"(a), "r"(ph) : "memory");
}
__device__ __forceinline__ void poll_cnt(const unsigned* p, unsigned target) {
  asm volatile(
      "{\n.reg .pred p;\n.reg .u32 n;\n.reg .s32 v;\nmov.u32 n, 0;\n"
      "LW:\nld.relaxed.gpu.global.u32 v, [%0];\nsub.s32 v, v, %1;\nsetp.ge.s32 p, v, 0;\n@p bra LD;\n"
      "nanosleep.u32 64;\nadd.u32 n, n, 1;\nsetp.lt.u32 p, n, 4000000;\n@p bra LW;\ntrap;\n"
      "LD:\nfence.acquire.gpu;\nfence.proxy.async.global;\n}\n" ::"l"(p), "r"(target) : "memory");
}
__device__ __forceinline__ void publish(unsigned* p) {
  asm volatile("fence.proxy.async.global;\nfence.release.gpu;\nred.relaxed.gpu.global.add.u32 [%0], 1;" ::"l"(p) : "memory");
}
__device__ __forceinline__ uint32_t movm(uint32_t v) { uint32_t r; asm volatile("movmatrix.sync.aligned.m8n8.trans.b16 %0, %1;" : "=r"(r) : "r"(v)); return r; }
__device__ __forceinline__ void fence_async_smem() { asm volatile("fence.proxy.async.shared::cta;" ::: "memory"); }
__device__ __forceinline__ bool elect1() { uint32_t p; asm volatile("{\n.reg .pred P;\nelect.sync _|P, 0xffffffff;\nselp.u32 %0,1,0,P;\n}\n" : "=r"(p)); return p; }
__device__ __forceinline__ void bar_sync(int id, int n) { asm volatile("bar.sync %0, %1;" ::"r"(id), "r"(n) : "memory"); }
__device__ __forceinline__ void bar_arrive(int id, int n) { asm volatile("bar.arrive %0, %1;" ::"r"(id), "r"(n) : "memory"); }
__device__ __forceinline__ void bulk_g2s(uint32_t dst, const void* src, int bytes, uint32_t mb) {
  asm volatile("cp.async.bulk.shared::cluster.global.mbarrier::complete_tx::bytes [%0], [%1], %2, [%3];" ::"r"(dst), "l"(src), "r"(bytes), "r"(mb) : "memory");
}
__device__ __forceinline__ void bulk_prefetch(const void* src, int bytes) { asm volatile("cp.async.bulk.prefetch.L2.global [%0], %1;" ::"l"(src), "r"(bytes) : "memory"); }
__device__ __forceinline__ void tma2d(uint32_t dst, const CUtensorMap* m, int c0, int c1, uint32_t mb) {
  asm volatile("cp.async.bulk.tensor.2d.shared::cluster.global.mbarrier::complete_tx::bytes [%0], [%1, {%3, %4}], [%2];" ::"r"(dst), "l"(m), "r"(mb), "r"(c0), "r"(c1) : "memory");
}
__device__ __forceinline__ void tma3d(uint32_t dst, const CUtensorMap* m, int c0, int c1, int c2, uint32_t mb) {
  asm volatile("cp.async.bulk.tensor.3d.shared::cluster.global.mbarrier::complete_tx::bytes [%0], [%1, {%3, %4, %5}], [%2];" ::"r"(dst), "l"(m), "r"(mb), "r"(c0), "r"(c1), "r"(c2) : "memory");
}
__device__ __forceinline__ int frag_col(int l) {
  const int tl = l >> 3, i = l & 7;
  return (tl < 8 ? 32 * (tl >> 2) + 8 * (i >> 1) + 2 * (tl & 3) : 48 + 4 * (i >> 1) + 2 * tl) + (i & 1);
}
__device__ __forceinline__ void tma5d(uint32_t dst, const CUtensorMap* m, int c0, int c4, uint32_t mb) {
  asm volatile("cp.async.bulk.tensor.5d.shared::cluster.global.mbarrier::complete_tx::bytes [%0], [%1, {%3, %5, %5, %5, %4}], [%2];" ::"r"(dst), "l"(m), "r"(mb), "r"(c0), "r"(c4), "r"(0) : "memory");
}
__device__ __forceinline__ uint64_t dsc(uint32_t lo, uint32_t hi) { return ((uint64_t)hi << 32) | lo; }
__device__ __forceinline__ void wg_fence() { asm volatile("wgmma.fence.sync.aligned;" ::: "memory"); }
__device__ __forceinline__ void wg_commit() { asm volatile("wgmma.commit_group.sync.aligned;" ::: "memory"); }
template <int N> __device__ __forceinline__ void wg_wait() { asm volatile("wgmma.wait_group.sync.aligned %0;" ::"n"(N) : "memory"); }
__device__ __forceinline__ void wgmma_n192(float (&d)[96], uint64_t da, uint64_t db, int scale_d) {
  asm volatile("{\n.reg .pred p;\nsetp.ne.b32 p, %98, 0;\n"
    "wgmma.mma_async.sync.aligned.m64n192k16.f32.bf16.bf16 "
    "{"
    "%0, %1, %2, %3, %4, %5, %6, %7, %8, %9, %10, %11, %12, %13, %14, %15, "
    "%16, %17, %18, %19, %20, %21, %22, %23, %24, %25, %26, %27, %28, %29, %30, %31, "
    "%32, %33, %34, %35, %36, %37, %38, %39, %40, %41, %42, %43, %44, %45, %46, %47, "
    "%48, %49, %50, %51, %52, %53, %54, %55, %56, %57, %58, %59, %60, %61, %62, %63, "
    "%64, %65, %66, %67, %68, %69, %70, %71, %72, %73, %74, %75, %76, %77, %78, %79, "
    "%80, %81, %82, %83, %84, %85, %86, %87, %88, %89, %90, %91, %92, %93, %94, %95"
    "}, "
    "%96, %97, p, 1, 1, 0, 1;\n}\n"
    : "+f"(d[0]), "+f"(d[1]), "+f"(d[2]), "+f"(d[3]), "+f"(d[4]), "+f"(d[5]), "+f"(d[6]), "+f"(d[7]),
      "+f"(d[8]), "+f"(d[9]), "+f"(d[10]), "+f"(d[11]), "+f"(d[12]), "+f"(d[13]), "+f"(d[14]), "+f"(d[15]),
      "+f"(d[16]), "+f"(d[17]), "+f"(d[18]), "+f"(d[19]), "+f"(d[20]), "+f"(d[21]), "+f"(d[22]), "+f"(d[23]),
      "+f"(d[24]), "+f"(d[25]), "+f"(d[26]), "+f"(d[27]), "+f"(d[28]), "+f"(d[29]), "+f"(d[30]), "+f"(d[31]),
      "+f"(d[32]), "+f"(d[33]), "+f"(d[34]), "+f"(d[35]), "+f"(d[36]), "+f"(d[37]), "+f"(d[38]), "+f"(d[39]),
      "+f"(d[40]), "+f"(d[41]), "+f"(d[42]), "+f"(d[43]), "+f"(d[44]), "+f"(d[45]), "+f"(d[46]), "+f"(d[47]),
      "+f"(d[48]), "+f"(d[49]), "+f"(d[50]), "+f"(d[51]), "+f"(d[52]), "+f"(d[53]), "+f"(d[54]), "+f"(d[55]),
      "+f"(d[56]), "+f"(d[57]), "+f"(d[58]), "+f"(d[59]), "+f"(d[60]), "+f"(d[61]), "+f"(d[62]), "+f"(d[63]),
      "+f"(d[64]), "+f"(d[65]), "+f"(d[66]), "+f"(d[67]), "+f"(d[68]), "+f"(d[69]), "+f"(d[70]), "+f"(d[71]),
      "+f"(d[72]), "+f"(d[73]), "+f"(d[74]), "+f"(d[75]), "+f"(d[76]), "+f"(d[77]), "+f"(d[78]), "+f"(d[79]),
      "+f"(d[80]), "+f"(d[81]), "+f"(d[82]), "+f"(d[83]), "+f"(d[84]), "+f"(d[85]), "+f"(d[86]), "+f"(d[87]),
      "+f"(d[88]), "+f"(d[89]), "+f"(d[90]), "+f"(d[91]), "+f"(d[92]), "+f"(d[93]), "+f"(d[94]), "+f"(d[95])
    : "l"(da), "l"(db), "r"(scale_d));
}

__device__ __forceinline__ void wgmma_n80(float (&d)[40], uint64_t da, uint64_t db, int scale_d) {
  asm volatile("{\n.reg .pred p;\nsetp.ne.b32 p, %42, 0;\n"
    "wgmma.mma_async.sync.aligned.m64n80k16.f32.bf16.bf16 "
    "{"
    "%0, %1, %2, %3, %4, %5, %6, %7, %8, %9, %10, %11, %12, %13, %14, %15, "
    "%16, %17, %18, %19, %20, %21, %22, %23, %24, %25, %26, %27, %28, %29, %30, %31, "
    "%32, %33, %34, %35, %36, %37, %38, %39"
    "}, "
    "%40, %41, p, 1, 1, 0, 1;\n}\n"
    : "+f"(d[0]), "+f"(d[1]), "+f"(d[2]), "+f"(d[3]), "+f"(d[4]), "+f"(d[5]), "+f"(d[6]), "+f"(d[7]),
      "+f"(d[8]), "+f"(d[9]), "+f"(d[10]), "+f"(d[11]), "+f"(d[12]), "+f"(d[13]), "+f"(d[14]), "+f"(d[15]),
      "+f"(d[16]), "+f"(d[17]), "+f"(d[18]), "+f"(d[19]), "+f"(d[20]), "+f"(d[21]), "+f"(d[22]), "+f"(d[23]),
      "+f"(d[24]), "+f"(d[25]), "+f"(d[26]), "+f"(d[27]), "+f"(d[28]), "+f"(d[29]), "+f"(d[30]), "+f"(d[31]),
      "+f"(d[32]), "+f"(d[33]), "+f"(d[34]), "+f"(d[35]), "+f"(d[36]), "+f"(d[37]), "+f"(d[38]), "+f"(d[39])
    : "l"(da), "l"(db), "r"(scale_d));
}

__device__ __forceinline__ void hmma(float* c, uint32_t a0, uint32_t a1, uint32_t a2, uint32_t a3, uint32_t b0, uint32_t b1) {
  asm volatile("mma.sync.aligned.m16n8k16.row.col.f32.f16.f16.f32 {%0,%1,%2,%3}, {%4,%5,%6,%7}, {%8,%9}, {%0,%1,%2,%3};"
      : "+f"(c[0]), "+f"(c[1]), "+f"(c[2]), "+f"(c[3]) : "r"(a0), "r"(a1), "r"(a2), "r"(a3), "r"(b0), "r"(b1));
}
__device__ __forceinline__ void ldsm4(uint32_t* r, uint32_t a) { asm volatile("ldmatrix.sync.aligned.m8n8.x4.shared.b16 {%0,%1,%2,%3}, [%4];" : "=r"(r[0]), "=r"(r[1]), "=r"(r[2]), "=r"(r[3]) : "r"(a) : "memory"); }
__device__ __forceinline__ void ldsm4t(uint32_t* r, uint32_t a) { asm volatile("ldmatrix.sync.aligned.m8n8.x4.trans.shared.b16 {%0,%1,%2,%3}, [%4];" : "=r"(r[0]), "=r"(r[1]), "=r"(r[2]), "=r"(r[3]) : "r"(a) : "memory"); }
__device__ __forceinline__ void stsm4(uint32_t a, uint32_t r0, uint32_t r1, uint32_t r2, uint32_t r3) { asm volatile("stmatrix.sync.aligned.m8n8.x4.shared.b16 [%0], {%1,%2,%3,%4};" ::"r"(a), "r"(r0), "r"(r1), "r"(r2), "r"(r3) : "memory"); }
__device__ __forceinline__ void stsm4t(uint32_t a, uint32_t r0, uint32_t r1, uint32_t r2, uint32_t r3) { asm volatile("stmatrix.sync.aligned.m8n8.x4.trans.shared.b16 [%0], {%1,%2,%3,%4};" ::"r"(a), "r"(r0), "r"(r1), "r"(r2), "r"(r3) : "memory"); }
__device__ __forceinline__ uint32_t lds32(uint32_t a) { uint32_t v; asm volatile("ld.shared.u32 %0, [%1];" : "=r"(v) : "r"(a) : "memory"); return v; }
__device__ __forceinline__ uint2 lds64(uint32_t a) { uint2 v; asm volatile("ld.shared.v2.u32 {%0,%1}, [%2];" : "=r"(v.x), "=r"(v.y) : "r"(a) : "memory"); return v; }
__device__ __forceinline__ uint4 lds128(uint32_t a) { uint4 v; asm volatile("ld.shared.v4.u32 {%0,%1,%2,%3}, [%4];" : "=r"(v.x), "=r"(v.y), "=r"(v.z), "=r"(v.w) : "r"(a) : "memory"); return v; }
__device__ __forceinline__ void sts16(uint32_t a, uint32_t v) { asm volatile("st.shared.u16 [%0], %1;" ::"r"(a), "h"((unsigned short)v) : "memory"); }
__device__ __forceinline__ void sts32(uint32_t a, uint32_t v) { asm volatile("st.shared.u32 [%0], %1;" ::"r"(a), "r"(v) : "memory"); }
__device__ __forceinline__ void sts64(uint32_t a, uint32_t x, uint32_t y) { asm volatile("st.shared.v2.u32 [%0], {%1,%2};" ::"r"(a), "r"(x), "r"(y) : "memory"); }
__device__ __forceinline__ void sts128(uint32_t a, uint32_t x, uint32_t y, uint32_t z, uint32_t w) { asm volatile("st.shared.v4.u32 [%0], {%1,%2,%3,%4};" ::"r"(a), "r"(x), "r"(y), "r"(z), "r"(w) : "memory"); }
__device__ __forceinline__ float bflo(uint32_t v) { return __uint_as_float(v << 16); }
__device__ __forceinline__ float bfhi(uint32_t v) { return __uint_as_float(v & 0xffff0000u); }
__device__ __forceinline__ uint32_t pack_bf(float lo, float hi) { uint32_t r; asm("cvt.rn.bf16x2.f32 %0, %1, %2;" : "=r"(r) : "f"(hi), "f"(lo)); return r; }
__device__ __forceinline__ uint32_t pack_h(float lo, float hi) { uint32_t r; asm("cvt.rn.f16x2.f32 %0, %1, %2;" : "=r"(r) : "f"(hi), "f"(lo)); return r; }
__device__ __forceinline__ float rnd_bf(float v) { return __bfloat162float(__float2bfloat16_rn(v)); }
__device__ __forceinline__ float ex2a(float v) { float r; asm("ex2.approx.ftz.f32 %0, %1;" : "=f"(r) : "f"(v)); return r; }
__device__ __forceinline__ float tanha(float v) { float r; asm("tanh.approx.f32 %0, %1;" : "=f"(r) : "f"(v)); return r; }
__device__ __forceinline__ uint32_t hadd(uint32_t a, uint32_t b) { uint32_t r; asm("add.rn.f16x2 %0, %1, %2;" : "=r"(r) : "r"(a), "r"(b)); return r; }
__device__ __forceinline__ uint32_t badd(uint32_t a, uint32_t b) { uint32_t r; asm("add.rn.bf16x2 %0, %1, %2;" : "=r"(r) : "r"(a), "r"(b)); return r; }
__device__ __forceinline__ uint32_t bmul(uint32_t a, uint32_t b) { uint32_t r; asm("mul.rn.bf16x2 %0, %1, %2;" : "=r"(r) : "r"(a), "r"(b)); return r; }
__device__ __forceinline__ uint32_t bsub(uint32_t a, uint32_t b) { uint32_t r; asm("sub.rn.bf16x2 %0, %1, %2;" : "=r"(r) : "r"(a), "r"(b)); return r; }
__device__ __forceinline__ uint32_t dup(uint32_t v, uint32_t nz) { uint32_t r; asm volatile("add.rn.f32 %0, %1, %2;" : "=r"(r) : "r"(v), "r"(nz)); return r; }
__device__ __forceinline__ void bmma(float* c, uint32_t a0, uint32_t a1, uint32_t a2, uint32_t a3, uint32_t b0, uint32_t b1) {
  asm("mma.sync.aligned.m16n8k16.row.col.f32.bf16.bf16.f32 {%0,%1,%2,%3}, {%4,%5,%6,%7}, {%8,%9}, {%0,%1,%2,%3};"
      : "+f"(c[0]), "+f"(c[1]), "+f"(c[2]), "+f"(c[3]) : "r"(a0), "r"(a1), "r"(a2), "r"(a3), "r"(b0), "r"(b1));
}
__device__ __forceinline__ uint32_t odd_pair(uint32_t a, uint32_t b) { return __byte_perm(a, b, 0x5432); }
__device__ __forceinline__ int upos(int c) { return c ^ ((c >> 5) & 7) ^ ((c >> 3) & 1); }
__device__ __forceinline__ int uoff(int pos) { return (pos >> 1) * 160 + (pos & 1) * 16; }

struct cf { float r, i; };
__device__ __forceinline__ cf cmul(cf a, cf b) { cf o; o.r = fmaf(a.r, b.r, -a.i * b.i); o.i = fmaf(a.r, b.i, a.i * b.r); return o; }
__device__ __forceinline__ cf cmulj(cf a, cf b) { cf o; o.r = fmaf(a.r, b.r, a.i * b.i); o.i = fmaf(a.i, b.r, -a.r * b.i); return o; }
__device__ __forceinline__ cf csq(cf a) { cf o; o.r = fmaf(a.r, a.r, -a.i * a.i); o.i = (a.r + a.r) * a.i; return o; }
struct hp { uint32_t r, i; };
__device__ __forceinline__ hp hpack(cf a, cf b) { hp o; o.r = pack_h(a.r, b.r); o.i = pack_h(a.i, b.i); return o; }
__device__ __forceinline__ hp hmulc(hp a, uint32_t c) {
  __half2 ar = *reinterpret_cast<__half2*>(&a.r), ai = *reinterpret_cast<__half2*>(&a.i), cc = *reinterpret_cast<__half2*>(&c);
  __half2 orr = __hfma2(ar, __low2half2(cc), __hneg2(__hmul2(ai, __high2half2(cc))));
  __half2 oi = __hfma2(ar, __high2half2(cc), __hmul2(ai, __low2half2(cc)));
  hp o; o.r = *reinterpret_cast<uint32_t*>(&orr); o.i = *reinterpret_cast<uint32_t*>(&oi); return o;
}
__device__ __forceinline__ hp hmulj(hp a, uint32_t c) {
  __half2 ar = *reinterpret_cast<__half2*>(&a.r), ai = *reinterpret_cast<__half2*>(&a.i), cc = *reinterpret_cast<__half2*>(&c);
  __half2 orr = __hfma2(ar, __low2half2(cc), __hmul2(ai, __high2half2(cc)));
  __half2 oi = __hfma2(ai, __low2half2(cc), __hneg2(__hmul2(ar, __high2half2(cc))));
  hp o; o.r = *reinterpret_cast<uint32_t*>(&orr); o.i = *reinterpret_cast<uint32_t*>(&oi); return o;
}
__device__ __forceinline__ void sts_tile(uint32_t a, const hp* t) {
  sts128(a, t[0].r, t[1].r, t[2].r, t[3].r);
  sts128(a + 512, t[0].i, t[1].i, t[2].i, t[3].i);
}
template <int STEP> __device__ __forceinline__ void put2(uint32_t a0, uint32_t a1, uint32_t h, uint32_t sel) {
  const uint32_t x = __byte_perm(h, h, sel), y = x >> 16;
  sts16(a0, x); sts16(a0 + STEP * 4 + 2, x);
  sts16(a1, y); sts16(a1 + STEP * 4 + 2, y);
}

__device__ __forceinline__ void spare_work(const Params& p, const CUtensorMap* tmW1, int k, int tid) {
  const int lane = tid & 31;
  unsigned ep = 0;
  if (tid >= 480) ep = p.scr->epoch[128 + k] + 1;
  if (tid == 480) {
    for (int i = 0; i < 8; i++) mbar_init(bar + 8 * i, i < 4 ? 1 : 12);
    asm volatile("fence.mbarrier_init.release.cluster;" ::: "memory");
    fence_async_smem();
  }
  __syncthreads();
  float a[2][4] = {{0.f, 0.f, 0.f, 0.f}, {0.f, 0.f, 0.f, 0.f}};
  if (tid >= 480) {
    if (elect1()) {
#pragma unroll 1
      for (int s = 0; s < 10; s++) {
        mbar_wait(bar + 8 * (4 + (s & 3)), ((s >> 2) & 1) ^ 1);
        mbar_expect(bar + 8 * (s & 3), 49152);
#pragma unroll 1
        for (int b = 0; b < 2; b++) tma3d(sb + (s & 3) * 49152 + b * 24576, tmW1, 0, s * 64, k * 6 + b * 3, bar + 8 * (s & 3));
      }
    }
    __syncwarp();
  } else if (tid < 384) {
    const uint32_t idn = (lane >> 3) == (lane & 3) ? ((lane & 4) ? 0x3f800000u : 0x3f80u) : 0u;
#pragma unroll 1
    for (int s = 0; s < 10; s++) {
      mbar_wait(bar + 8 * (s & 3), (s >> 2) & 1);
      const uint32_t ad = sb + (s & 3) * 49152 + (tid >> 6) * 8192 + (tid & 63) * 16;
#pragma unroll
      for (int i = 0; i < 8; i += 2) {
        const uint4 v = lds128(ad + i * 1024), w = lds128(ad + i * 1024 + 1024);
        bmma(a[0], v.x, v.y, w.x, w.y, idn, idn);
        bmma(a[1], v.z, v.w, w.z, w.w, idn, idn);
      }
      __syncwarp();
      if (lane == 0) mbar_arrive(bar + 8 * (4 + (s & 3)));
    }
    const int rho = (tid >> 3) & 7;
    const uint32_t ad = sb + 196608 + rho * 1536 + ((tid >> 6) * 8 + ((tid & 7) ^ rho)) * 32;
    sts128(ad, __float_as_uint(a[0][0]), __float_as_uint(a[0][1]), __float_as_uint(a[0][2]), __float_as_uint(a[0][3]));
    sts128(ad + 16, __float_as_uint(a[1][0]), __float_as_uint(a[1][1]), __float_as_uint(a[1][2]), __float_as_uint(a[1][3]));
  }
  __syncthreads();
  if (tid < 384) {
    float s = 0.f;
#pragma unroll
    for (int r = 0; r < 8; r++) s += __uint_as_float(lds32(sb + 196608 + r * 1536 + tid * 4));
    p.scr->cs[k * 384 + tid] = s;
  }
  __syncthreads();
  if (tid == 480) {
    publish(p.scr->cnt + C_CS * 32);
    p.scr->epoch[128 + k] = ep;
    poll_cnt(p.scr->cnt + C_LN * 32, ep * 128);
  }
}

__device__ __forceinline__ void load1(int s, const CUtensorMap* tmX, const CUtensorMap* tmW1, int rg1, int j1) {
  const uint32_t d = sb + (s & 3) * SLOT1, mb = bar + 8 * (B_FULL1 + s);
  mbar_expect(mb, SLOT1);
  tma2d(d, tmX, s * 64, rg1 * 128, mb);
  tma3d(d + 16384, tmW1, 0, s * 64, j1 * 3, mb);
}
__device__ __forceinline__ void load_x(uint32_t (&xv)[2][10], const __nv_bfloat16* xc, int rstep, int q) {
#pragma unroll
  for (int r = 0; r < 2; r++) {
    const uint4 a = __ldg((const uint4*)(xc + r * rstep) + q), b = __ldg((const uint4*)(xc + r * rstep) + 4 + q);
    const uint2 c = __ldg((const uint2*)(xc + r * rstep + 64) + q);
    xv[r][0] = a.x; xv[r][1] = a.y; xv[r][2] = a.z; xv[r][3] = a.w; xv[r][4] = b.x; xv[r][5] = b.y; xv[r][6] = b.z; xv[r][7] = b.w;
    xv[r][8] = c.x; xv[r][9] = c.y;
  }
}

__device__ __forceinline__ uint32_t pin(uint32_t v, uint32_t z) { uint32_t r; asm volatile("add.u32 %0, %1, %2;" : "=r"(r) : "r"(v), "r"(z)); return r; }
struct Comb { uint32_t o[7]; };
__device__ __forceinline__ Comb comb_setup(int tid, uint32_t z) {
  Comb k;
  const int c = tid & 127, c1 = c < 112 ? c + 32 : c - 112, c2 = c < 112 ? c + 144 : c - 96;
  const uint32_t zr = ZA1 + (c & 7) * 16, a2 = ZA2 + ((c & ~15) - 32 + ((((c >> 1) & 7) + (c & 1) * 8) ^ ((c & 1) * 4))) * 16;
  k.o[0] = uoff(upos(c1)); k.o[1] = uoff(upos(c2));
  k.o[2] = c < 112 ? ZA1 + 512 + ((2 * c) ^ ((c >> 2) & 1)) * 16 : zr;
  k.o[3] = c1 >= 64 ? a2 : zr; k.o[4] = c < 112 ? a2 + 112 * 16 : zr;
  k.o[5] = ((c1 >> 4) * 1280 + (c & 15)) * 16; k.o[6] = ((c2 >> 4) * 1280 + (c & 15)) * 16;
#pragma unroll
  for (int i = 0; i < 7; i++) k.o[i] = pin(k.o[i], z);
  return k;
}
__device__ __forceinline__ void combine(const Comb& k, int ch, int wid, uint4* sT) {
  const uint32_t ub = sb + OFF_U + ch * 32, zb = sb + OFF_Z + ch * ZSZ;
  const int row = (wid & 15) * 5 + ch;
  char* dst = (char*)(sT + ((wid >> 4) * 16 * 80 + row) * 16);
  mbar_wait(bar + 8 * (B_PART + ch), 0);
  const uint32_t sc = lds32(sb + OFF_CHC + ch * 8);
  const uint4 y0 = lds128(zb + k.o[2]), y1 = lds128(zb + (k.o[2] ^ 16));
  const uint4 v2 = lds128(zb + k.o[3]), u2 = lds128(zb + k.o[4]);
  const uint4 v0 = lds128(ub + k.o[0]), u0 = lds128(ub + k.o[1]);
  fence_async_smem();
  *(uint4*)(dst + (k.o[5] ^ ((row & 7) * 16))) =
      make_uint4(bmul(badd(badd(y0.x, v2.x), v0.x), sc), bmul(badd(badd(y0.y, v2.y), v0.y), sc),
                 bmul(badd(badd(y1.x, v2.z), v0.z), sc), bmul(badd(badd(y1.y, v2.w), v0.w), sc));
  *(uint4*)(dst + (k.o[6] ^ ((row & 7) * 16))) =
      make_uint4(bmul(badd(badd(y0.z, u2.x), u0.x), sc), bmul(badd(badd(y0.w, u2.y), u0.y), sc),
                 bmul(badd(badd(y1.z, u2.z), u0.z), sc), bmul(badd(badd(y1.w, u2.w), u0.w), sc));
  __syncwarp();
  if (elect1()) mbar_arrive(bar + 8 * (B_FREE + ch));
}

template <bool USE_SMID>
__global__ void __launch_bounds__(512, 1)
fused_s4_ffn_kernel(const Params p, const __grid_constant__ CUtensorMap tmX, const __grid_constant__ CUtensorMap tmW1,
                    const __grid_constant__ CUtensorMap tmU, const __grid_constant__ CUtensorMap tmW2) {
  extern __shared__ __align__(1024) unsigned char smem_raw[];
  const int tid = threadIdx.x, lane = tid & 31;
  const int warp = __shfl_sync(0xffffffffu, tid >> 5, 0);
  const int g = lane >> 2, q = lane & 3;
  uint32_t sid;
  if (USE_SMID) asm("mov.u32 %0, %smid;" : "=r"(sid)); else sid = blockIdx.x;
  if (sid - 120u < 4u) { spare_work(p, &tmW1, sid - 120, tid); return; }
  const int wid = sid < 120 ? sid : sid - 4;
  unsigned* const cnt = p.scr->cnt;

  float kacc[5][4];
  const int kpart = (warp >= 5) + (warp >= 10), kch = warp - 5 * kpart;
  float dt, k0;
  uint32_t xv[2][10], xs[2], mw, pds;
  {
    uint32_t pa[6], pld;
    unsigned ep0;
    if (warp < 15) {
      const int ch = (wid >> 4) * 80 + frag_col((wid & 15) * 5 + kch);
      const int o = (ch * 3 + kpart) * 32 + lane;
      pa[0] = __ldg((const uint32_t*)p.are + o); pa[1] = __ldg((const uint32_t*)p.aim + o);
      pa[2] = __ldg((const uint32_t*)p.bre + o); pa[3] = __ldg((const uint32_t*)p.bim + o);
      pa[4] = __ldg((const uint32_t*)p.cre + o); pa[5] = __ldg((const uint32_t*)p.cim + o);
      pld = __ldg((const unsigned short*)p.logdt + ch);
      pds = __ldg((const unsigned short*)p.dskip + ch);
    } else {
      ep0 = p.scr->epoch[wid];
      if ((uint32_t)__cvta_generic_to_shared(smem_raw) != sb) __trap();
    }
    if (elect1()) {
      const int gi = (warp + 1) & 15;
#pragma unroll
      for (int i = 0; i < 6; i++) mbar_init(bar + 48 * gi + 8 * i, gi < 7 ? 1 : gi == 7 ? 2 : gi < 10 ? 4 : 8);
      asm volatile("fence.mbarrier_init.release.cluster;" ::: "memory");
    }
    if (warp == 15) {
      sts32(sb + OFF_ZERO + lane * 4, 0);
      int gpc, i;
      if (sid < 64) { gpc = (sid & 15) >> 1; i = sid >> 4; }
      else if (sid < 120) { const int t = sid - 64; i = t / 14; gpc = 1 + ((t - i * 14) >> 1); i += 4; }
      else { gpc = 0; i = 4 + ((sid - 124) >> 1); }
      const int qi = ((0x52741630 >> (4 * i)) & 7) * 2 + (sid & 1);
      const int rg = 4 * (gpc >> 1) + (qi >> 2), jc = 4 * (gpc & 1) + (qi & 3);
      sts64(sb + OFF_EP + 8, rg, jc);
      __syncwarp();
      if (elect1()) {
        if (DELAY_NS) __nanosleep(DELAY_NS);
        bulk_prefetch(p.x + wid * 16 * DM, 16 * DM * 2);
#pragma unroll 1
        for (int s = 0; s < 4; s++) load1(s, &tmX, &tmW1, rg, jc);
        bulk_prefetch(p.w1 + wid * 5 * FF, 5 * FF * 2);
        bulk_prefetch(p.w2 + wid * 12 * DM, 12 * DM * 2);
        asm volatile("prefetch.tensormap [%0];\nprefetch.tensormap [%1];" ::"l"(&tmU), "l"(&tmW2) : "memory");
      }
    }
#pragma unroll
    for (int j = 0; j < 5; j++) { kacc[j][0] = kacc[j][1] = kacc[j][2] = kacc[j][3] = 0.f; }
    float zr, th, zr1, th1;
    cf c, c1;
    const uint32_t ks = sb + OFF_KS + warp * 4096;
    if (warp < 15) {
      dt = rnd_bf(expf(bflo(pld)));
      c = cmul(cf{bflo(pa[4]), bflo(pa[5])}, cf{bflo(pa[2]), bflo(pa[3])});
      c1 = cmul(cf{bfhi(pa[4]), bfhi(pa[5])}, cf{bfhi(pa[2]), bfhi(pa[3])});
      mw = __reduce_max_sync(0xffffffffu, __float_as_uint(fmaxf(fmaxf(fabsf(c.r), fabsf(c.i)), fmaxf(fabsf(c1.r), fabsf(c1.i)))));
      mw = min(max(mw & 0x7f800000u, 20u << 23), 240u << 23);
      const float sc = __uint_as_float((259u << 23) - mw), dl2 = dt * 1.4426950408889634f;
      k0 = c.r + c1.r;
      zr = bflo(pa[0]) * dl2; th = bflo(pa[1]) * dt; zr1 = bfhi(pa[0]) * dl2; th1 = bfhi(pa[1]) * dt;
      c.r *= sc; c.i *= -sc; c1.r *= sc; c1.i *= -sc;
    }
    __syncwarp();
    if (warp >= 8) {
      const __nv_bfloat16* xr = p.x + (wid * 16 + ((g >> 1) << 2) + (g & 1)) * DM;
      load_x(xv, xr + (warp - 8) * 80, 2 * DM, q);
      xs[0] = __ldg((const uint32_t*)xr); xs[1] = __ldg((const uint32_t*)(xr + 2 * DM));
    }
    {
      const uint32_t ka = ks + (lane >> 3) * 512 + (lane & 7) * 16;
      const uint32_t kb = ks + ((lane >> 3) & 1) * 512 + ((lane >> 4) * 8 + (lane & 7)) * 16;
#pragma unroll 1
      for (int it = 0; it < 2; it++) {
        if (it == 1 && warp >= 8) {
          float sm[4] = {0.f, 0.f, 0.f, 0.f}, g0[4] = {0.f, 0.f, 0.f, 0.f}, g1[4] = {0.f, 0.f, 0.f, 0.f};
#pragma unroll
          for (int r = 0; r < 2; r++)
            xs[r] = fabsf(bflo(xs[r]) - bfhi(xs[r])) * 8.f < fabsf(bflo(xs[r])) ? __byte_perm(xs[r], 0, 0x1010) : 0u;
#pragma unroll
          for (int i = 0; i < 10; i += 2) {
            const uint32_t a0 = bsub(xv[0][i], xs[0]), a1 = bsub(xv[1][i], xs[1]), a2 = bsub(xv[0][i + 1], xs[0]), a3 = bsub(xv[1][i + 1], xs[1]);
            bmma(sm, a0, a1, a2, a3, 0x3f803f80u, 0x3f803f80u);
            bmma(g0, a0, a1, a2, a3, xv[0][i], xv[0][i + 1]);
            bmma(g1, a0, a1, a2, a3, xv[1][i], xv[1][i + 1]);
          }
          if (q == (g >> 1))
            sts128(sb + OFF_LNP + (warp - 8) * 128 + g * 16, __float_as_uint(sm[0]), __float_as_uint((g & 1) ? g0[1] : g0[0]),
                   __float_as_uint(sm[2]), __float_as_uint((g & 1) ? g1[3] : g1[2]));
          if (warp < 15) bar_arrive(1, 256);
        }
        if (warp == 15) continue;
        float m = ex2a(zr);
        const cf w1 = cf{m * __cosf(th), m * __sinf(th)};
        m = ex2a(zr * 8.f);
        const cf w8 = cf{m * __cosf(th * 8.f), m * __sinf(th * 8.f)};
        const cf w16 = csq(w8), w32 = csq(w16), w64 = csq(w32), w128 = csq(w64), w256 = csq(w128), w512 = csq(w256), w1024 = csq(w512);
        hp lo[8];
        lo[0] = hpack(cf{1.f, 0.f}, w8);
        lo[1] = hmulc(lo[0], pack_h(w16.r, w16.i));
        { const uint32_t k = pack_h(w32.r, w32.i); lo[2] = hmulc(lo[0], k); lo[3] = hmulc(lo[1], k); }
        { const uint32_t k = pack_h(w64.r, w64.i);
#pragma unroll
          for (int i = 0; i < 4; i++) lo[4 + i] = hmulc(lo[i], k); }
        const uint32_t st = ks + lane * 16;
        sts128(st + 512, lo[4].r, lo[5].r, lo[6].r, lo[7].r);
        sts128(st + 1536, lo[4].i, lo[5].i, lo[6].i, lo[7].i);
        sts128(st, lo[0].r, lo[1].r, lo[2].r, lo[3].r);
        sts128(st + 1024, lo[0].i, lo[1].i, lo[2].i, lo[3].i);
        const uint32_t k128 = pack_h(w128.r, w128.i), k256 = pack_h(w256.r, w256.i), k512 = pack_h(w512.r, w512.i);
        const cf t8 = cmulj(c, w8);
        hp T0[4], T1[4], T2[4], T3[4], T4[4];
        { const cf u0 = cmulj(t8, w1024), u1 = cmulj(u0, w128);
          T4[0] = hpack(u0, u1); T4[1] = hmulj(T4[0], k256); T4[2] = hmulj(T4[0], k512); T4[3] = hmulj(T4[1], k512); }
        sts_tile(st + 2048, T4);
        __syncwarp();
        uint32_t af[4][4];
#pragma unroll
        for (int mg = 0; mg < 4; mg++) ldsm4t(af[mg], ka + mg * 128);
#pragma unroll
        for (int mg = 0; mg < 4; mg += 2) {
          uint32_t b[4];
          ldsm4t(b, kb + 2048 + mg * 128);
          hmma(kacc[4], af[mg][0], af[mg][1], af[mg][2], af[mg][3], b[0], b[1]);
          hmma(kacc[4], af[mg + 1][0], af[mg + 1][1], af[mg + 1][2], af[mg + 1][3], b[2], b[3]);
        }
        const cf t1 = cmulj(c, w1), t2 = cmulj(t1, w1), t3 = cmulj(t2, w1), t4 = cmulj(t3, w1);
        const cf t5 = cmulj(t4, w1), t6 = cmulj(t5, w1), t7 = cmulj(t6, w1);
        T0[0] = hpack(t4, t8); T0[1] = hpack(t2, t6); T0[2] = hpack(t1, t5); T0[3] = hpack(t3, t7);
#pragma unroll
        for (int i = 0; i < 4; i++) T1[i] = hmulj(T0[i], k128);
        T2[0] = hmulj(T0[0], k256); T2[1] = hmulj(T0[1], k256); T2[2] = hmulj(T1[0], k256); T2[3] = hmulj(T1[1], k256);
        T3[0] = hmulj(T0[0], k512); T3[1] = hmulj(T1[0], k512); T3[2] = hmulj(T2[0], k512); T3[3] = hmulj(T2[2], k512);
        __syncwarp();
        sts_tile(st + 3072, T3);
        sts_tile(st + 2048, T2);
        sts_tile(st + 1024, T1);
        sts_tile(st, T0);
        __syncwarp();
#pragma unroll
        for (int mg = 0; mg < 4; mg += 2)
#pragma unroll
          for (int j = 3; j >= 0; j--) {
            uint32_t b[4];
            ldsm4t(b, kb + j * 1024 + mg * 128);
            hmma(kacc[j], af[mg][0], af[mg][1], af[mg][2], af[mg][3], b[0], b[1]);
            hmma(kacc[j], af[mg + 1][0], af[mg + 1][1], af[mg + 1][2], af[mg + 1][3], b[2], b[3]);
          }
        __syncwarp();
        zr = zr1; th = th1; c = c1;
      }
    }
    if (warp < 10) {
#pragma unroll
      for (int j = 0; j < 5; j++)
        sts128(ks + j * 512 + lane * 16, __float_as_uint(kacc[j][0]), __float_as_uint(kacc[j][1]), __float_as_uint(kacc[j][2]), __float_as_uint(kacc[j][3]));
      sts64(ks + 2560 + lane * 8, __float_as_uint(k0), mw);
    } else if (warp == 15) {
      if (lane == 0) { p.scr->epoch[wid] = ep0 + 1; sts32(sb + OFF_EP, ep0 + 1); }
      bar_sync(1, 256);
      float s1 = 0.f, s2 = 0.f;
#pragma unroll
      for (int w = 0; w < 8; w++) {
        const uint2 v = lds64(sb + OFF_LNP + w * 128 + g * 16 + (q & 1) * 8);
        s1 += __uint_as_float(v.x); s2 += __uint_as_float(v.y);
      }
      const float md = s1 * (1.f / DM), mean = bflo((q & 1) ? xs[1] : xs[0]) + md;
      const float var = fmaxf(fmaf(-md, mean, s2 * (1.f / DM)), 0.f);
      const float m = rnd_bf(mean);
      float sd, ri;
      asm("sqrt.approx.f32 %0, %1;" : "=f"(sd) : "f"(rnd_bf(rnd_bf(var) + 1e-5f)));
      asm("rcp.approx.f32 %0, %1;" : "=f"(ri) : "f"(rnd_bf(sd)));
      if (q < 2) {
        p.scr->stats[wid * 16 + ((g >> 1) << 2) + (g & 1) + 2 * q] = make_float2(-m, 0.5f * ri);
        sts64(sb + OFF_STAT + g * 16 + q * 8, __float_as_uint(-m * ri), __float_as_uint(ri));
      }
    }
  }
  __syncthreads();

  if (warp < 8) {
    float acc[96];
    const uint32_t alo = ((sb >> 4) | (1 << 16)) + (warp >> 2) * 512;
#pragma unroll 1
    for (int s = 0; s < 10; s++) {
      const uint32_t so = (s & 3) * (SLOT1 >> 4);
      mbar_wait(bar + 8 * (B_FULL1 + s), 0);
      wg_fence();
#pragma unroll
      for (int kk = 0; kk < 4; kk++)
        wgmma_n192(acc, dsc(alo + so + kk * 2, 0x40000040u), dsc((((sb + 16384) >> 4) | (512 << 16)) + so + kk * 128, 0x40000040u), (s | kk) != 0);
      wg_commit();
      wg_wait<1>();
      if (lane == 0) mbar_arrive(bar + 8 * (B_REL1 + s));
    }
    wg_wait<0>();
    bar_arrive(14, 384);
    bar_arrive(7, 384);
    mbar_wait(bar + 8 * B_EPI, 0);
    const uint2 s0 = lds64(sb + OFF_STAT + (warp * 16 + g) * 8), s1 = lds64(sb + OFF_STAT + (warp * 16 + g + 8) * 8);
    const float nm0 = __uint_as_float(s0.x), r0 = __uint_as_float(s0.y), nm1 = __uint_as_float(s1.x), r1 = __uint_as_float(s1.y);
    const uint4 erj = lds128(sb + OFF_EP);
    const unsigned ep = erj.x;
    const int rg1 = erj.z, j1 = erj.w;
    uint4* hd = p.scr->h + (rg1 * 24 + j1) * 1024 + warp * 128 + q * 8 + g;
#pragma unroll
    for (int grp = 0; grp < 6; grp++) {
      uint32_t o0[4], o1[4];
#pragma unroll
      for (int tl = 0; tl < 4; tl++) {
        const int nt = grp * 4 + tl;
        const uint2 cs = lds64(sb + OFF_CS + (nt * 8 + 2 * q) * 4);
        const float ca = __uint_as_float(cs.x), cb = __uint_as_float(cs.y);
        const float a = fmaf(nm0, ca, acc[4 * nt]) * r0, b = fmaf(nm0, cb, acc[4 * nt + 1]) * r0;
        const float c = fmaf(nm1, ca, acc[4 * nt + 2]) * r1, d = fmaf(nm1, cb, acc[4 * nt + 3]) * r1;
        o0[tl] = pack_bf(fmaf(a, tanha(a), a), fmaf(b, tanha(b), b));
        o1[tl] = pack_bf(fmaf(c, tanha(c), c), fmaf(d, tanha(d), d));
      }
      uint4* dst = hd + (grp >> 1) * 8192 + (grp & 1) * 32;
      dst[0] = make_uint4(o0[0], o0[1], o0[2], o0[3]);
      dst[64] = make_uint4(o1[0], o1[1], o1[2], o1[3]);
      if (PACE_NS) __nanosleep(PACE_NS);
      if (grp == 1) {
        if (warp == 7) { bar_sync(2, 448); if (lane == 0) publish(cnt + C_H0 * 32); __syncwarp(); }
        else bar_arrive(2, 448);
      }
    }
    if (warp == 6) { bar_sync(11, 256); if (lane == 0) publish(cnt + (C_H1 + rg1) * 32); __syncwarp(); }
    else bar_arrive(11, 256);
    const int go = (rg1 * 128 + warp * 16 + g) * DM + j1 * 80;
    load_x(xv, p.x + go, 8 * DM, q);
    if (warp < 4) {
      const Comb cmb = comb_setup(tid, 0);
#pragma unroll 1
      for (int ch = 0; ch < 3; ch++) {
        combine(cmb, ch, wid, p.scr->sT);
      }
    } else if (warp == 4) {
      if (elect1()) {
        poll_cnt(cnt + C_H0 * 32, ep * 128);
#pragma unroll 1
        for (int s = 0; s < NS2 - 2; s++) {
          if (s == 3) poll_cnt(cnt + (C_H1 + rg1) * 32, ep * 8);
          if (s == 3) mbar_wait(bar + 8 * B_FREE, 0);
          if (s >= 3) mbar_wait(bar + 8 * (B_FREE + s - 2), 0);
          const uint32_t mb = bar + 8 * (B_FULL2 + s);
          mbar_expect(mb, SLOT2);
          bulk_g2s(sb + s * SLOT2, p.scr->h + (rg1 * 24 + s) * 1024, 16384, mb);
          bulk_g2s(sb + s * SLOT2 + 16384, p.scr->w2p + (j1 * 24 + s) * 640, 10240, mb);
        }
      }
      __syncwarp();
    }
    float acc2[40];
    bar_sync(8, 512);
    {
      const uint32_t al2 = ((sb >> 4) | (8 << 16)) + (warp >> 2) * 512;
      uint32_t so = 0;
#pragma unroll 1
      for (int s = 0; s < 24; s++) {
        mbar_wait(bar + 8 * (B_FULL2 + s), 0);
        wg_fence();
#pragma unroll
        for (int kk = 0; kk < 4; kk++)
          wgmma_n80(acc2, dsc(al2 + so + kk * 16, 64), dsc((((sb + 16384) >> 4) | (80 << 16)) + so + kk * 160, 8), (s | kk) != 0);
        wg_commit();
        so = so == (NS2 - 1) * (SLOT2 >> 4) ? 0 : so + (SLOT2 >> 4);
        wg_wait<1>();
        if (lane == 0) mbar_arrive(bar + 8 * (B_REL2 + s));
      }
    }
    mbar_wait(bar + 8 * B_SFULL, 0);
    uint32_t sv[5][4];
    {
      const int i = lane & 7, mi = lane >> 3;
      const uint32_t a = sb + OFF_U + ((mi >> 1) * 8 + i) * 256 + (((2 * warp + (mi & 1)) ^ i) << 4);
#pragma unroll
      for (int k = 0; k < 5; k++) ldsm4t(sv[k], a + k * 4096);
    }
    wg_wait<0>();
#pragma unroll
    for (int hh = 0; hh < 2; hh++) {
      uint32_t o[10];
#pragma unroll
      for (int tl = 0; tl < 10; tl++) {
        const uint32_t xw = xv[hh][tl];
        const uint32_t sw = sv[tl >> 1][(tl & 1) * 2 + hh];
        const float a = acc2[4 * tl + 2 * hh], b = acc2[4 * tl + 2 * hh + 1];
        o[tl] = pack_bf(fmaf(bflo(sw), fmaf(a, tanha(a), a), bflo(xw)), fmaf(bfhi(sw), fmaf(b, tanha(b), b), bfhi(xw)));
      }
      __nv_bfloat16* op = p.out + go + hh * 8 * DM;
      ((uint4*)op)[q] = make_uint4(o[0], o[1], o[2], o[3]);
      ((uint4*)op)[4 + q] = make_uint4(o[4], o[5], o[6], o[7]);
      ((uint2*)(op + 64))[q] = make_uint2(o[8], o[9]);
    }
  } else {
    const int cw = warp - 8;
    const uint4 erj = lds128(sb + OFF_EP);
    const unsigned ep = erj.x;
    const int rg1 = erj.z, j1 = erj.w;
    {
      const uint4 st = lds128(sb + OFF_STAT + g * 16);
      const float n0 = __uint_as_float(st.x), r0 = __uint_as_float(st.y), n1 = __uint_as_float(st.z), r1 = __uint_as_float(st.w);
      const int up = upos(2 * wid);
      uint2* dst = (uint2*)p.scr->uT + ((up >> 1) * DM + cw * 80) * 4 + (lane ^ ((up & 1) << 1));
#pragma unroll
      for (int i = 0; i < 10; i++) {
        const uint32_t a = movm(pack_h(fmaf(bflo(xv[0][i]), r0, n0), fmaf(bfhi(xv[0][i]), r0, n0)));
        const uint32_t b = movm(pack_h(fmaf(bflo(xv[1][i]), r1, n1), fmaf(bfhi(xv[1][i]), r1, n1)));
        dst[i * 32] = make_uint2(a, b);
      }
    }
    if (warp == 8) {
      bar_sync(12, 256);
      if (lane == 0) publish(cnt + C_LN * 32);
      __syncwarp();
    } else bar_arrive(12, 256);
    if (warp == 15) {
      if (elect1()) {
#pragma unroll 1
        for (int s = 4; s < 10; s++) {
          mbar_wait(bar + 8 * (B_REL1 + s - 3), 0);
          load1(s, &tmX, &tmW1, rg1, j1);
        }
      }
      __syncwarp();
    }
    if (warp >= 10 && warp < 15) {
      const uint32_t pb = sb + OFF_P + kch * 3072, pk = sb + OFF_KS + kch * 4096;
      const uint2 e0 = lds64(pk + 2560 + lane * 8), e1 = lds64(pk + 5 * 4096 + 2560 + lane * 8);
      const float dsk = bflo(pds);
      uint32_t kex = __float_as_uint(fmaxf(__uint_as_float(max(max(e0.y, e1.y), mw)) * dt, fabsf(dsk) * (1.f / 256.f))) >> 23;
      kex = min(max(kex, 20u), 240u);
      const float s2 = __uint_as_float((258 - kex) << 23), sd = s2 * dt * (1.f / 32.f);
      const float f0 = __uint_as_float(e0.y) * sd, f1 = __uint_as_float(e1.y) * sd, f2 = __uint_as_float(mw) * sd;
      k0 += __uint_as_float(e0.x) + __uint_as_float(e1.x);
#pragma unroll
      for (int o = 16; o; o >>= 1) k0 += __shfl_xor_sync(0xffffffffu, k0, o);
      const float k0n = fmaf(k0, dt, dsk) * s2;
      uint32_t h[5][2];
#pragma unroll
      for (int j = 0; j < 5; j++) {
        const uint4 a = lds128(pk + j * 512 + lane * 16), b = lds128(pk + 5 * 4096 + j * 512 + lane * 16);
#pragma unroll
        for (int e = 0; e < 4; e++) kacc[j][e] = fmaf(__uint_as_float((&a.x)[e]), f0, fmaf(__uint_as_float((&b.x)[e]), f1, kacc[j][e] * f2));
        if (j == 1) {
          const float k256 = __shfl_sync(0xffffffffu, kacc[1][3], 28);
          if (lane == 31) kacc[1][3] -= k256;
        }
        if (j == 2 || j == 3) { h[j][0] = pack_h(kacc[j][0], kacc[j][2]); h[j][1] = pack_h(kacc[j][1], kacc[j][3]); }
        else { h[j][0] = pack_h(kacc[j][0], kacc[j][1]); h[j][1] = pack_h(kacc[j][2], kacc[j][3]); }
      }
      fence_async_smem();
      bar_arrive(4, 192);
#pragma unroll
      for (int i = 0; i < 6; i++) sts128(pb + i * 512 + lane * 16, 0, 0, 0, 0);
      __syncwarp();
      {
        const int sw = g >> 2;
        const uint32_t sel = sw ? 0x1032 : 0x3210;
        const uint32_t a = pb + (P0 + 8 * g + ((0x3124 >> (4 * q)) & 7)) * 4, a0 = a + sw * 16, a1 = a + 16 - sw * 16;
        put2<1>(a0, a1, h[0][0], sel);
        put2<1>(a0 + 256, a1 + 256, h[0][1], sel);
        put2<1>(a0 + 512, a1 + 512, h[1][0], sel);
        put2<1>(lane == 28 ? pb + PB1 * 4 : a0 + 768, a1 + 768, h[1][1], sel);
      }
      {
        const int sw = q >> 1;
        const uint32_t sel = sw ? 0x1032 : 0x3210;
        uint32_t a = pb + (((q & 1) ? PA1 : PB1 + 1) + 32 * sw + 2 * g) * 4;
        put2<1>(a + sw * 64, a + 64 - sw * 64, h[2][0], sel);
        put2<1>(a + 4 + sw * 64, a + 68 - sw * 64, h[2][1], sel);
        a = pb + (PA2 + g + 16 * q) * 4;
        put2<2>(a + sw * 32, a + 32 - sw * 32, h[3][0], sel);
        put2<2>(a + (PB2 - PA2) * 4 + sw * 32, a + (PB2 - PA2) * 4 + 32 - sw * 32, h[3][1], sel);
        a = pb + (((g & 1) ? PB3 : PA3) + (g >> 1) + 16 * q) * 4;
        const uint32_t hx = sw ? h[4][1] : h[4][0], hy = sw ? h[4][0] : h[4][1];
        put2<1>(a + sw * 16, a + 32 + sw * 16, hx, 0x3210);
        put2<1>(a + 16 - sw * 16, a + 48 - sw * 16, hy, 0x3210);
      }
      if (lane == 30) put2<1>(pb + P0 * 4, pb + (PA1 + 64) * 4, pack_h(k0n, kacc[2][3]), 0x3210);
      if (lane == 31) sts64(sb + OFF_CHC + kch * 8, (kex - 4) * 0x00800080u, __byte_perm(h[3][1], 0, 0x3232));
    }
    if (warp == 8) {
      bar_sync(13, 64);
      if (elect1()) {
        mbar_expect(bar + 8 * B_UFULL, 144 * 160);
        mbar_expect(bar + 8 * B_EPI, 1024 + 768);
        poll_cnt(cnt + C_LN * 32, ep * 128);
        tma2d(sb + OFF_U - 16 * 160, &tmU, wid * 80, -16, bar + 8 * B_UFULL);
        bulk_g2s(sb + OFF_STAT, p.scr->stats + rg1 * 128, 1024, bar + 8 * B_EPI);
      }
      __syncwarp();
      bar_arrive(15, 224);
    } else if (warp == 9) {
      bar_sync(4, 192);
      bar_arrive(13, 64);
      if (elect1()) {
        mbar_expect(bar + 8 * B_W2, 96 * 176);
        tma5d(sb + OFF_W2S, &tmW2, (wid & 7) * 80, (wid >> 3) * 3, bar + 8 * B_W2);
        poll_cnt(cnt + C_CS * 32, ep * 4);
        bulk_g2s(sb + OFF_CS, p.scr->cs + j1 * 192, 768, bar + 8 * B_EPI);
      }
      __syncwarp();
    }
    if (warp >= 9 && warp < 15) {
      const int uu = (warp - 9) >> 1, G = (warp - 9) & 1;
      const int grp = (wid >> 3) * 3 + uu, jj = grp / 6, rem = grp - jj * 6;
      const uint32_t a = sb + OFF_W2S + (uu * 32 + lane) * 176;
      uint4* dst = p.scr->w2p + ((wid & 7) * 24 + 8 * (rem >> 1) + jj) * 640 + ((rem & 1) * 4 + (lane >> 3)) * 80 + (lane & 7);
      mbar_wait(bar + 8 * B_W2, 0);
      const uint4 wv[4] = {lds128(a + G * 64), lds128(a + G * 64 + 16), lds128(a + G * 64 + 32), lds128(a + G * 64 + 48)};
      const uint4 t0 = lds128(a + 128), t1 = lds128(a + 144);
      uint32_t w[20];
#pragma unroll
      for (int i = 0; i < 16; i++) w[i] = bmul((&wv[i >> 2].x)[i & 3], 0x3f003f00u);
      w[16] = bmul(G ? t0.y : t0.x, 0x3f003f00u); w[17] = bmul(G ? t0.w : t0.z, 0x3f003f00u);
      w[18] = bmul(G ? t1.y : t1.x, 0x3f003f00u); w[19] = bmul(G ? t1.w : t1.z, 0x3f003f00u);
      bar_sync(15, 224);
#pragma unroll
      for (int i = 0; i < 4; i++) dst[G * 32 + 8 * i] = make_uint4(w[i], w[4 + i], w[8 + i], w[12 + i]);
      dst[64 + G * 8] = make_uint4(w[16], w[17], w[18], w[19]);
      bar_arrive(2, 448);
      if (warp == 12) bar_arrive(3, 64);
    } else if (warp == 15) bar_sync(3, 64);
    const int wg = warp >> 2, role = (warp + 2 * wg) & 3;
    uint32_t co[6], cpa = (g - 2 * q) * 4;
    if (role < 2) {
#pragma unroll
      for (int gm = 0; gm < 3; gm++) {
        const int hb = 2 * (lane & 7) + role - 2 + gm, l3 = ((lane >> 3) ^ (hb >> 1)) & 7;
        co[2 * gm] = hb * 1280 + uoff(l3); co[2 * gm + 1] = hb * 1280 + uoff(l3 ^ 4);
      }
    } else {
      const int mi = lane >> 3, hf = (lane >> 2) & 1;
      co[0] = hf * 1792 + (mi ^ hf) * 64 + ((q ^ (mi >> 1) ^ (hf * 2)) << 4);
      co[1] = co[0] ^ 96;
      co[2] = (lane ^ (role == 2 ? (mi & 1) : ((lane >> 1) & 4))) << 4;
      co[3] = lane * 16;
      co[4] = (g >> 1) == q ? ((g & 1) ? 0xffff0000u : 0xffffu) : 0u;
      co[5] = 2 * cpa;
    }
    const uint32_t zero = lds32(sb + OFF_ZERO), nz = zero | 0x80000000u;
#pragma unroll
    for (int i = 0; i < 6; i++) co[i] = pin(co[i], zero);
    cpa = pin(cpa, zero);
    const Comb cmb = comb_setup(tid, zero);
    mbar_wait(bar + 8 * B_UFULL, 0);
#pragma unroll 1
    for (int ch = (cw >> 2) * 4; ch >= (cw >> 2); ch--) {
      if (ch < 4) mbar_wait(bar + 8 * (B_REL1 + (ch ? 8 : 7)), 0);
      const int qt = (cw + ch) & 3, j = qt * 32 + lane;
      const uint32_t ub = sb + OFF_U + ch * 32, zb = sb + OFF_Z + ch * ZSZ;
      uint32_t w_[20], o_[20], d_[20], b3_[20];
      uint32_t *w = w_ + 8, *o = o_ + 8, *d = d_ + 8, *b3 = b3_ + 8;
      {
        const uint32_t am = ub + uoff(upos(2 * j - 2)), a0 = ub + uoff(upos(2 * j));
        const uint2 a = lds64(am + 8);
        const uint4 b = lds128(am ^ 16), c = lds128(a0), e = lds128(a0 ^ 16);
        w[8] = lds32(ub + uoff(upos((2 * j + 2) & 255)));
        w[-6] = a.x; w[-5] = a.y; w[-4] = b.x; w[-3] = b.y; w[-2] = b.z; w[-1] = b.w;
        w[0] = c.x; w[1] = c.y; w[2] = c.z; w[3] = c.w; w[4] = e.x; w[5] = e.y; w[6] = e.z; w[7] = e.w;
      }
#pragma unroll
      for (int i = -1; i <= 7; i++) o[i] = odd_pair(w[i], w[i + 1]);
#pragma unroll
      for (int i = 0; i <= 7; i++) { d[i] = hadd(w[i], o[i]); b3[i] = hadd(d[i], o[i - 1]); }
      if (j < 112) {
        const int gr = j >> 1;
        const uint32_t a1 = zb + ZA1 + 512 + (gr ^ ((gr >> 2) & 1)) * 64 + ((gr >> 1) & 3) * 16 + (j & 1) * 8;
#pragma unroll
        for (int pp = 0; pp < 4; pp++) {
          const uint32_t sel = (pp & 1) ? 0x7632 : 0x5410;
          const int k = pp >> 1;
          sts64(a1 ^ (pp * 16), __byte_perm(w[k - 1], w[k + 1], sel), __byte_perm(w[k + 3], w[k + 5], sel));
          sts64((a1 ^ (pp * 16)) + (ZB1 - ZA1), __byte_perm(b3[k], b3[k + 2], sel), __byte_perm(b3[k + 4], b3[k + 6], sel));
        }
      } else {
        const uint32_t a1 = zb + ZA1 + ((lane ^ 7) & 15) * 16;
        sts128(a1, 0, 0, 0, 0); sts128(a1 + 256, 0, 0, 0, 0); sts128(a1 + ZB1 - ZA1, 0, 0, 0, 0);
        sts128(a1 + ZB1 - ZA1 + 256, 0, 0, 0, j == 127 ? w[8] << 16 : 0u);
      }
      if (qt < 3) {
        uint32_t e_[20], b5_[20];
        uint32_t *e = e_ + 8, *b5 = b5_ + 8;
#pragma unroll
        for (int i = -6; i <= -2; i++) o[i] = odd_pair(w[i], w[i + 1]);
#pragma unroll
        for (int i = -6; i <= -1; i++) d[i] = hadd(w[i], o[i]);
#pragma unroll
        for (int i = -5; i <= -1; i++) b3[i] = hadd(d[i], o[i - 1]);
#pragma unroll
        for (int i = -5; i <= 4; i++) e[i] = hadd(d[i - 1], d[i]);
#pragma unroll
        for (int i = -4; i <= 4; i++) b5[i] = hadd(e[i], w[i + 1]);
        const uint32_t a2 = zb + ((j >> 3) * 16 + (j & 7)) * 16;
        sts128(a2 + ZA2, b3[-2], b3[-1], b3[0], b3[1]);
        sts128(a2 + ZA2 + 128, b3[2], b3[3], b3[4], b3[5]);
        sts128(a2 + ZB2, b5[-4], b5[-3], b5[-2], b5[-1]);
        sts128(a2 + ZB2 + 128, b5[0], b5[1], b5[2], b5[3]);
        if (qt < 2) {
          sts128(a2 + ZS, d[-2], d[-1], d[0], d[1]);
          sts128(a2 + ZS + 128, d[2], d[3], d[4], d[5]);
          uint32_t b7[8], b9[8];
#pragma unroll
          for (int i = -4; i <= 3; i++) { b7[i + 4] = hadd(b3[i - 1], e[i + 1]); b9[i + 4] = hadd(e[i - 1], b5[i + 1]); }
          const uint32_t a3 = zb + ((j >> 4) * 32 + (j & 15)) * 16;
          sts128(a3 + ZA3, b7[0], b7[1], b7[2], b7[3]);
          sts128(a3 + ZA3 + 256, b7[4], b7[5], b7[6], b7[7]);
          sts128(a3 + ZB3 + 256, b9[0], b9[1], b9[2], b9[3]);
          if (j < 63) sts128(a3 + ZB3 + ((j & 15) == 15 ? 272 : 16), b9[4], b9[5], b9[6], b9[7]);
          else sts128(zb + ZB3, 0, 0, 0, 0);
        }
      }
    }
    if (wg == 3) bar_arrive(0, 256);
    bar_sync(wg == 2 ? 14 : 7, 384);
#pragma unroll 1
    for (int ch = wg - 2; ch < 5; ch += 2) {
      const uint32_t ub = sb + OFF_U + ch * 32, zb = sb + OFF_Z + ch * ZSZ, pb = sb + OFF_P + ch * 3072;
      if (ch == 2) bar_sync(0, 256);
      const uint32_t pa = pb + cpa;
      if (role < 2) {
        float acc[8][4];
#pragma unroll
        for (int r = 0; r < 8; r++) { acc[r][0] = acc[r][1] = acc[r][2] = acc[r][3] = 0.f; }
        float fix = 0.f;
        if (role == 1 && lane == 28) {
          const uint32_t k = lds32(pb + PB1 * 4), u0 = lds32(ub);
          fix = __low2float(*reinterpret_cast<const __half2*>(&k)) * __low2float(*reinterpret_cast<const __half2*>(&u0));
        }
        uint32_t b[12][4], A[17][4];
#pragma unroll
        for (int i = 11; i >= 8; i--) ldsm4(b[i], ub + (co[4 + (i & 1)] ^ (((i >> 1) & 1) * 16)) + ((i >> 1) & 1) * 640);
        A[0][0] = lds32(pa + P0 * 4); A[0][1] = lds32(pa + P0 * 4 + 32); A[0][2] = lds32(sb + OFF_ZERO + 4);
#pragma unroll
        for (int m = 0; m <= 16; m++) {
          if (m < 16) {
            A[m + 1][0] = lds32(pa + P0 * 4 + (2 * m + 2) * 32);
            A[m + 1][1] = m < 15 ? lds32(pa + P0 * 4 + (2 * m + 3) * 32) : lds32(sb + OFF_ZERO + 8);
          }
          if ((m & 1) == 0 && m < 16) {
            const int i = 7 - (m >> 1);
            ldsm4(b[i], ub + (co[2 * (i >> 2) + (i & 1)] ^ (((i >> 1) & 1) * 16)) + ((i >> 1) & 1) * 640);
          }
          if (m == 9 && elect1()) mbar_arrive(bar + 8 * (B_PAIR + ch));
          A[m][3] = dup(A[m][0], nz);
          if (m < 16) A[m + 1][2] = dup(A[m][1], nz);
#pragma unroll
          for (int r = 7; r >= 0; r--) {
            const int f = 16 + r - m;
            hmma(acc[r], A[m][0], A[m][1], A[m][2], A[m][3], b[f >> 1][(f & 1) * 2], b[f >> 1][(f & 1) * 2 + 1]);
          }
        }
        acc[7][2] += fix;
        mbar_wait(bar + 8 * (B_PAIR + ch), 0);
#pragma unroll
        for (int i = 3; i >= 0; i--)
          stsm4t(ub + (co[4 + (i & 1)] ^ (((i >> 1) & 1) * 16)) + ((i >> 1) & 1) * 640, pack_bf(acc[2 * i][0], acc[2 * i][1]), pack_bf(acc[2 * i][2], acc[2 * i][3]),
                 pack_bf(acc[2 * i + 1][0], acc[2 * i + 1][1]), pack_bf(acc[2 * i + 1][2], acc[2 * i + 1][3]));
      } else if (role == 2) {
        float acc[14][4];
#pragma unroll
        for (int r = 0; r < 14; r++) { acc[r][0] = acc[r][1] = acc[r][2] = acc[r][3] = 0.f; }
#pragma unroll
        for (int arr = 0; arr < 2; arr++) {
          uint32_t A[5][4];
#pragma unroll
          for (int m = 0; m < 5; m++) {
            A[m][0] = lds32(pa + (arr ? PB1 : PA1) * 4 + m * 64);
            A[m][1] = m < 4 ? lds32(pa + (arr ? PB1 : PA1) * 4 + m * 64 + 32) : lds32(sb + OFF_ZERO + 4 + arr * 8);
          }
#pragma unroll
          for (int m = 4; m >= 1; m--) { A[m][2] = dup(A[m - 1][1], nz); A[m][3] = dup(A[m][0], nz); }
          A[0][2] = lds32(sb + OFF_ZERO + 8 + arr * 8); A[0][3] = dup(A[0][0], nz);
#pragma unroll
          for (int ip = 0; ip < 9; ip++) {
            uint32_t b[4];
            ldsm4(b, zb + co[ip & 1] + (arr ? ZB1 : ZA1) + ip * 256);
#pragma unroll
            for (int hh = 0; hh < 2; hh++)
#pragma unroll
              for (int m = 0; m < 5; m++) {
                const int i = 2 * ip + hh - 4 + m;
                if (i >= 0 && i < 14) hmma(acc[i], A[m][0], A[m][1], A[m][2], A[m][3], b[2 * hh], b[2 * hh + 1]);
              }
          }
        }
        const uint32_t a = zb + ZA1 + 512 + co[2];
#pragma unroll
        for (int i = 0; i < 7; i++)
          stsm4(a + i * 512, pack_bf(acc[2 * i][0], acc[2 * i][1]), pack_bf(acc[2 * i][2], acc[2 * i][3]),
                pack_bf(acc[2 * i + 1][0], acc[2 * i + 1][1]), pack_bf(acc[2 * i + 1][2], acc[2 * i + 1][3]));
      } else {
        float acc[12][4];
        const uint32_t za = zb + co[3];
        {
          float d[4][2][4];
#pragma unroll
          for (int r = 0; r < 8; r++) { d[r >> 1][r & 1][0] = d[r >> 1][r & 1][1] = d[r >> 1][r & 1][2] = d[r >> 1][r & 1][3] = 0.f; }
#pragma unroll
          for (int arr = 0; arr < 2; arr++) {
            uint32_t A[4][4];
#pragma unroll
            for (int m = 0; m < 4; m++) { A[m][0] = lds32(pa + (arr ? PB3 : PA3) * 4 + m * 64); A[m][1] = lds32(pa + (arr ? PB3 : PA3) * 4 + m * 64 + 32); }
#pragma unroll
            for (int m = 0; m < 4; m++) { A[m][2] = m ? dup(A[m - 1][1], nz) : lds32(sb + OFF_ZERO + 4 + arr * 4); A[m][3] = dup(A[m][0], nz); }
#pragma unroll
            for (int io = 0; io < 4; io++) {
              uint32_t b[4];
              ldsm4t(b, za + (arr ? ZB3 : ZA3) + io * 512);
#pragma unroll
              for (int m = 0; m + io < 4; m++) {
                hmma(d[io + m][0], A[m][0], A[m][1], A[m][2], A[m][3], b[0], b[1]);
                hmma(d[io + m][1], A[m][0], A[m][1], A[m][2], A[m][3], b[2], b[3]);
              }
            }
          }
#pragma unroll
          for (int r = 0; r < 4; r++) {
            acc[r][0] = acc[r][1] = acc[r][2] = acc[r][3] = 0.f;
            acc[4 + 2 * r][0] = d[r][0][0]; acc[4 + 2 * r][1] = d[r][0][1]; acc[4 + 2 * r][2] = d[r][1][0]; acc[4 + 2 * r][3] = d[r][1][1];
            acc[5 + 2 * r][0] = d[r][0][2]; acc[5 + 2 * r][1] = d[r][0][3]; acc[5 + 2 * r][2] = d[r][1][2]; acc[5 + 2 * r][3] = d[r][1][3];
          }
        }
        {
          const uint32_t k0 = lds32(sb + OFF_CHC + ch * 8 + 4) & co[4];
          const uint32_t k1 = lds32(sb + OFF_ZERO + 12), k2 = lds32(sb + OFF_ZERO + 16), k3 = dup(k0, nz);
#pragma unroll
          for (int ip = 0; ip < 4; ip++) {
            uint32_t b[4];
            ldsm4t(b, za + ZS + ip * 512);
            hmma(acc[4 + 2 * ip], k0, k1, k2, k3, b[0], b[1]);
            hmma(acc[5 + 2 * ip], k0, k1, k2, k3, b[2], b[3]);
          }
        }
        const uint32_t pa2 = pb + co[5];
#pragma unroll
        for (int arr = 0; arr < 2; arr++) {
          uint32_t A[5][4];
#pragma unroll
          for (int m = 0; m < 5; m++) {
            const uint2 v = lds64(pa2 + (arr ? PB2 : PA2) * 4 + m * 64);
            A[m][0] = v.x; A[m][1] = v.y; A[m][2] = lds32(pa2 + (arr ? PB2 : PA2) * 4 + m * 64 - 4);
          }
#pragma unroll
          for (int m = 0; m < 5; m++) A[m][3] = dup(A[m][0], nz);
#pragma unroll
          for (int ip = 0; ip < 6; ip++) {
            uint32_t b[4];
            ldsm4t(b, za + (arr ? ZB2 : ZA2) + ip * 512);
#pragma unroll
            for (int hh = 0; hh < 2; hh++)
#pragma unroll
              for (int m = 0; m < 5; m++) {
                const int i = 2 * ip + hh + m;
                if (i < 12) hmma(acc[i], A[m][0], A[m][1], A[m][2], A[m][3], b[2 * hh], b[2 * hh + 1]);
              }
          }
        }
        const uint32_t a = zb + ZA2 + co[2];
#pragma unroll
        for (int i = 0; i < 6; i++)
          stsm4(a + i * 512, pack_bf(acc[2 * i][0], acc[2 * i][1]), pack_bf(acc[2 * i][2], acc[2 * i][3]),
                pack_bf(acc[2 * i + 1][0], acc[2 * i + 1][1]), pack_bf(acc[2 * i + 1][2], acc[2 * i + 1][3]));
      }
      __syncwarp();
      if (elect1()) mbar_arrive(bar + 8 * (B_PART + ch));
    }
    bar_arrive(8, 512);
    combine(cmb, 6 - wg, wid, p.scr->sT);
    if (warp == 12) {
      if (elect1()) {
        const uint4* srcA = p.scr->h + (rg1 * 24 + NS2 - 2) * 1024;
        const uint4* srcB = p.scr->w2p + (j1 * 24 + NS2 - 2) * 640;
        uint32_t d = sb + (NS2 - 2) * SLOT2;
        mbar_wait(bar + 8 * (B_FULL2 + 4), 0);
        asm volatile("fence.proxy.async.global;" ::: "memory");
#pragma unroll 1
        for (int s = NS2 - 2; s < 24; s++) {
          mbar_wait(bar + 8 * (s < NS2 ? B_FREE + s - 2 : B_REL2 + s - NS2 + 1), 0);
          const uint32_t mb = bar + 8 * (B_FULL2 + s);
          mbar_expect(mb, SLOT2);
          bulk_g2s(d, srcA, 16384, mb);
          bulk_g2s(d + 16384, srcB, 10240, mb);
          srcA += 1024; srcB += 640;
          d = d == sb + (NS2 - 1) * SLOT2 ? sb : d + SLOT2;
        }
      }
      __syncwarp();
    } else if (warp == 13) {
      if (elect1()) {
#pragma unroll 1
        for (int c = 2; c < 5; c++) mbar_wait(bar + 8 * (B_FREE + c), 0);
        publish(cnt + (C_S + (wid >> 4)) * 32);
        mbar_expect(bar + 8 * B_SFULL, 20480);
        poll_cnt(cnt + (C_S + j1) * 32, ep * 16);
        mbar_wait(bar + 8 * (B_REL2 + 24 - NS2), 0);
        bulk_g2s(sb + OFF_U, p.scr->sT + (j1 * 16 + rg1) * 1280, 20480, bar + 8 * B_SFULL);
      }
      __syncwarp();
    }
  }
}

typedef CUresult (*EncodeFn)(CUtensorMap*, CUtensorMapDataType, cuuint32_t, void*, const cuuint64_t*, const cuuint64_t*,
                             const cuuint32_t*, const cuuint32_t*, CUtensorMapInterleave, CUtensorMapSwizzle,
                             CUtensorMapL2promotion, CUtensorMapFloatOOBfill);

}

extern "C" void kernel_launch(void* const* d_in, const int* in_sizes, int n_in, void* d_out, int out_size) {
  static EncodeFn enc = nullptr;
  static int nsm = 0;
  static void* scr = nullptr;
  if (!enc) {
    void* fn = nullptr;
    cudaDriverEntryPointQueryResult qr;
    cudaGetDriverEntryPoint("cuTensorMapEncodeTiled", &fn, cudaEnableDefault, &qr);
    enc = (EncodeFn)fn;
    int dev = 0;
    cudaGetDevice(&dev);
    cudaDeviceGetAttribute(&nsm, cudaDevAttrMultiProcessorCount, dev);
    cudaFuncSetAttribute(fused_s4_ffn_kernel<true>, cudaFuncAttributeMaxDynamicSharedMemorySize, SMEM_BYTES);
    cudaFuncSetAttribute(fused_s4_ffn_kernel<false>, cudaFuncAttributeMaxDynamicSharedMemorySize, SMEM_BYTES);
    cudaGetSymbolAddress(&scr, g_scr);
  }
  Params p;
  p.x = (const __nv_bfloat16*)d_in[0];
  p.are = (const __nv_bfloat16*)d_in[1]; p.aim = (const __nv_bfloat16*)d_in[2];
  p.bre = (const __nv_bfloat16*)d_in[3]; p.bim = (const __nv_bfloat16*)d_in[4];
  p.cre = (const __nv_bfloat16*)d_in[5]; p.cim = (const __nv_bfloat16*)d_in[6];
  p.logdt = (const __nv_bfloat16*)d_in[7]; p.dskip = (const __nv_bfloat16*)d_in[8];
  p.w1 = (const __nv_bfloat16*)d_in[10]; p.w2 = (const __nv_bfloat16*)d_in[11];
  p.out = (__nv_bfloat16*)d_out;
  p.scr = (Scratch*)scr;
  CUtensorMap tmX, tmW1, tmU, tmW2;
  const cuuint32_t es[5] = {1, 1, 1, 1, 1};
  {
    const cuuint64_t gd[5] = {DM, 2, 4, 4, FF / 32}, gs[4] = {DM * 2, DM * 16, DM * 4, DM * 64};
    const cuuint32_t bx[5] = {88, 2, 4, 4, 3};
    enc(&tmW2, CU_TENSOR_MAP_DATA_TYPE_BFLOAT16, 5, d_in[11], gd, gs, bx, es, CU_TENSOR_MAP_INTERLEAVE_NONE,
        CU_TENSOR_MAP_SWIZZLE_NONE, CU_TENSOR_MAP_L2_PROMOTION_NONE, CU_TENSOR_MAP_FLOAT_OOB_FILL_NONE);
  }
  {
    const cuuint64_t gd[2] = {16 * DM, 128}, gs[1] = {DM * 32};
    const cuuint32_t bx[2] = {80, 144};
    enc(&tmU, CU_TENSOR_MAP_DATA_TYPE_FLOAT16, 2, p.scr->uT, gd, gs, bx, es, CU_TENSOR_MAP_INTERLEAVE_NONE,
        CU_TENSOR_MAP_SWIZZLE_NONE, CU_TENSOR_MAP_L2_PROMOTION_NONE, CU_TENSOR_MAP_FLOAT_OOB_FILL_NONE);
  }
  {
    const cuuint64_t gd[2] = {DM, SEQ}, gs[1] = {DM * 2};
    const cuuint32_t bx[2] = {64, 128};
    enc(&tmX, CU_TENSOR_MAP_DATA_TYPE_BFLOAT16, 2, d_in[0], gd, gs, bx, es, CU_TENSOR_MAP_INTERLEAVE_NONE,
        CU_TENSOR_MAP_SWIZZLE_128B, CU_TENSOR_MAP_L2_PROMOTION_L2_128B, CU_TENSOR_MAP_FLOAT_OOB_FILL_NONE);
  }
  {
    const cuuint64_t gd[3] = {64, DM, FF / 64}, gs[2] = {FF * 2, 128};
    const cuuint32_t bx[3] = {64, 64, 3};
    enc(&tmW1, CU_TENSOR_MAP_DATA_TYPE_BFLOAT16, 3, d_in[10], gd, gs, bx, es, CU_TENSOR_MAP_INTERLEAVE_NONE,
        CU_TENSOR_MAP_SWIZZLE_128B, CU_TENSOR_MAP_L2_PROMOTION_L2_128B, CU_TENSOR_MAP_FLOAT_OOB_FILL_NONE);
  }
  if (nsm == 132) fused_s4_ffn_kernel<true><<<132, 512, SMEM_BYTES>>>(p, tmX, tmW1, tmU, tmW2);
  else fused_s4_ffn_kernel<false><<<132, 512, SMEM_BYTES>>>(p, tmX, tmW1, tmU, tmW2);
}
```

```cpp
#include <cuda_runtime.h>
#include <cuda_bf16.h>
#include <cuda_fp16.h>
#include <cuda.h>
#include <stdint.h>

namespace {

constexpr int SEQ = 2048, DM = 640, FF = 1536;

constexpr int SLOT1 = 40960;
constexpr int SLOT2 = 26624;
constexpr int NS2 = 7;
#define GATE 1
#define SPARE_NS 700
#define DELAY_NS 0
#define PACE_NS 30
constexpr int OFF_Z = 85504, ZSZ = 20480;
constexpr int ZA3 = 0, ZB3 = 2048, ZS = 4096, ZA2 = 6144, ZB2 = 9216, ZA1 = 12288, ZB1 = 16384;
constexpr int OFF_W2S = OFF_Z + 4 * ZSZ;
constexpr int OFF_U = 190464;
constexpr int OFF_P = 210944;
constexpr int OFF_KS = 163840;
constexpr int OFF_LNP = 225280;
constexpr int OFF_MISC = 226304;
constexpr int OFF_CHC = OFF_MISC + 16;
constexpr int OFF_EP = OFF_MISC + 64;
constexpr int OFF_ZERO = OFF_MISC + 128;
constexpr int OFF_STAT = OFF_MISC + 1024;
constexpr int OFF_CS = OFF_MISC + 2048;
constexpr int OFF_BAR = OFF_MISC + 2816;
constexpr int SMEM_BYTES = OFF_MISC + 6144;
constexpr int P0 = 8, PA1 = 280, PB1 = 360, PA2 = 448, PB2 = 544, PA3 = 632, PB3 = 704;
enum { B_FULL1 = 0, B_FULL2 = 10, B_UFULL = 34, B_EPI = 35, B_SFULL = 36, B_W2 = 37,
       B_PAIR = 42,
       B_FREE = 48, B_PART = 54,
       B_REL1 = 60, B_REL2 = 70 };
enum { C_LN = 0, C_CS = 1, C_H0 = 2, C_H1 = 18, C_S = 34, C_W2 = 42, C_NUM = 43 };

struct Scratch {
  unsigned cnt[64 * 32];
  unsigned epoch[256];
  float2 stats[SEQ];
  float cs[FF];
  uint4 uT[DM * 256];
  uint4 w2p[8 * 24 * 640];
  uint4 sT[8 * 16 * 1280];
  uint4 h[16 * 24 * 1024];
};
__device__ __align__(1024) Scratch g_scr;
constexpr uint32_t sb = 1024;
constexpr uint32_t bar = sb + OFF_BAR;

struct Params {
  const __nv_bfloat16 *are, *aim, *bre, *bim, *cre, *cim, *logdt, *dskip, *x, *w1, *w2;
  __nv_bfloat16* out;
  Scratch* scr;
};

__device__ __forceinline__ void mbar_init(uint32_t a, int c) { asm volatile("mbarrier.init.shared::cta.b64 [%0], %1;" ::"r"(a), "r"(c)); }
__device__ __forceinline__ void mbar_expect(uint32_t a, int b) { asm volatile("mbarrier.arrive.expect_tx.shared::cta.b64 _, [%0], %1;" ::"r"(a), "r"(b) : "memory"); }
__device__ __forceinline__ void mbar_arrive(uint32_t a) { asm volatile("mbarrier.arrive.shared::cta.b64 _, [%0];" ::"r"(a) : "memory"); }
__device__ __forceinline__ void mbar_wait(uint32_t a, int ph) {
  asm volatile(
      "{\n.reg .pred p;\n.reg .u32 n;\n"
      "mbarrier.try_wait.parity.shared::cta.b64 p, [%0], %1;\n@p bra LD;\nmov.u32 n, 0;\n"
      "LW:\nmbarrier.try_wait.parity.shared::cta.b64 p, [%0], %1, 20000;\n@p bra LD;\n"
      "add.u32 n, n, 1;\nsetp.lt.u32 p, n, 100000;\n@p bra LW;\ntrap;\nLD:\n}\n" ::"r"(a), "r"(ph) : "memory");
}
__device__ __forceinline__ void poll_cnt(const unsigned* p, unsigned target) {
  asm volatile(
      "{\n.reg .pred p;\n.reg .u32 n;\n.reg .s32 v;\nmov.u32 n, 0;\n"
      "LW:\nld.relaxed.gpu.global.u32 v, [%0];\nsub.s32 v, v, %1;\nsetp.ge.s32 p, v, 0;\n@p bra LD;\n"
      "nanosleep.u32 64;\nadd.u32 n, n, 1;\nsetp.lt.u32 p, n, 4000000;\n@p bra LW;\ntrap;\n"
      "LD:\nfence.acquire.gpu;\nfence.proxy.async.global;\n}\n" ::"l"(p), "r"(target) : "memory");
}
__device__ __forceinline__ void publish(unsigned* p) {
  asm volatile("fence.proxy.async.global;\nfence.release.gpu;\nred.relaxed.gpu.global.add.u32 [%0], 1;" ::"l"(p) : "memory");
}
__device__ __forceinline__ uint32_t movm(uint32_t v) { uint32_t r; asm volatile("movmatrix.sync.aligned.m8n8.trans.b16 %0, %1;" : "=r"(r) : "r"(v)); return r; }
__device__ __forceinline__ void fence_async_smem() { asm volatile("fence.proxy.async.shared::cta;" ::: "memory"); }
__device__ __forceinline__ bool elect1() { uint32_t p; asm volatile("{\n.reg .pred P;\nelect.sync _|P, 0xffffffff;\nselp.u32 %0,1,0,P;\n}\n" : "=r"(p)); return p; }
__device__ __forceinline__ void bar_sync(int id, int n) { asm volatile("bar.sync %0, %1;" ::"r"(id), "r"(n) : "memory"); }
__device__ __forceinline__ void bar_arrive(int id, int n) { asm volatile("bar.arrive %0, %1;" ::"r"(id), "r"(n) : "memory"); }
__device__ __forceinline__ void bulk_g2s(uint32_t dst, const void* src, int bytes, uint32_t mb) {
  asm volatile("cp.async.bulk.shared::cluster.global.mbarrier::complete_tx::bytes [%0], [%1], %2, [%3];" ::"r"(dst), "l"(src), "r"(bytes), "r"(mb) : "memory");
}
__device__ __forceinline__ void bulk_prefetch(const void* src, int bytes) { asm volatile("cp.async.bulk.prefetch.L2.global [%0], %1;" ::"l"(src), "r"(bytes) : "memory"); }
__device__ __forceinline__ void tma2d(uint32_t dst, const CUtensorMap* m, int c0, int c1, uint32_t mb) {
  asm volatile("cp.async.bulk.tensor.2d.shared::cluster.global.mbarrier::complete_tx::bytes [%0], [%1, {%3, %4}], [%2];" ::"r"(dst), "l"(m), "r"(mb), "r"(c0), "r"(c1) : "memory");
}
__device__ __forceinline__ void tma3d(uint32_t dst, const CUtensorMap* m, int c0, int c1, int c2, uint32_t mb) {
  asm volatile("cp.async.bulk.tensor.3d.shared::cluster.global.mbarrier::complete_tx::bytes [%0], [%1, {%3, %4, %5}], [%2];" ::"r"(dst), "l"(m), "r"(mb), "r"(c0), "r"(c1), "r"(c2) : "memory");
}
__device__ __forceinline__ int frag_col(int l) {
  const int tl = l >> 3, i = l & 7;
  return (tl < 8 ? 32 * (tl >> 2) + 8 * (i >> 1) + 2 * (tl & 3) : 48 + 4 * (i >> 1) + 2 * tl) + (i & 1);
}
__device__ __forceinline__ void tma5d(uint32_t dst, const CUtensorMap* m, int c0, int c4, uint32_t mb) {
  asm volatile("cp.async.bulk.tensor.5d.shared::cluster.global.mbarrier::complete_tx::bytes [%0], [%1, {%3, %5, %5, %5, %4}], [%2];" ::"r"(dst), "l"(m), "r"(mb), "r"(c0), "r"(c4), "r"(0) : "memory");
}
__device__ __forceinline__ uint64_t dsc(uint32_t lo, uint32_t hi) { return ((uint64_t)hi << 32) | lo; }
__device__ __forceinline__ void wg_fence() { asm volatile("wgmma.fence.sync.aligned;" ::: "memory"); }
__device__ __forceinline__ void wg_commit() { asm volatile("wgmma.commit_group.sync.aligned;" ::: "memory"); }
template <int N> __device__ __forceinline__ void wg_wait() { asm volatile("wgmma.wait_group.sync.aligned %0;" ::"n"(N) : "memory"); }
__device__ __forceinline__ void wgmma_n192(float (&d)[96], uint64_t da, uint64_t db, int scale_d) {
  asm volatile("{\n.reg .pred p;\nsetp.ne.b32 p, %98, 0;\n"
    "wgmma.mma_async.sync.aligned.m64n192k16.f32.bf16.bf16 "
    "{"
    "%0, %1, %2, %3, %4, %5, %6, %7, %8, %9, %10, %11, %12, %13, %14, %15, "
    "%16, %17, %18, %19, %20, %21, %22, %23, %24, %25, %26, %27, %28, %29, %30, %31, "
    "%32, %33, %34, %35, %36, %37, %38, %39, %40, %41, %42, %43, %44, %45, %46, %47, "
    "%48, %49, %50, %51, %52, %53, %54, %55, %56, %57, %58, %59, %60, %61, %62, %63, "
    "%64, %65, %66, %67, %68, %69, %70, %71, %72, %73, %74, %75, %76, %77, %78, %79, "
    "%80, %81, %82, %83, %84, %85, %86, %87, %88, %89, %90, %91, %92, %93, %94, %95"
    "}, "
    "%96, %97, p, 1, 1, 0, 1;\n}\n"
    : "+f"(d[0]), "+f"(d[1]), "+f"(d[2]), "+f"(d[3]), "+f"(d[4]), "+f"(d[5]), "+f"(d[6]), "+f"(d[7]),
      "+f"(d[8]), "+f"(d[9]), "+f"(d[10]), "+f"(d[11]), "+f"(d[12]), "+f"(d[13]), "+f"(d[14]), "+f"(d[15]),
      "+f"(d[16]), "+f"(d[17]), "+f"(d[18]), "+f"(d[19]), "+f"(d[20]), "+f"(d[21]), "+f"(d[22]), "+f"(d[23]),
      "+f"(d[24]), "+f"(d[25]), "+f"(d[26]), "+f"(d[27]), "+f"(d[28]), "+f"(d[29]), "+f"(d[30]), "+f"(d[31]),
      "+f"(d[32]), "+f"(d[33]), "+f"(d[34]), "+f"(d[35]), "+f"(d[36]), "+f"(d[37]), "+f"(d[38]), "+f"(d[39]),
      "+f"(d[40]), "+f"(d[41]), "+f"(d[42]), "+f"(d[43]), "+f"(d[44]), "+f"(d[45]), "+f"(d[46]), "+f"(d[47]),
      "+f"(d[48]), "+f"(d[49]), "+f"(d[50]), "+f"(d[51]), "+f"(d[52]), "+f"(d[53]), "+f"(d[54]), "+f"(d[55]),
      "+f"(d[56]), "+f"(d[57]), "+f"(d[58]), "+f"(d[59]), "+f"(d[60]), "+f"(d[61]), "+f"(d[62]), "+f"(d[63]),
      "+f"(d[64]), "+f"(d[65]), "+f"(d[66]), "+f"(d[67]), "+f"(d[68]), "+f"(d[69]), "+f"(d[70]), "+f"(d[71]),
      "+f"(d[72]), "+f"(d[73]), "+f"(d[74]), "+f"(d[75]), "+f"(d[76]), "+f"(d[77]), "+f"(d[78]), "+f"(d[79]),
      "+f"(d[80]), "+f"(d[81]), "+f"(d[82]), "+f"(d[83]), "+f"(d[84]), "+f"(d[85]), "+f"(d[86]), "+f"(d[87]),
      "+f"(d[88]), "+f"(d[89]), "+f"(d[90]), "+f"(d[91]), "+f"(d[92]), "+f"(d[93]), "+f"(d[94]), "+f"(d[95])
    : "l"(da), "l"(db), "r"(scale_d));
}

__device__ __forceinline__ void wgmma_n80(float (&d)[40], uint64_t da, uint64_t db, int scale_d) {
  asm volatile("{\n.reg .pred p;\nsetp.ne.b32 p, %42, 0;\n"
    "wgmma.mma_async.sync.aligned.m64n80k16.f32.bf16.bf16 "
    "{"
    "%0, %1, %2, %3, %4, %5, %6, %7, %8, %9, %10, %11, %12, %13, %14, %15, "
    "%16, %17, %18, %19, %20, %21, %22, %23, %24, %25, %26, %27, %28, %29, %30, %31, "
    "%32, %33, %34, %35, %36, %37, %38, %39"
    "}, "
    "%40, %41, p, 1, 1, 0, 1;\n}\n"
    : "+f"(d[0]), "+f"(d[1]), "+f"(d[2]), "+f"(d[3]), "+f"(d[4]), "+f"(d[5]), "+f"(d[6]), "+f"(d[7]),
      "+f"(d[8]), "+f"(d[9]), "+f"(d[10]), "+f"(d[11]), "+f"(d[12]), "+f"(d[13]), "+f"(d[14]), "+f"(d[15]),
      "+f"(d[16]), "+f"(d[17]), "+f"(d[18]), "+f"(d[19]), "+f"(d[20]), "+f"(d[21]), "+f"(d[22]), "+f"(d[23]),
      "+f"(d[24]), "+f"(d[25]), "+f"(d[26]), "+f"(d[27]), "+f"(d[28]), "+f"(d[29]), "+f"(d[30]), "+f"(d[31]),
      "+f"(d[32]), "+f"(d[33]), "+f"(d[34]), "+f"(d[35]), "+f"(d[36]), "+f"(d[37]), "+f"(d[38]), "+f"(d[39])
    : "l"(da), "l"(db), "r"(scale_d));
}

__device__ __forceinline__ void hmma(float* c, uint32_t a0, uint32_t a1, uint32_t a2, uint32_t a3, uint32_t b0, uint32_t b1) {
  asm volatile("mma.sync.aligned.m16n8k16.row.col.f32.f16.f16.f32 {%0,%1,%2,%3}, {%4,%5,%6,%7}, {%8,%9}, {%0,%1,%2,%3};"
      : "+f"(c[0]), "+f"(c[1]), "+f"(c[2]), "+f"(c[3]) : "r"(a0), "r"(a1), "r"(a2), "r"(a3), "r"(b0), "r"(b1));
}
__device__ __forceinline__ void ldsm4(uint32_t* r, uint32_t a) { asm volatile("ldmatrix.sync.aligned.m8n8.x4.shared.b16 {%0,%1,%2,%3}, [%4];" : "=r"(r[0]), "=r"(r[1]), "=r"(r[2]), "=r"(r[3]) : "r"(a) : "memory"); }
__device__ __forceinline__ void ldsm4t(uint32_t* r, uint32_t a) { asm volatile("ldmatrix.sync.aligned.m8n8.x4.trans.shared.b16 {%0,%1,%2,%3}, [%4];" : "=r"(r[0]), "=r"(r[1]), "=r"(r[2]), "=r"(r[3]) : "r"(a) : "memory"); }
__device__ __forceinline__ void stsm4(uint32_t a, uint32_t r0, uint32_t r1, uint32_t r2, uint32_t r3) { asm volatile("stmatrix.sync.aligned.m8n8.x4.shared.b16 [%0], {%1,%2,%3,%4};" ::"r"(a), "r"(r0), "r"(r1), "r"(r2), "r"(r3) : "memory"); }
__device__ __forceinline__ void stsm4t(uint32_t a, uint32_t r0, uint32_t r1, uint32_t r2, uint32_t r3) { asm volatile("stmatrix.sync.aligned.m8n8.x4.trans.shared.b16 [%0], {%1,%2,%3,%4};" ::"r"(a), "r"(r0), "r"(r1), "r"(r2), "r"(r3) : "memory"); }
__device__ __forceinline__ uint32_t lds32(uint32_t a) { uint32_t v; asm volatile("ld.shared.u32 %0, [%1];" : "=r"(v) : "r"(a) : "memory"); return v; }
__device__ __forceinline__ uint2 lds64(uint32_t a) { uint2 v; asm volatile("ld.shared.v2.u32 {%0,%1}, [%2];" : "=r"(v.x), "=r"(v.y) : "r"(a) : "memory"); return v; }
__device__ __forceinline__ uint4 lds128(uint32_t a) { uint4 v; asm volatile("ld.shared.v4.u32 {%0,%1,%2,%3}, [%4];" : "=r"(v.x), "=r"(v.y), "=r"(v.z), "=r"(v.w) : "r"(a) : "memory"); return v; }
__device__ __forceinline__ void sts16(uint32_t a, uint32_t v) { asm volatile("st.shared.u16 [%0], %1;" ::"r"(a), "h"((unsigned short)v) : "memory"); }
__device__ __forceinline__ void sts32(uint32_t a, uint32_t v) { asm volatile("st.shared.u32 [%0], %1;" ::"r"(a), "r"(v) : "memory"); }
__device__ __forceinline__ void sts64(uint32_t a, uint32_t x, uint32_t y) { asm volatile("st.shared.v2.u32 [%0], {%1,%2};" ::"r"(a), "r"(x), "r"(y) : "memory"); }
__device__ __forceinline__ void sts128(uint32_t a, uint32_t x, uint32_t y, uint32_t z, uint32_t w) { asm volatile("st.shared.v4.u32 [%0], {%1,%2,%3,%4};" ::"r"(a), "r"(x), "r"(y), "r"(z), "r"(w) : "memory"); }
__device__ __forceinline__ float bflo(uint32_t v) { return __uint_as_float(v << 16); }
__device__ __forceinline__ float bfhi(uint32_t v) { return __uint_as_float(v & 0xffff0000u); }
__device__ __forceinline__ uint32_t pack_bf(float lo, float hi) { uint32_t r; asm("cvt.rn.bf16x2.f32 %0, %1, %2;" : "=r"(r) : "f"(hi), "f"(lo)); return r; }
__device__ __forceinline__ uint32_t pack_h(float lo, float hi) { uint32_t r; asm("cvt.rn.f16x2.f32 %0, %1, %2;" : "=r"(r) : "f"(hi), "f"(lo)); return r; }
__device__ __forceinline__ float rnd_bf(float v) { return __bfloat162float(__float2bfloat16_rn(v)); }
__device__ __forceinline__ float ex2a(float v) { float r; asm("ex2.approx.ftz.f32 %0, %1;" : "=f"(r) : "f"(v)); return r; }
__device__ __forceinline__ float tanha(float v) { float r; asm("tanh.approx.f32 %0, %1;" : "=f"(r) : "f"(v)); return r; }
__device__ __forceinline__ uint32_t hadd(uint32_t a, uint32_t b) { uint32_t r; asm("add.rn.f16x2 %0, %1, %2;" : "=r"(r) : "r"(a), "r"(b)); return r; }
__device__ __forceinline__ uint32_t badd(uint32_t a, uint32_t b) { uint32_t r; asm("add.rn.bf16x2 %0, %1, %2;" : "=r"(r) : "r"(a), "r"(b)); return r; }
__device__ __forceinline__ uint32_t bmul(uint32_t a, uint32_t b) { uint32_t r; asm("mul.rn.bf16x2 %0, %1, %2;" : "=r"(r) : "r"(a), "r"(b)); return r; }
__device__ __forceinline__ uint32_t bsub(uint32_t a, uint32_t b) { uint32_t r; asm("sub.rn.bf16x2 %0, %1, %2;" : "=r"(r) : "r"(a), "r"(b)); return r; }
__device__ __forceinline__ uint32_t dup(uint32_t v, uint32_t nz) { uint32_t r; asm volatile("add.rn.f32 %0, %1, %2;" : "=r"(r) : "r"(v), "r"(nz)); return r; }
__device__ __forceinline__ void bmma(float* c, uint32_t a0, uint32_t a1, uint32_t a2, uint32_t a3, uint32_t b0, uint32_t b1) {
  asm("mma.sync.aligned.m16n8k16.row.col.f32.bf16.bf16.f32 {%0,%1,%2,%3}, {%4,%5,%6,%7}, {%8,%9}, {%0,%1,%2,%3};"
      : "+f"(c[0]), "+f"(c[1]), "+f"(c[2]), "+f"(c[3]) : "r"(a0), "r"(a1), "r"(a2), "r"(a3), "r"(b0), "r"(b1));
}
__device__ __forceinline__ uint32_t odd_pair(uint32_t a, uint32_t b) { return __byte_perm(a, b, 0x5432); }
__device__ __forceinline__ int upos(int c) { return c ^ ((c >> 5) & 7) ^ ((c >> 3) & 1); }
__device__ __forceinline__ int uoff(int pos) { return (pos >> 1) * 160 + (pos & 1) * 16; }

struct cf { float r, i; };
__device__ __forceinline__ cf cmul(cf a, cf b) { cf o; o.r = fmaf(a.r, b.r, -a.i * b.i); o.i = fmaf(a.r, b.i, a.i * b.r); return o; }
__device__ __forceinline__ cf cmulj(cf a, cf b) { cf o; o.r = fmaf(a.r, b.r, a.i * b.i); o.i = fmaf(a.i, b.r, -a.r * b.i); return o; }
__device__ __forceinline__ cf csq(cf a) { cf o; o.r = fmaf(a.r, a.r, -a.i * a.i); o.i = (a.r + a.r) * a.i; return o; }
struct hp { uint32_t r, i; };
__device__ __forceinline__ hp hpack(cf a, cf b) { hp o; o.r = pack_h(a.r, b.r); o.i = pack_h(a.i, b.i); return o; }
__device__ __forceinline__ hp hmulc(hp a, uint32_t c) {
  __half2 ar = *reinterpret_cast<__half2*>(&a.r), ai = *reinterpret_cast<__half2*>(&a.i), cc = *reinterpret_cast<__half2*>(&c);
  __half2 orr = __hfma2(ar, __low2half2(cc), __hneg2(__hmul2(ai, __high2half2(cc))));
  __half2 oi = __hfma2(ar, __high2half2(cc), __hmul2(ai, __low2half2(cc)));
  hp o; o.r = *reinterpret_cast<uint32_t*>(&orr); o.i = *reinterpret_cast<uint32_t*>(&oi); return o;
}
__device__ __forceinline__ hp hmulj(hp a, uint32_t c) {
  __half2 ar = *reinterpret_cast<__half2*>(&a.r), ai = *reinterpret_cast<__half2*>(&a.i), cc = *reinterpret_cast<__half2*>(&c);
  __half2 orr = __hfma2(ar, __low2half2(cc), __hmul2(ai, __high2half2(cc)));
  __half2 oi = __hfma2(ai, __low2half2(cc), __hneg2(__hmul2(ar, __high2half2(cc))));
  hp o; o.r = *reinterpret_cast<uint32_t*>(&orr); o.i = *reinterpret_cast<uint32_t*>(&oi); return o;
}
__device__ __forceinline__ void sts_tile(uint32_t a, const hp* t) {
  sts128(a, t[0].r, t[1].r, t[2].r, t[3].r);
  sts128(a + 512, t[0].i, t[1].i, t[2].i, t[3].i);
}
template <int STEP> __device__ __forceinline__ void put2(uint32_t a0, uint32_t a1, uint32_t h, uint32_t sel) {
  const uint32_t x = __byte_perm(h, h, sel), y = x >> 16;
  sts16(a0, x); sts16(a0 + STEP * 4 + 2, x);
  sts16(a1, y); sts16(a1 + STEP * 4 + 2, y);
}

__device__ __forceinline__ void spare_work(const Params& p, const CUtensorMap* tmW1, int k, int tid) {
  const int lane = tid & 31;
  unsigned ep = 0;
  if (tid >= 480) ep = p.scr->epoch[128 + k] + 1;
  if (tid == 480) {
    for (int i = 0; i < 8; i++) mbar_init(bar + 8 * i, i < 4 ? 1 : 12);
    asm volatile("fence.mbarrier_init.release.cluster;" ::: "memory");
    fence_async_smem();
  }
  __syncthreads();
  float a[2][4] = {{0.f, 0.f, 0.f, 0.f}, {0.f, 0.f, 0.f, 0.f}};
  if (tid >= 480) {
    if (elect1()) {
      if (SPARE_NS) __nanosleep(SPARE_NS);
#pragma unroll 1
      for (int s = 0; s < 10; s++) {
        mbar_wait(bar + 8 * (4 + (s & 3)), ((s >> 2) & 1) ^ 1);
        mbar_expect(bar + 8 * (s & 3), 49152);
#pragma unroll 1
        for (int b = 0; b < 2; b++) tma3d(sb + (s & 3) * 49152 + b * 24576, tmW1, 0, s * 64, k * 6 + b * 3, bar + 8 * (s & 3));
      }
    }
    __syncwarp();
  } else if (tid < 384) {
    const uint32_t idn = (lane >> 3) == (lane & 3) ? ((lane & 4) ? 0x3f800000u : 0x3f80u) : 0u;
#pragma unroll 1
    for (int s = 0; s < 10; s++) {
      mbar_wait(bar + 8 * (s & 3), (s >> 2) & 1);
      const uint32_t ad = sb + (s & 3) * 49152 + (tid >> 6) * 8192 + (tid & 63) * 16;
#pragma unroll
      for (int i = 0; i < 8; i += 2) {
        const uint4 v = lds128(ad + i * 1024), w = lds128(ad + i * 1024 + 1024);
        bmma(a[0], v.x, v.y, w.x, w.y, idn, idn);
        bmma(a[1], v.z, v.w, w.z, w.w, idn, idn);
      }
      __syncwarp();
      if (lane == 0) mbar_arrive(bar + 8 * (4 + (s & 3)));
    }
    const int rho = (tid >> 3) & 7;
    const uint32_t ad = sb + 196608 + rho * 1536 + ((tid >> 6) * 8 + ((tid & 7) ^ rho)) * 32;
    sts128(ad, __float_as_uint(a[0][0]), __float_as_uint(a[0][1]), __float_as_uint(a[0][2]), __float_as_uint(a[0][3]));
    sts128(ad + 16, __float_as_uint(a[1][0]), __float_as_uint(a[1][1]), __float_as_uint(a[1][2]), __float_as_uint(a[1][3]));
  }
  __syncthreads();
  if (tid < 384) {
    float s = 0.f;
#pragma unroll
    for (int r = 0; r < 8; r++) s += __uint_as_float(lds32(sb + 196608 + r * 1536 + tid * 4));
    p.scr->cs[k * 384 + tid] = s;
  }
  __syncthreads();
  if (tid == 480) {
    publish(p.scr->cnt + C_CS * 32);
    p.scr->epoch[128 + k] = ep;
    poll_cnt(p.scr->cnt + C_LN * 32, ep * 128);
  }
}

__device__ __forceinline__ void load1(int s, const CUtensorMap* tmX, const CUtensorMap* tmW1, int rg1, int j1) {
  const uint32_t d = sb + (s & 3) * SLOT1, mb = bar + 8 * (B_FULL1 + s);
  mbar_expect(mb, SLOT1);
  tma2d(d, tmX, s * 64, rg1 * 128, mb);
  tma3d(d + 16384, tmW1, 0, s * 64, j1 * 3, mb);
}
__device__ __forceinline__ void load_x(uint32_t (&xv)[2][10], const __nv_bfloat16* xc, int rstep, int q) {
#pragma unroll
  for (int r = 0; r < 2; r++) {
    const uint4 a = __ldg((const uint4*)(xc + r * rstep) + q), b = __ldg((const uint4*)(xc + r * rstep) + 4 + q);
    const uint2 c = __ldg((const uint2*)(xc + r * rstep + 64) + q);
    xv[r][0] = a.x; xv[r][1] = a.y; xv[r][2] = a.z; xv[r][3] = a.w; xv[r][4] = b.x; xv[r][5] = b.y; xv[r][6] = b.z; xv[r][7] = b.w;
    xv[r][8] = c.x; xv[r][9] = c.y;
  }
}

__device__ __forceinline__ uint32_t pin(uint32_t v, uint32_t z) { uint32_t r; asm volatile("add.u32 %0, %1, %2;" : "=r"(r) : "r"(v), "r"(z)); return r; }
struct Comb { uint32_t o[7]; };
__device__ __forceinline__ Comb comb_setup(int tid, uint32_t z) {
  Comb k;
  const int c = tid & 127, c1 = c < 112 ? c + 32 : c - 112, c2 = c < 112 ? c + 144 : c - 96;
  const uint32_t zr = ZA1 + (c & 7) * 16, a2 = ZA2 + ((c & ~15) - 32 + ((((c >> 1) & 7) + (c & 1) * 8) ^ ((c & 1) * 4))) * 16;
  k.o[0] = uoff(upos(c1)); k.o[1] = uoff(upos(c2));
  k.o[2] = c < 112 ? ZA1 + 512 + ((2 * c) ^ ((c >> 2) & 1)) * 16 : zr;
  k.o[3] = c1 >= 64 ? a2 : zr; k.o[4] = c < 112 ? a2 + 112 * 16 : zr;
  k.o[5] = ((c1 >> 4) * 1280 + (c & 15)) * 16; k.o[6] = ((c2 >> 4) * 1280 + (c & 15)) * 16;
#pragma unroll
  for (int i = 0; i < 7; i++) k.o[i] = pin(k.o[i], z);
  return k;
}
__device__ __forceinline__ void combine(const Comb& k, int ch, int wid, uint4* sT) {
  const uint32_t ub = sb + OFF_U + ch * 32, zb = sb + OFF_Z + ch * ZSZ;
  const int row = (wid & 15) * 5 + ch;
  char* dst = (char*)(sT + ((wid >> 4) * 16 * 80 + row) * 16);
  mbar_wait(bar + 8 * (B_PART + ch), 0);
  const uint32_t sc = lds32(sb + OFF_CHC + ch * 8);
  const uint4 y0 = lds128(zb + k.o[2]), y1 = lds128(zb + (k.o[2] ^ 16));
  const uint4 v2 = lds128(zb + k.o[3]), u2 = lds128(zb + k.o[4]);
  const uint4 v0 = lds128(ub + k.o[0]), u0 = lds128(ub + k.o[1]);
  fence_async_smem();
  *(uint4*)(dst + (k.o[5] ^ ((row & 7) * 16))) =
      make_uint4(bmul(badd(badd(y0.x, v2.x), v0.x), sc), bmul(badd(badd(y0.y, v2.y), v0.y), sc),
                 bmul(badd(badd(y1.x, v2.z), v0.z), sc), bmul(badd(badd(y1.y, v2.w), v0.w), sc));
  *(uint4*)(dst + (k.o[6] ^ ((row & 7) * 16))) =
      make_uint4(bmul(badd(badd(y0.z, u2.x), u0.x), sc), bmul(badd(badd(y0.w, u2.y), u0.y), sc),
                 bmul(badd(badd(y1.z, u2.z), u0.z), sc), bmul(badd(badd(y1.w, u2.w), u0.w), sc));
  __syncwarp();
  if (elect1()) mbar_arrive(bar + 8 * (B_FREE + ch));
}

template <bool USE_SMID>
__global__ void __launch_bounds__(512, 1)
fused_s4_ffn_kernel(const Params p, const __grid_constant__ CUtensorMap tmX, const __grid_constant__ CUtensorMap tmW1,
                    const __grid_constant__ CUtensorMap tmU, const __grid_constant__ CUtensorMap tmW2) {
  extern __shared__ __align__(1024) unsigned char smem_raw[];
  const int tid = threadIdx.x, lane = tid & 31;
  const int warp = __shfl_sync(0xffffffffu, tid >> 5, 0);
  const int g = lane >> 2, q = lane & 3;
  uint32_t sid;
  if (USE_SMID) asm("mov.u32 %0, %smid;" : "=r"(sid)); else sid = blockIdx.x;
  if (sid - 120u < 4u) { spare_work(p, &tmW1, sid - 120, tid); return; }
  const int wid = sid < 120 ? sid : sid - 4;
  unsigned* const cnt = p.scr->cnt;

  float kacc[5][4];
  const int kpart = (warp >= 5) + (warp >= 10), kch = warp - 5 * kpart;
  float dt, k0;
  uint32_t xv[2][10], xs[2], mw, pds;
  {
    uint32_t pa[6], pld;
    unsigned ep0;
    if (warp < 15) {
      const int ch = (wid >> 4) * 80 + frag_col((wid & 15) * 5 + kch);
      const int o = (ch * 3 + kpart) * 32 + lane;
      pa[0] = __ldg((const uint32_t*)p.are + o); pa[1] = __ldg((const uint32_t*)p.aim + o);
      pa[2] = __ldg((const uint32_t*)p.bre + o); pa[3] = __ldg((const uint32_t*)p.bim + o);
      pa[4] = __ldg((const uint32_t*)p.cre + o); pa[5] = __ldg((const uint32_t*)p.cim + o);
      pld = __ldg((const unsigned short*)p.logdt + ch);
      pds = __ldg((const unsigned short*)p.dskip + ch);
    } else {
      ep0 = p.scr->epoch[wid];
      if ((uint32_t)__cvta_generic_to_shared(smem_raw) != sb) __trap();
    }
    if (elect1()) {
      const int gi = (warp + 1) & 15;
#pragma unroll
      for (int i = 0; i < 6; i++) mbar_init(bar + 48 * gi + 8 * i, gi < 7 ? 1 : gi == 7 ? 2 : gi < 10 ? 4 : 8);
      asm volatile("fence.mbarrier_init.release.cluster;" ::: "memory");
    }
    if (warp == 15) {
      sts32(sb + OFF_ZERO + lane * 4, 0);
      int gpc, i;
      if (sid < 64) { gpc = (sid & 15) >> 1; i = sid >> 4; }
      else if (sid < 120) { const int t = sid - 64; i = t / 14; gpc = 1 + ((t - i * 14) >> 1); i += 4; }
      else { gpc = 0; i = 4 + ((sid - 124) >> 1); }
      const int qi = ((0x52741630 >> (4 * i)) & 7) * 2 + (sid & 1);
      const int rg = 4 * (gpc >> 1) + (qi >> 2), jc = 4 * (gpc & 1) + (qi & 3);
      sts64(sb + OFF_EP + 8, rg, jc);
      __syncwarp();
      if (GATE) bar_sync(5, 512);
      if (elect1()) {
        if (DELAY_NS) __nanosleep(DELAY_NS);
        bulk_prefetch(p.x + wid * 16 * DM, 16 * DM * 2);
#pragma unroll 1
        for (int s = 0; s < 4; s++) load1(s, &tmX, &tmW1, rg, jc);
        bulk_prefetch(p.w1 + wid * 5 * FF, 5 * FF * 2);
        bulk_prefetch(p.w2 + wid * 12 * DM, 12 * DM * 2);
        asm volatile("prefetch.tensormap [%0];\nprefetch.tensormap [%1];" ::"l"(&tmU), "l"(&tmW2) : "memory");
      }
    }
#pragma unroll
    for (int j = 0; j < 5; j++) { kacc[j][0] = kacc[j][1] = kacc[j][2] = kacc[j][3] = 0.f; }
    float zr, th, zr1, th1;
    cf c, c1;
    const uint32_t ks = sb + OFF_KS + warp * 4096;
    if (warp < 15) {
      dt = rnd_bf(expf(bflo(pld)));
      c = cmul(cf{bflo(pa[4]), bflo(pa[5])}, cf{bflo(pa[2]), bflo(pa[3])});
      c1 = cmul(cf{bfhi(pa[4]), bfhi(pa[5])}, cf{bfhi(pa[2]), bfhi(pa[3])});
      mw = __reduce_max_sync(0xffffffffu, __float_as_uint(fmaxf(fmaxf(fabsf(c.r), fabsf(c.i)), fmaxf(fabsf(c1.r), fabsf(c1.i)))));
      if (GATE) bar_arrive(5, 512);
      mw = min(max(mw & 0x7f800000u, 20u << 23), 240u << 23);
      const float sc = __uint_as_float((259u << 23) - mw), dl2 = dt * 1.4426950408889634f;
      k0 = c.r + c1.r;
      zr = bflo(pa[0]) * dl2; th = bflo(pa[1]) * dt; zr1 = bfhi(pa[0]) * dl2; th1 = bfhi(pa[1]) * dt;
      c.r *= sc; c.i *= -sc; c1.r *= sc; c1.i *= -sc;
    }
    __syncwarp();
    if (warp >= 8) {
      const __nv_bfloat16* xr = p.x + (wid * 16 + ((g >> 1) << 2) + (g & 1)) * DM;
      load_x(xv, xr + (warp - 8) * 80, 2 * DM, q);
      xs[0] = __ldg((const uint32_t*)xr); xs[1] = __ldg((const uint32_t*)(xr + 2 * DM));
    }
    {
      const uint32_t ka = ks + (lane >> 3) * 512 + (lane & 7) * 16;
      const uint32_t kb = ks + ((lane >> 3) & 1) * 512 + ((lane >> 4) * 8 + (lane & 7)) * 16;
#pragma unroll 1
      for (int it = 0; it < 2; it++) {
        if (it == 1 && warp >= 8) {
          float sm[4] = {0.f, 0.f, 0.f, 0.f}, g0[4] = {0.f, 0.f, 0.f, 0.f}, g1[4] = {0.f, 0.f, 0.f, 0.f};
#pragma unroll
          for (int r = 0; r < 2; r++)
            xs[r] = fabsf(bflo(xs[r]) - bfhi(xs[r])) * 8.f < fabsf(bflo(xs[r])) ? __byte_perm(xs[r], 0, 0x1010) : 0u;
#pragma unroll
          for (int i = 0; i < 10; i += 2) {
            const uint32_t a0 = bsub(xv[0][i], xs[0]), a1 = bsub(xv[1][i], xs[1]), a2 = bsub(xv[0][i + 1], xs[0]), a3 = bsub(xv[1][i + 1], xs[1]);
            bmma(sm, a0, a1, a2, a3, 0x3f803f80u, 0x3f803f80u);
            bmma(g0, a0, a1, a2, a3, xv[0][i], xv[0][i + 1]);
            bmma(g1, a0, a1, a2, a3, xv[1][i], xv[1][i + 1]);
          }
          if (q == (g >> 1))
            sts128(sb + OFF_LNP + (warp - 8) * 128 + g * 16, __float_as_uint(sm[0]), __float_as_uint((g & 1) ? g0[1] : g0[0]),
                   __float_as_uint(sm[2]), __float_as_uint((g & 1) ? g1[3] : g1[2]));
          if (warp < 15) bar_arrive(1, 256);
        }
        if (warp == 15) continue;
        float m = ex2a(zr);
        const cf w1 = cf{m * __cosf(th), m * __sinf(th)};
        m = ex2a(zr * 8.f);
        const cf w8 = cf{m * __cosf(th * 8.f), m * __sinf(th * 8.f)};
        const cf w16 = csq(w8), w32 = csq(w16), w64 = csq(w32), w128 = csq(w64), w256 = csq(w128), w512 = csq(w256), w1024 = csq(w512);
        hp lo[8];
        lo[0] = hpack(cf{1.f, 0.f}, w8);
        lo[1] = hmulc(lo[0], pack_h(w16.r, w16.i));
        { const uint32_t k = pack_h(w32.r, w32.i); lo[2] = hmulc(lo[0], k); lo[3] = hmulc(lo[1], k); }
        { const uint32_t k = pack_h(w64.r, w64.i);
#pragma unroll
          for (int i = 0; i < 4; i++) lo[4 + i] = hmulc(lo[i], k); }
        const uint32_t st = ks + lane * 16;
        sts128(st + 512, lo[4].r, lo[5].r, lo[6].r, lo[7].r);
        sts128(st + 1536, lo[4].i, lo[5].i, lo[6].i, lo[7].i);
        sts128(st, lo[0].r, lo[1].r, lo[2].r, lo[3].r);
        sts128(st + 1024, lo[0].i, lo[1].i, lo[2].i, lo[3].i);
        const uint32_t k128 = pack_h(w128.r, w128.i), k256 = pack_h(w256.r, w256.i), k512 = pack_h(w512.r, w512.i);
        const cf t8 = cmulj(c, w8);
        hp T0[4], T1[4], T2[4], T3[4], T4[4];
        { const cf u0 = cmulj(t8, w1024), u1 = cmulj(u0, w128);
          T4[0] = hpack(u0, u1); T4[1] = hmulj(T4[0], k256); T4[2] = hmulj(T4[0], k512); T4[3] = hmulj(T4[1], k512); }
        sts_tile(st + 2048, T4);
        __syncwarp();
        uint32_t af[4][4];
#pragma unroll
        for (int mg = 0; mg < 4; mg++) ldsm4t(af[mg], ka + mg * 128);
#pragma unroll
        for (int mg = 0; mg < 4; mg += 2) {
          uint32_t b[4];
          ldsm4t(b, kb + 2048 + mg * 128);
          hmma(kacc[4], af[mg][0], af[mg][1], af[mg][2], af[mg][3], b[0], b[1]);
          hmma(kacc[4], af[mg + 1][0], af[mg + 1][1], af[mg + 1][2], af[mg + 1][3], b[2], b[3]);
        }
        const cf t1 = cmulj(c, w1), t2 = cmulj(t1, w1), t3 = cmulj(t2, w1), t4 = cmulj(t3, w1);
        const cf t5 = cmulj(t4, w1), t6 = cmulj(t5, w1), t7 = cmulj(t6, w1);
        T0[0] = hpack(t4, t8); T0[1] = hpack(t2, t6); T0[2] = hpack(t1, t5); T0[3] = hpack(t3, t7);
#pragma unroll
        for (int i = 0; i < 4; i++) T1[i] = hmulj(T0[i], k128);
        T2[0] = hmulj(T0[0], k256); T2[1] = hmulj(T0[1], k256); T2[2] = hmulj(T1[0], k256); T2[3] = hmulj(T1[1], k256);
        T3[0] = hmulj(T0[0], k512); T3[1] = hmulj(T1[0], k512); T3[2] = hmulj(T2[0], k512); T3[3] = hmulj(T2[2], k512);
        __syncwarp();
        sts_tile(st + 3072, T3);
        sts_tile(st + 2048, T2);
        sts_tile(st + 1024, T1);
        sts_tile(st, T0);
        __syncwarp();
#pragma unroll
        for (int mg = 0; mg < 4; mg += 2)
#pragma unroll
          for (int j = 3; j >= 0; j--) {
            uint32_t b[4];
            ldsm4t(b, kb + j * 1024 + mg * 128);
            hmma(kacc[j], af[mg][0], af[mg][1], af[mg][2], af[mg][3], b[0], b[1]);
            hmma(kacc[j], af[mg + 1][0], af[mg + 1][1], af[mg + 1][2], af[mg + 1][3], b[2], b[3]);
          }
        __syncwarp();
        zr = zr1; th = th1; c = c1;
      }
    }
    if (warp < 10) {
#pragma unroll
      for (int j = 0; j < 5; j++)
        sts128(ks + j * 512 + lane * 16, __float_as_uint(kacc[j][0]), __float_as_uint(kacc[j][1]), __float_as_uint(kacc[j][2]), __float_as_uint(kacc[j][3]));
      sts64(ks + 2560 + lane * 8, __float_as_uint(k0), mw);
    } else if (warp == 15) {
      if (lane == 0) { p.scr->epoch[wid] = ep0 + 1; sts32(sb + OFF_EP, ep0 + 1); }
      bar_sync(1, 256);
      float s1 = 0.f, s2 = 0.f;
#pragma unroll
      for (int w = 0; w < 8; w++) {
        const uint2 v = lds64(sb + OFF_LNP + w * 128 + g * 16 + (q & 1) * 8);
        s1 += __uint_as_float(v.x); s2 += __uint_as_float(v.y);
      }
      const float md = s1 * (1.f / DM), mean = bflo((q & 1) ? xs[1] : xs[0]) + md;
      const float var = fmaxf(fmaf(-md, mean, s2 * (1.f / DM)), 0.f);
      const float m = rnd_bf(mean);
      float sd, ri;
      asm("sqrt.approx.f32 %0, %1;" : "=f"(sd) : "f"(rnd_bf(rnd_bf(var) + 1e-5f)));
      asm("rcp.approx.f32 %0, %1;" : "=f"(ri) : "f"(rnd_bf(sd)));
      if (q < 2) {
        p.scr->stats[wid * 16 + ((g >> 1) << 2) + (g & 1) + 2 * q] = make_float2(-m, 0.5f * ri);
        sts64(sb + OFF_STAT + g * 16 + q * 8, __float_as_uint(-m * ri), __float_as_uint(ri));
      }
    }
  }
  __syncthreads();

  if (warp < 8) {
    float acc[96];
    const uint32_t alo = ((sb >> 4) | (1 << 16)) + (warp >> 2) * 512;
#pragma unroll 1
    for (int s = 0; s < 10; s++) {
      const uint32_t so = (s & 3) * (SLOT1 >> 4);
      mbar_wait(bar + 8 * (B_FULL1 + s), 0);
      wg_fence();
#pragma unroll
      for (int kk = 0; kk < 4; kk++)
        wgmma_n192(acc, dsc(alo + so + kk * 2, 0x40000040u), dsc((((sb + 16384) >> 4) | (512 << 16)) + so + kk * 128, 0x40000040u), (s | kk) != 0);
      wg_commit();
      wg_wait<1>();
      if (lane == 0) mbar_arrive(bar + 8 * (B_REL1 + s));
    }
    wg_wait<0>();
    bar_arrive(14, 384);
    bar_arrive(7, 384);
    mbar_wait(bar + 8 * B_EPI, 0);
    const uint2 s0 = lds64(sb + OFF_STAT + (warp * 16 + g) * 8), s1 = lds64(sb + OFF_STAT + (warp * 16 + g + 8) * 8);
    const float nm0 = __uint_as_float(s0.x), r0 = __uint_as_float(s0.y), nm1 = __uint_as_float(s1.x), r1 = __uint_as_float(s1.y);
    const uint4 erj = lds128(sb + OFF_EP);
    const unsigned ep = erj.x;
    const int rg1 = erj.z, j1 = erj.w;
    uint4* hd = p.scr->h + (rg1 * 24 + j1) * 1024 + warp * 128 + q * 8 + g;
#pragma unroll
    for (int grp = 0; grp < 6; grp++) {
      uint32_t o0[4], o1[4];
#pragma unroll
      for (int tl = 0; tl < 4; tl++) {
        const int nt = grp * 4 + tl;
        const uint2 cs = lds64(sb + OFF_CS + (nt * 8 + 2 * q) * 4);
        const float ca = __uint_as_float(cs.x), cb = __uint_as_float(cs.y);
        const float a = fmaf(nm0, ca, acc[4 * nt]) * r0, b = fmaf(nm0, cb, acc[4 * nt + 1]) * r0;
        const float c = fmaf(nm1, ca, acc[4 * nt + 2]) * r1, d = fmaf(nm1, cb, acc[4 * nt + 3]) * r1;
        o0[tl] = pack_bf(fmaf(a, tanha(a), a), fmaf(b, tanha(b), b));
        o1[tl] = pack_bf(fmaf(c, tanha(c), c), fmaf(d, tanha(d), d));
      }
      uint4* dst = hd + (grp >> 1) * 8192 + (grp & 1) * 32;
      dst[0] = make_uint4(o0[0], o0[1], o0[2], o0[3]);
      dst[64] = make_uint4(o1[0], o1[1], o1[2], o1[3]);
      if (PACE_NS) __nanosleep(PACE_NS);
      if (grp == 1) {
        if (warp == 7) { bar_sync(2, 448); if (lane == 0) publish(cnt + C_H0 * 32); __syncwarp(); }
        else bar_arrive(2, 448);
      }
    }
    if (warp == 6) { bar_sync(11, 256); if (lane == 0) publish(cnt + (C_H1 + rg1) * 32); __syncwarp(); }
    else bar_arrive(11, 256);
    const int go = (rg1 * 128 + warp * 16 + g) * DM + j1 * 80;
    load_x(xv, p.x + go, 8 * DM, q);
    if (warp < 4) {
      const Comb cmb = comb_setup(tid, 0);
#pragma unroll 1
      for (int ch = 0; ch < 3; ch++) {
        combine(cmb, ch, wid, p.scr->sT);
      }
    } else if (warp == 4) {
      if (elect1()) {
        poll_cnt(cnt + C_H0 * 32, ep * 128);
#pragma unroll 1
        for (int s = 0; s < NS2 - 2; s++) {
          if (s == 3) poll_cnt(cnt + (C_H1 + rg1) * 32, ep * 8);
          if (s == 3) mbar_wait(bar + 8 * B_FREE, 0);
          if (s >= 3) mbar_wait(bar + 8 * (B_FREE + s - 2), 0);
          const uint32_t mb = bar + 8 * (B_FULL2 + s);
          mbar_expect(mb, SLOT2);
          bulk_g2s(sb + s * SLOT2, p.scr->h + (rg1 * 24 + s) * 1024, 16384, mb);
          bulk_g2s(sb + s * SLOT2 + 16384, p.scr->w2p + (j1 * 24 + s) * 640, 10240, mb);
        }
      }
      __syncwarp();
    }
    float acc2[40];
    bar_sync(8, 512);
    {
      const uint32_t al2 = ((sb >> 4) | (8 << 16)) + (warp >> 2) * 512;
      uint32_t so = 0;
#pragma unroll 1
      for (int s = 0; s < 24; s++) {
        mbar_wait(bar + 8 * (B_FULL2 + s), 0);
        wg_fence();
#pragma unroll
        for (int kk = 0; kk < 4; kk++)
          wgmma_n80(acc2, dsc(al2 + so + kk * 16, 64), dsc((((sb + 16384) >> 4) | (80 << 16)) + so + kk * 160, 8), (s | kk) != 0);
        wg_commit();
        so = so == (NS2 - 1) * (SLOT2 >> 4) ? 0 : so + (SLOT2 >> 4);
        wg_wait<1>();
        if (lane == 0) mbar_arrive(bar + 8 * (B_REL2 + s));
      }
    }
    mbar_wait(bar + 8 * B_SFULL, 0);
    uint32_t sv[5][4];
    {
      const int i = lane & 7, mi = lane >> 3;
      const uint32_t a = sb + OFF_U + ((mi >> 1) * 8 + i) * 256 + (((2 * warp + (mi & 1)) ^ i) << 4);
#pragma unroll
      for (int k = 0; k < 5; k++) ldsm4t(sv[k], a + k * 4096);
    }
    wg_wait<0>();
#pragma unroll
    for (int hh = 0; hh < 2; hh++) {
      uint32_t o[10];
#pragma unroll
      for (int tl = 0; tl < 10; tl++) {
        const uint32_t xw = xv[hh][tl];
        const uint32_t sw = sv[tl >> 1][(tl & 1) * 2 + hh];
        const float a = acc2[4 * tl + 2 * hh], b = acc2[4 * tl + 2 * hh + 1];
        o[tl] = pack_bf(fmaf(bflo(sw), fmaf(a, tanha(a), a), bflo(xw)), fmaf(bfhi(sw), fmaf(b, tanha(b), b), bfhi(xw)));
      }
      __nv_bfloat16* op = p.out + go + hh * 8 * DM;
      ((uint4*)op)[q] = make_uint4(o[0], o[1], o[2], o[3]);
      ((uint4*)op)[4 + q] = make_uint4(o[4], o[5], o[6], o[7]);
      ((uint2*)(op + 64))[q] = make_uint2(o[8], o[9]);
    }
  } else {
    const int cw = warp - 8;
    const uint4 erj = lds128(sb + OFF_EP);
    const unsigned ep = erj.x;
    const int rg1 = erj.z, j1 = erj.w;
    {
      const uint4 st = lds128(sb + OFF_STAT + g * 16);
      const float n0 = __uint_as_float(st.x), r0 = __uint_as_float(st.y), n1 = __uint_as_float(st.z), r1 = __uint_as_float(st.w);
      const int up = upos(2 * wid);
      uint2* dst = (uint2*)p.scr->uT + ((up >> 1) * DM + cw * 80) * 4 + (lane ^ ((up & 1) << 1));
#pragma unroll
      for (int i = 0; i < 10; i++) {
        const uint32_t a = movm(pack_h(fmaf(bflo(xv[0][i]), r0, n0), fmaf(bfhi(xv[0][i]), r0, n0)));
        const uint32_t b = movm(pack_h(fmaf(bflo(xv[1][i]), r1, n1), fmaf(bfhi(xv[1][i]), r1, n1)));
        dst[i * 32] = make_uint2(a, b);
      }
    }
    if (warp == 8) {
      bar_sync(12, 256);
      if (lane == 0) publish(cnt + C_LN * 32);
      __syncwarp();
    } else bar_arrive(12, 256);
    if (warp == 15) {
      if (elect1()) {
#pragma unroll 1
        for (int s = 4; s < 10; s++) {
          mbar_wait(bar + 8 * (B_REL1 + s - 3), 0);
          load1(s, &tmX, &tmW1, rg1, j1);
        }
      }
      __syncwarp();
    }
    if (warp >= 10 && warp < 15) {
      const uint32_t pb = sb + OFF_P + kch * 3072, pk = sb + OFF_KS + kch * 4096;
      const uint2 e0 = lds64(pk + 2560 + lane * 8), e1 = lds64(pk + 5 * 4096 + 2560 + lane * 8);
      const float dsk = bflo(pds);
      uint32_t kex = __float_as_uint(fmaxf(__uint_as_float(max(max(e0.y, e1.y), mw)) * dt, fabsf(dsk) * (1.f / 256.f))) >> 23;
      kex = min(max(kex, 20u), 240u);
      const float s2 = __uint_as_float((258 - kex) << 23), sd = s2 * dt * (1.f / 32.f);
      const float f0 = __uint_as_float(e0.y) * sd, f1 = __uint_as_float(e1.y) * sd, f2 = __uint_as_float(mw) * sd;
      k0 += __uint_as_float(e0.x) + __uint_as_float(e1.x);
#pragma unroll
      for (int o = 16; o; o >>= 1) k0 += __shfl_xor_sync(0xffffffffu, k0, o);
      const float k0n = fmaf(k0, dt, dsk) * s2;
      uint32_t h[5][2];
#pragma unroll
      for (int j = 0; j < 5; j++) {
        const uint4 a = lds128(pk + j * 512 + lane * 16), b = lds128(pk + 5 * 4096 + j * 512 + lane * 16);
#pragma unroll
        for (int e = 0; e < 4; e++) kacc[j][e] = fmaf(__uint_as_float((&a.x)[e]), f0, fmaf(__uint_as_float((&b.x)[e]), f1, kacc[j][e] * f2));
        if (j == 1) {
          const float k256 = __shfl_sync(0xffffffffu, kacc[1][3], 28);
          if (lane == 31) kacc[1][3] -= k256;
        }
        if (j == 2 || j == 3) { h[j][0] = pack_h(kacc[j][0], kacc[j][2]); h[j][1] = pack_h(kacc[j][1], kacc[j][3]); }
        else { h[j][0] = pack_h(kacc[j][0], kacc[j][1]); h[j][1] = pack_h(kacc[j][2], kacc[j][3]); }
      }
      fence_async_smem();
      bar_arrive(4, 192);
#pragma unroll
      for (int i = 0; i < 6; i++) sts128(pb + i * 512 + lane * 16, 0, 0, 0, 0);
      __syncwarp();
      {
        const int sw = g >> 2;
        const uint32_t sel = sw ? 0x1032 : 0x3210;
        const uint32_t a = pb + (P0 + 8 * g + ((0x3124 >> (4 * q)) & 7)) * 4, a0 = a + sw * 16, a1 = a + 16 - sw * 16;
        put2<1>(a0, a1, h[0][0], sel);
        put2<1>(a0 + 256, a1 + 256, h[0][1], sel);
        put2<1>(a0 + 512, a1 + 512, h[1][0], sel);
        put2<1>(lane == 28 ? pb + PB1 * 4 : a0 + 768, a1 + 768, h[1][1], sel);
      }
      {
        const int sw = q >> 1;
        const uint32_t sel = sw ? 0x1032 : 0x3210;
        uint32_t a = pb + (((q & 1) ? PA1 : PB1 + 1) + 32 * sw + 2 * g) * 4;
        put2<1>(a + sw * 64, a + 64 - sw * 64, h[2][0], sel);
        put2<1>(a + 4 + sw * 64, a + 68 - sw * 64, h[2][1], sel);
        a = pb + (PA2 + g + 16 * q) * 4;
        put2<2>(a + sw * 32, a + 32 - sw * 32, h[3][0], sel);
        put2<2>(a + (PB2 - PA2) * 4 + sw * 32, a + (PB2 - PA2) * 4 + 32 - sw * 32, h[3][1], sel);
        a = pb + (((g & 1) ? PB3 : PA3) + (g >> 1) + 16 * q) * 4;
        const uint32_t hx = sw ? h[4][1] : h[4][0], hy = sw ? h[4][0] : h[4][1];
        put2<1>(a + sw * 16, a + 32 + sw * 16, hx, 0x3210);
        put2<1>(a + 16 - sw * 16, a + 48 - sw * 16, hy, 0x3210);
      }
      if (lane == 30) put2<1>(pb + P0 * 4, pb + (PA1 + 64) * 4, pack_h(k0n, kacc[2][3]), 0x3210);
      if (lane == 31) sts64(sb + OFF_CHC + kch * 8, (kex - 4) * 0x00800080u, __byte_perm(h[3][1], 0, 0x3232));
    }
    if (warp == 8) {
      bar_sync(13, 64);
      if (elect1()) {
        mbar_expect(bar + 8 * B_UFULL, 144 * 160);
        mbar_expect(bar + 8 * B_EPI, 1024 + 768);
        poll_cnt(cnt + C_LN * 32, ep * 128);
        tma2d(sb + OFF_U - 16 * 160, &tmU, wid * 80, -16, bar + 8 * B_UFULL);
        bulk_g2s(sb + OFF_STAT, p.scr->stats + rg1 * 128, 1024, bar + 8 * B_EPI);
      }
      __syncwarp();
      bar_arrive(15, 224);
    } else if (warp == 9) {
      bar_sync(4, 192);
      bar_arrive(13, 64);
      if (elect1()) {
        mbar_expect(bar + 8 * B_W2, 96 * 176);
        tma5d(sb + OFF_W2S, &tmW2, (wid & 7) * 80, (wid >> 3) * 3, bar + 8 * B_W2);
        poll_cnt(cnt + C_CS * 32, ep * 4);
        bulk_g2s(sb + OFF_CS, p.scr->cs + j1 * 192, 768, bar + 8 * B_EPI);
      }
      __syncwarp();
    }
    if (warp >= 9 && warp < 15) {
      const int uu = (warp - 9) >> 1, G = (warp - 9) & 1;
      const int grp = (wid >> 3) * 3 + uu, jj = grp / 6, rem = grp - jj * 6;
      const uint32_t a = sb + OFF_W2S + (uu * 32 + lane) * 176;
      uint4* dst = p.scr->w2p + ((wid & 7) * 24 + 8 * (rem >> 1) + jj) * 640 + ((rem & 1) * 4 + (lane >> 3)) * 80 + (lane & 7);
      mbar_wait(bar + 8 * B_W2, 0);
      const uint4 wv[4] = {lds128(a + G * 64), lds128(a + G * 64 + 16), lds128(a + G * 64 + 32), lds128(a + G * 64 + 48)};
      const uint4 t0 = lds128(a + 128), t1 = lds128(a + 144);
      uint32_t w[20];
#pragma unroll
      for (int i = 0; i < 16; i++) w[i] = bmul((&wv[i >> 2].x)[i & 3], 0x3f003f00u);
      w[16] = bmul(G ? t0.y : t0.x, 0x3f003f00u); w[17] = bmul(G ? t0.w : t0.z, 0x3f003f00u);
      w[18] = bmul(G ? t1.y : t1.x, 0x3f003f00u); w[19] = bmul(G ? t1.w : t1.z, 0x3f003f00u);
      bar_sync(15, 224);
#pragma unroll
      for (int i = 0; i < 4; i++) dst[G * 32 + 8 * i] = make_uint4(w[i], w[4 + i], w[8 + i], w[12 + i]);
      dst[64 + G * 8] = make_uint4(w[16], w[17], w[18], w[19]);
      bar_arrive(2, 448);
      if (warp == 12) bar_arrive(3, 64);
    } else if (warp == 15) bar_sync(3, 64);
    const int wg = warp >> 2, role = (warp + 2 * wg) & 3;
    uint32_t co[6], cpa = (g - 2 * q) * 4;
    if (role < 2) {
#pragma unroll
      for (int gm = 0; gm < 3; gm++) {
        const int hb = 2 * (lane & 7) + role - 2 + gm, l3 = ((lane >> 3) ^ (hb >> 1)) & 7;
        co[2 * gm] = hb * 1280 + uoff(l3); co[2 * gm + 1] = hb * 1280 + uoff(l3 ^ 4);
      }
    } else {
      const int mi = lane >> 3, hf = (lane >> 2) & 1;
      co[0] = hf * 1792 + (mi ^ hf) * 64 + ((q ^ (mi >> 1) ^ (hf * 2)) << 4);
      co[1] = co[0] ^ 96;
      co[2] = (lane ^ (role == 2 ? (mi & 1) : ((lane >> 1) & 4))) << 4;
      co[3] = lane * 16;
      co[4] = (g >> 1) == q ? ((g & 1) ? 0xffff0000u : 0xffffu) : 0u;
      co[5] = 2 * cpa;
    }
    const uint32_t zero = lds32(sb + OFF_ZERO), nz = zero | 0x80000000u;
#pragma unroll
    for (int i = 0; i < 6; i++) co[i] = pin(co[i], zero);
    cpa = pin(cpa, zero);
    const Comb cmb = comb_setup(tid, zero);
    mbar_wait(bar + 8 * B_UFULL, 0);
#pragma unroll 1
    for (int ch = (cw >> 2) * 4; ch >= (cw >> 2); ch--) {
      if (ch < 4) mbar_wait(bar + 8 * (B_REL1 + (ch ? 8 : 7)), 0);
      const int qt = (cw + ch) & 3, j = qt * 32 + lane;
      const uint32_t ub = sb + OFF_U + ch * 32, zb = sb + OFF_Z + ch * ZSZ;
      uint32_t w_[20], o_[20], d_[20], b3_[20];
      uint32_t *w = w_ + 8, *o = o_ + 8, *d = d_ + 8, *b3 = b3_ + 8;
      {
        const uint32_t am = ub + uoff(upos(2 * j - 2)), a0 = ub + uoff(upos(2 * j));
        const uint2 a = lds64(am + 8);
        const uint4 b = lds128(am ^ 16), c = lds128(a0), e = lds128(a0 ^ 16);
        w[8] = lds32(ub + uoff(upos((2 * j + 2) & 255)));
        w[-6] = a.x; w[-5] = a.y; w[-4] = b.x; w[-3] = b.y; w[-2] = b.z; w[-1] = b.w;
        w[0] = c.x; w[1] = c.y; w[2] = c.z; w[3] = c.w; w[4] = e.x; w[5] = e.y; w[6] = e.z; w[7] = e.w;
      }
#pragma unroll
      for (int i = -1; i <= 7; i++) o[i] = odd_pair(w[i], w[i + 1]);
#pragma unroll
      for (int i = 0; i <= 7; i++) { d[i] = hadd(w[i], o[i]); b3[i] = hadd(d[i], o[i - 1]); }
      if (j < 112) {
        const int gr = j >> 1;
        const uint32_t a1 = zb + ZA1 + 512 + (gr ^ ((gr >> 2) & 1)) * 64 + ((gr >> 1) & 3) * 16 + (j & 1) * 8;
#pragma unroll
        for (int pp = 0; pp < 4; pp++) {
          const uint32_t sel = (pp & 1) ? 0x7632 : 0x5410;
          const int k = pp >> 1;
          sts64(a1 ^ (pp * 16), __byte_perm(w[k - 1], w[k + 1], sel), __byte_perm(w[k + 3], w[k + 5], sel));
          sts64((a1 ^ (pp * 16)) + (ZB1 - ZA1), __byte_perm(b3[k], b3[k + 2], sel), __byte_perm(b3[k + 4], b3[k + 6], sel));
        }
      } else {
        const uint32_t a1 = zb + ZA1 + ((lane ^ 7) & 15) * 16;
        sts128(a1, 0, 0, 0, 0); sts128(a1 + 256, 0, 0, 0, 0); sts128(a1 + ZB1 - ZA1, 0, 0, 0, 0);
        sts128(a1 + ZB1 - ZA1 + 256, 0, 0, 0, j == 127 ? w[8] << 16 : 0u);
      }
      if (qt < 3) {
        uint32_t e_[20], b5_[20];
        uint32_t *e = e_ + 8, *b5 = b5_ + 8;
#pragma unroll
        for (int i = -6; i <= -2; i++) o[i] = odd_pair(w[i], w[i + 1]);
#pragma unroll
        for (int i = -6; i <= -1; i++) d[i] = hadd(w[i], o[i]);
#pragma unroll
        for (int i = -5; i <= -1; i++) b3[i] = hadd(d[i], o[i - 1]);
#pragma unroll
        for (int i = -5; i <= 4; i++) e[i] = hadd(d[i - 1], d[i]);
#pragma unroll
        for (int i = -4; i <= 4; i++) b5[i] = hadd(e[i], w[i + 1]);
        const uint32_t a2 = zb + ((j >> 3) * 16 + (j & 7)) * 16;
        sts128(a2 + ZA2, b3[-2], b3[-1], b3[0], b3[1]);
        sts128(a2 + ZA2 + 128, b3[2], b3[3], b3[4], b3[5]);
        sts128(a2 + ZB2, b5[-4], b5[-3], b5[-2], b5[-1]);
        sts128(a2 + ZB2 + 128, b5[0], b5[1], b5[2], b5[3]);
        if (qt < 2) {
          sts128(a2 + ZS, d[-2], d[-1], d[0], d[1]);
          sts128(a2 + ZS + 128, d[2], d[3], d[4], d[5]);
          uint32_t b7[8], b9[8];
#pragma unroll
          for (int i = -4; i <= 3; i++) { b7[i + 4] = hadd(b3[i - 1], e[i + 1]); b9[i + 4] = hadd(e[i - 1], b5[i + 1]); }
          const uint32_t a3 = zb + ((j >> 4) * 32 + (j & 15)) * 16;
          sts128(a3 + ZA3, b7[0], b7[1], b7[2], b7[3]);
          sts128(a3 + ZA3 + 256, b7[4], b7[5], b7[6], b7[7]);
          sts128(a3 + ZB3 + 256, b9[0], b9[1], b9[2], b9[3]);
          if (j < 63) sts128(a3 + ZB3 + ((j & 15) == 15 ? 272 : 16), b9[4], b9[5], b9[6], b9[7]);
          else sts128(zb + ZB3, 0, 0, 0, 0);
        }
      }
    }
    if (wg == 3) bar_arrive(0, 256);
    bar_sync(wg == 2 ? 14 : 7, 384);
#pragma unroll 1
    for (int ch = wg - 2; ch < 5; ch += 2) {
      const uint32_t ub = sb + OFF_U + ch * 32, zb = sb + OFF_Z + ch * ZSZ, pb = sb + OFF_P + ch * 3072;
      if (ch == 2) bar_sync(0, 256);
      const uint32_t pa = pb + cpa;
      if (role < 2) {
        float acc[8][4];
#pragma unroll
        for (int r = 0; r < 8; r++) { acc[r][0] = acc[r][1] = acc[r][2] = acc[r][3] = 0.f; }
        float fix = 0.f;
        if (role == 1 && lane == 28) {
          const uint32_t k = lds32(pb + PB1 * 4), u0 = lds32(ub);
          fix = __low2float(*reinterpret_cast<const __half2*>(&k)) * __low2float(*reinterpret_cast<const __half2*>(&u0));
        }
        uint32_t b[12][4], A[17][4];
#pragma unroll
        for (int i = 11; i >= 8; i--) ldsm4(b[i], ub + (co[4 + (i & 1)] ^ (((i >> 1) & 1) * 16)) + ((i >> 1) & 1) * 640);
        A[0][0] = lds32(pa + P0 * 4); A[0][1] = lds32(pa + P0 * 4 + 32); A[0][2] = lds32(sb + OFF_ZERO + 4);
#pragma unroll
        for (int m = 0; m <= 16; m++) {
          if (m < 16) {
            A[m + 1][0] = lds32(pa + P0 * 4 + (2 * m + 2) * 32);
            A[m + 1][1] = m < 15 ? lds32(pa + P0 * 4 + (2 * m + 3) * 32) : lds32(sb + OFF_ZERO + 8);
          }
          if ((m & 1) == 0 && m < 16) {
            const int i = 7 - (m >> 1);
            ldsm4(b[i], ub + (co[2 * (i >> 2) + (i & 1)] ^ (((i >> 1) & 1) * 16)) + ((i >> 1) & 1) * 640);
          }
          if (m == 9 && elect1()) mbar_arrive(bar + 8 * (B_PAIR + ch));
          A[m][3] = dup(A[m][0], nz);
          if (m < 16) A[m + 1][2] = dup(A[m][1], nz);
#pragma unroll
          for (int r = 7; r >= 0; r--) {
            const int f = 16 + r - m;
            hmma(acc[r], A[m][0], A[m][1], A[m][2], A[m][3], b[f >> 1][(f & 1) * 2], b[f >> 1][(f & 1) * 2 + 1]);
          }
        }
        acc[7][2] += fix;
        mbar_wait(bar + 8 * (B_PAIR + ch), 0);
#pragma unroll
        for (int i = 3; i >= 0; i--)
          stsm4t(ub + (co[4 + (i & 1)] ^ (((i >> 1) & 1) * 16)) + ((i >> 1) & 1) * 640, pack_bf(acc[2 * i][0], acc[2 * i][1]), pack_bf(acc[2 * i][2], acc[2 * i][3]),
                 pack_bf(acc[2 * i + 1][0], acc[2 * i + 1][1]), pack_bf(acc[2 * i + 1][2], acc[2 * i + 1][3]));
      } else if (role == 2) {
        float acc[14][4];
#pragma unroll
        for (int r = 0; r < 14; r++) { acc[r][0] = acc[r][1] = acc[r][2] = acc[r][3] = 0.f; }
#pragma unroll
        for (int arr = 0; arr < 2; arr++) {
          uint32_t A[5][4];
#pragma unroll
          for (int m = 0; m < 5; m++) {
            A[m][0] = lds32(pa + (arr ? PB1 : PA1) * 4 + m * 64);
            A[m][1] = m < 4 ? lds32(pa + (arr ? PB1 : PA1) * 4 + m * 64 + 32) : lds32(sb + OFF_ZERO + 4 + arr * 8);
          }
#pragma unroll
          for (int m = 4; m >= 1; m--) { A[m][2] = dup(A[m - 1][1], nz); A[m][3] = dup(A[m][0], nz); }
          A[0][2] = lds32(sb + OFF_ZERO + 8 + arr * 8); A[0][3] = dup(A[0][0], nz);
#pragma unroll
          for (int ip = 0; ip < 9; ip++) {
            uint32_t b[4];
            ldsm4(b, zb + co[ip & 1] + (arr ? ZB1 : ZA1) + ip * 256);
#pragma unroll
            for (int hh = 0; hh < 2; hh++)
#pragma unroll
              for (int m = 0; m < 5; m++) {
                const int i = 2 * ip + hh - 4 + m;
                if (i >= 0 && i < 14) hmma(acc[i], A[m][0], A[m][1], A[m][2], A[m][3], b[2 * hh], b[2 * hh + 1]);
              }
          }
        }
        const uint32_t a = zb + ZA1 + 512 + co[2];
#pragma unroll
        for (int i = 0; i < 7; i++)
          stsm4(a + i * 512, pack_bf(acc[2 * i][0], acc[2 * i][1]), pack_bf(acc[2 * i][2], acc[2 * i][3]),
                pack_bf(acc[2 * i + 1][0], acc[2 * i + 1][1]), pack_bf(acc[2 * i + 1][2], acc[2 * i + 1][3]));
      } else {
        float acc[12][4];
        const uint32_t za = zb + co[3];
        {
          float d[4][2][4];
#pragma unroll
          for (int r = 0; r < 8; r++) { d[r >> 1][r & 1][0] = d[r >> 1][r & 1][1] = d[r >> 1][r & 1][2] = d[r >> 1][r & 1][3] = 0.f; }
#pragma unroll
          for (int arr = 0; arr < 2; arr++) {
            uint32_t A[4][4];
#pragma unroll
            for (int m = 0; m < 4; m++) { A[m][0] = lds32(pa + (arr ? PB3 : PA3) * 4 + m * 64); A[m][1] = lds32(pa + (arr ? PB3 : PA3) * 4 + m * 64 + 32); }
#pragma unroll
            for (int m = 0; m < 4; m++) { A[m][2] = m ? dup(A[m - 1][1], nz) : lds32(sb + OFF_ZERO + 4 + arr * 4); A[m][3] = dup(A[m][0], nz); }
#pragma unroll
            for (int io = 0; io < 4; io++) {
              uint32_t b[4];
              ldsm4t(b, za + (arr ? ZB3 : ZA3) + io * 512);
#pragma unroll
              for (int m = 0; m + io < 4; m++) {
                hmma(d[io + m][0], A[m][0], A[m][1], A[m][2], A[m][3], b[0], b[1]);
                hmma(d[io + m][1], A[m][0], A[m][1], A[m][2], A[m][3], b[2], b[3]);
              }
            }
          }
#pragma unroll
          for (int r = 0; r < 4; r++) {
            acc[r][0] = acc[r][1] = acc[r][2] = acc[r][3] = 0.f;
            acc[4 + 2 * r][0] = d[r][0][0]; acc[4 + 2 * r][1] = d[r][0][1]; acc[4 + 2 * r][2] = d[r][1][0]; acc[4 + 2 * r][3] = d[r][1][1];
            acc[5 + 2 * r][0] = d[r][0][2]; acc[5 + 2 * r][1] = d[r][0][3]; acc[5 + 2 * r][2] = d[r][1][2]; acc[5 + 2 * r][3] = d[r][1][3];
          }
        }
        {
          const uint32_t k0 = lds32(sb + OFF_CHC + ch * 8 + 4) & co[4];
          const uint32_t k1 = lds32(sb + OFF_ZERO + 12), k2 = lds32(sb + OFF_ZERO + 16), k3 = dup(k0, nz);
#pragma unroll
          for (int ip = 0; ip < 4; ip++) {
            uint32_t b[4];
            ldsm4t(b, za + ZS + ip * 512);
            hmma(acc[4 + 2 * ip], k0, k1, k2, k3, b[0], b[1]);
            hmma(acc[5 + 2 * ip], k0, k1, k2, k3, b[2], b[3]);
          }
        }
        const uint32_t pa2 = pb + co[5];
#pragma unroll
        for (int arr = 0; arr < 2; arr++) {
          uint32_t A[5][4];
#pragma unroll
          for (int m = 0; m < 5; m++) {
            const uint2 v = lds64(pa2 + (arr ? PB2 : PA2) * 4 + m * 64);
            A[m][0] = v.x; A[m][1] = v.y; A[m][2] = lds32(pa2 + (arr ? PB2 : PA2) * 4 + m * 64 - 4);
          }
#pragma unroll
          for (int m = 0; m < 5; m++) A[m][3] = dup(A[m][0], nz);
#pragma unroll
          for (int ip = 0; ip < 6; ip++) {
            uint32_t b[4];
            ldsm4t(b, za + (arr ? ZB2 : ZA2) + ip * 512);
#pragma unroll
            for (int hh = 0; hh < 2; hh++)
#pragma unroll
              for (int m = 0; m < 5; m++) {
                const int i = 2 * ip + hh + m;
                if (i < 12) hmma(acc[i], A[m][0], A[m][1], A[m][2], A[m][3], b[2 * hh], b[2 * hh + 1]);
              }
          }
        }
        const uint32_t a = zb + ZA2 + co[2];
#pragma unroll
        for (int i = 0; i < 6; i++)
          stsm4(a + i * 512, pack_bf(acc[2 * i][0], acc[2 * i][1]), pack_bf(acc[2 * i][2], acc[2 * i][3]),
                pack_bf(acc[2 * i + 1][0], acc[2 * i + 1][1]), pack_bf(acc[2 * i + 1][2], acc[2 * i + 1][3]));
      }
      __syncwarp();
      if (elect1()) mbar_arrive(bar + 8 * (B_PART + ch));
    }
    bar_arrive(8, 512);
    combine(cmb, 6 - wg, wid, p.scr->sT);
    if (warp == 12) {
      if (elect1()) {
        const uint4* srcA = p.scr->h + (rg1 * 24 + NS2 - 2) * 1024;
        const uint4* srcB = p.scr->w2p + (j1 * 24 + NS2 - 2) * 640;
        uint32_t d = sb + (NS2 - 2) * SLOT2;
        mbar_wait(bar + 8 * (B_FULL2 + 4), 0);
        asm volatile("fence.proxy.async.global;" ::: "memory");
#pragma unroll 1
        for (int s = NS2 - 2; s < 24; s++) {
          mbar_wait(bar + 8 * (s < NS2 ? B_FREE + s - 2 : B_REL2 + s - NS2 + 1), 0);
          const uint32_t mb = bar + 8 * (B_FULL2 + s);
          mbar_expect(mb, SLOT2);
          bulk_g2s(d, srcA, 16384, mb);
          bulk_g2s(d + 16384, srcB, 10240, mb);
          srcA += 1024; srcB += 640;
          d = d == sb + (NS2 - 1) * SLOT2 ? sb : d + SLOT2;
        }
      }
      __syncwarp();
    } else if (warp == 13) {
      if (elect1()) {
#pragma unroll 1
        for (int c = 2; c < 5; c++) mbar_wait(bar + 8 * (B_FREE + c), 0);
        publish(cnt + (C_S + (wid >> 4)) * 32);
        mbar_expect(bar + 8 * B_SFULL, 20480);
        poll_cnt(cnt + (C_S + j1) * 32, ep * 16);
        mbar_wait(bar + 8 * (B_REL2 + 24 - NS2), 0);
        bulk_g2s(sb + OFF_U, p.scr->sT + (j1 * 16 + rg1) * 1280, 20480, bar + 8 * B_SFULL);
      }
      __syncwarp();
    }
  }
}

typedef CUresult (*EncodeFn)(CUtensorMap*, CUtensorMapDataType, cuuint32_t, void*, const cuuint64_t*, const cuuint64_t*,
                             const cuuint32_t*, const cuuint32_t*, CUtensorMapInterleave, CUtensorMapSwizzle,
                             CUtensorMapL2promotion, CUtensorMapFloatOOBfill);

}

extern "C" void kernel_launch(void* const* d_in, const int* in_sizes, int n_in, void* d_out, int out_size) {
  static EncodeFn enc = nullptr;
  static int nsm = 0;
  static void* scr = nullptr;
  if (!enc) {
    void* fn = nullptr;
    cudaDriverEntryPointQueryResult qr;
    cudaGetDriverEntryPoint("cuTensorMapEncodeTiled", &fn, cudaEnableDefault, &qr);
    enc = (EncodeFn)fn;
    int dev = 0;
    cudaGetDevice(&dev);
    cudaDeviceGetAttribute(&nsm, cudaDevAttrMultiProcessorCount, dev);
    cudaFuncSetAttribute(fused_s4_ffn_kernel<true>, cudaFuncAttributeMaxDynamicSharedMemorySize, SMEM_BYTES);
    cudaFuncSetAttribute(fused_s4_ffn_kernel<false>, cudaFuncAttributeMaxDynamicSharedMemorySize, SMEM_BYTES);
    cudaGetSymbolAddress(&scr, g_scr);
  }
  Params p;
  p.x = (const __nv_bfloat16*)d_in[0];
  p.are = (const __nv_bfloat16*)d_in[1]; p.aim = (const __nv_bfloat16*)d_in[2];
  p.bre = (const __nv_bfloat16*)d_in[3]; p.bim = (const __nv_bfloat16*)d_in[4];
  p.cre = (const __nv_bfloat16*)d_in[5]; p.cim = (const __nv_bfloat16*)d_in[6];
  p.logdt = (const __nv_bfloat16*)d_in[7]; p.dskip = (const __nv_bfloat16*)d_in[8];
  p.w1 = (const __nv_bfloat16*)d_in[10]; p.w2 = (const __nv_bfloat16*)d_in[11];
  p.out = (__nv_bfloat16*)d_out;
  p.scr = (Scratch*)scr;
  CUtensorMap tmX, tmW1, tmU, tmW2;
  const cuuint32_t es[5] = {1, 1, 1, 1, 1};
  {
    const cuuint64_t gd[5] = {DM, 2, 4, 4, FF / 32}, gs[4] = {DM * 2, DM * 16, DM * 4, DM * 64};
    const cuuint32_t bx[5] = {88, 2, 4, 4, 3};
    enc(&tmW2, CU_TENSOR_MAP_DATA_TYPE_BFLOAT16, 5, d_in[11], gd, gs, bx, es, CU_TENSOR_MAP_INTERLEAVE_NONE,
        CU_TENSOR_MAP_SWIZZLE_NONE, CU_TENSOR_MAP_L2_PROMOTION_NONE, CU_TENSOR_MAP_FLOAT_OOB_FILL_NONE);
  }
  {
    const cuuint64_t gd[2] = {16 * DM, 128}, gs[1] = {DM * 32};
    const cuuint32_t bx[2] = {80, 144};
    enc(&tmU, CU_TENSOR_MAP_DATA_TYPE_FLOAT16, 2, p.scr->uT, gd, gs, bx, es, CU_TENSOR_MAP_INTERLEAVE_NONE,
        CU_TENSOR_MAP_SWIZZLE_NONE, CU_TENSOR_MAP_L2_PROMOTION_NONE, CU_TENSOR_MAP_FLOAT_OOB_FILL_NONE);
  }
  {
    const cuuint64_t gd[2] = {DM, SEQ}, gs[1] = {DM * 2};
    const cuuint32_t bx[2] = {64, 128};
    enc(&tmX, CU_TENSOR_MAP_DATA_TYPE_BFLOAT16, 2, d_in[0], gd, gs, bx, es, CU_TENSOR_MAP_INTERLEAVE_NONE,
        CU_TENSOR_MAP_SWIZZLE_128B, CU_TENSOR_MAP_L2_PROMOTION_L2_128B, CU_TENSOR_MAP_FLOAT_OOB_FILL_NONE);
  }
  {
    const cuuint64_t gd[3] = {64, DM, FF / 64}, gs[2] = {FF * 2, 128};
    const cuuint32_t bx[3] = {64, 64, 3};
    enc(&tmW1, CU_TENSOR_MAP_DATA_TYPE_BFLOAT16, 3, d_in[10], gd, gs, bx, es, CU_TENSOR_MAP_INTERLEAVE_NONE,
        CU_TENSOR_MAP_SWIZZLE_128B, CU_TENSOR_MAP_L2_PROMOTION_L2_128B, CU_TENSOR_MAP_FLOAT_OOB_FILL_NONE);
  }
  if (nsm == 132) fused_s4_ffn_kernel<true><<<132, 512, SMEM_BYTES>>>(p, tmX, tmW1, tmU, tmW2);
  else fused_s4_ffn_kernel<false><<<132, 512, SMEM_BYTES>>>(p, tmX, tmW1, tmU, tmW2);
}
```

```cpp
#include <cuda_runtime.h>
#include <cuda_bf16.h>
#include <cuda_fp16.h>
#include <cuda.h>
#include <stdint.h>

namespace {

constexpr int SEQ = 2048, DM = 640, FF = 1536;

constexpr int SLOT1 = 40960;
constexpr int SLOT2 = 26624;
constexpr int NS2 = 7;
#define GATE 1
#define SPARE_NS 700
#define DELAY_NS 0
#define PACE_NS 30
constexpr int OFF_Z = 85504, ZSZ = 20480;
constexpr int ZA3 = 0, ZB3 = 2048, ZS = 4096, ZA2 = 6144, ZB2 = 9216, ZA1 = 12288, ZB1 = 16384;
constexpr int OFF_W2S = OFF_Z + 4 * ZSZ;
constexpr int OFF_U = 190464;
constexpr int OFF_P = 210944;
constexpr int OFF_KS = 163840;
constexpr int OFF_LNP = 225280;
constexpr int OFF_MISC = 226304;
constexpr int OFF_CHC = OFF_MISC + 16;
constexpr int OFF_EP = OFF_MISC + 64;
constexpr int OFF_ZERO = OFF_MISC + 128;
constexpr int OFF_STAT = OFF_MISC + 1024;
constexpr int OFF_CS = OFF_MISC + 2048;
constexpr int OFF_BAR = OFF_MISC + 2816;
constexpr int SMEM_BYTES = OFF_MISC + 6144;
constexpr int P0 = 8, PA1 = 280, PB1 = 360, PA2 = 448, PB2 = 544, PA3 = 632, PB3 = 704;
enum { B_FULL1 = 0, B_FULL2 = 10, B_UFULL = 34, B_EPI = 35, B_SFULL = 36, B_W2 = 37,
       B_PAIR = 42,
       B_FREE = 48, B_PART = 54,
       B_REL1 = 60, B_REL2 = 70 };
enum { C_LN = 0, C_CS = 1, C_H0 = 2, C_H1 = 18, C_S = 34, C_W2 = 42, C_NUM = 43 };

struct Scratch {
  unsigned cnt[64 * 32];
  unsigned epoch[256];
  float2 stats[SEQ];
  float cs[FF];
  uint4 uT[DM * 256];
  uint4 w2p[8 * 24 * 640];
  uint4 sT[8 * 16 * 1280];
  uint4 h[16 * 24 * 1024];
};
__device__ __align__(1024) Scratch g_scr;
constexpr uint32_t sb = 1024;
constexpr uint32_t bar = sb + OFF_BAR;

struct Params {
  const __nv_bfloat16 *are, *aim, *bre, *bim, *cre, *cim, *logdt, *dskip, *x, *w1, *w2;
  __nv_bfloat16* out;
  Scratch* scr;
};

__device__ __forceinline__ void mbar_init(uint32_t a, int c) { asm volatile("mbarrier.init.shared::cta.b64 [%0], %1;" ::"r"(a), "r"(c)); }
__device__ __forceinline__ void mbar_expect(uint32_t a, int b) { asm volatile("mbarrier.arrive.expect_tx.shared::cta.b64 _, [%0], %1;" ::"r"(a), "r"(b) : "memory"); }
__device__ __forceinline__ void mbar_arrive(uint32_t a) { asm volatile("mbarrier.arrive.shared::cta.b64 _, [%0];" ::"r"(a) : "memory"); }
__device__ __forceinline__ void mbar_wait(uint32_t a, int ph) {
  asm volatile(
      "{\n.reg .pred p;\n.reg .u32 n;\n"
      "mbarrier.try_wait.parity.shared::cta.b64 p, [%0], %1;\n@p bra LD;\nmov.u32 n, 0;\n"
      "LW:\nmbarrier.try_wait.parity.shared::cta.b64 p, [%0], %1, 20000;\n@p bra LD;\n"
      "add.u32 n, n, 1;\nsetp.lt.u32 p, n, 100000;\n@p bra LW;\ntrap;\nLD:\n}\n" ::"r"(a), "r"(ph) : "memory");
}
__device__ __forceinline__ void poll_cnt(const unsigned* p, unsigned target) {
  asm volatile(
      "{\n.reg .pred p;\n.reg .u32 n;\n.reg .s32 v;\nmov.u32 n, 0;\n"
      "LW:\nld.relaxed.gpu.global.u32 v, [%0];\nsub.s32 v, v, %1;\nsetp.ge.s32 p, v, 0;\n@p bra LD;\n"
      "nanosleep.u32 64;\nadd.u32 n, n, 1;\nsetp.lt.u32 p, n, 4000000;\n@p bra LW;\ntrap;\n"
      "LD:\nfence.acquire.gpu;\nfence.proxy.async.global;\n}\n" ::"l"(p), "r"(target) : "memory");
}
__device__ __forceinline__ void publish(unsigned* p) {
  asm volatile("fence.proxy.async.global;\nfence.release.gpu;\nred.relaxed.gpu.global.add.u32 [%0], 1;" ::"l"(p) : "memory");
}
__device__ __forceinline__ uint32_t movm(uint32_t v) { uint32_t r; asm volatile("movmatrix.sync.aligned.m8n8.trans.b16 %0, %1;" : "=r"(r) : "r"(v)); return r; }
__device__ __forceinline__ void fence_async_smem() { asm volatile("fence.proxy.async.shared::cta;" ::: "memory"); }
__device__ __forceinline__ bool elect1() { uint32_t p; asm volatile("{\n.reg .pred P;\nelect.sync _|P, 0xffffffff;\nselp.u32 %0,1,0,P;\n}\n" : "=r"(p)); return p; }
__device__ __forceinline__ void bar_sync(int id, int n) { asm volatile("bar.sync %0, %1;" ::"r"(id), "r"(n) : "memory"); }
__device__ __forceinline__ void bar_arrive(int id, int n) { asm volatile("bar.arrive %0, %1;" ::"r"(id), "r"(n) : "memory"); }
__device__ __forceinline__ void bulk_g2s(uint32_t dst, const void* src, int bytes, uint32_t mb) {
  asm volatile("cp.async.bulk.shared::cluster.global.mbarrier::complete_tx::bytes [%0], [%1], %2, [%3];" ::"r"(dst), "l"(src), "r"(bytes), "r"(mb) : "memory");
}
__device__ __forceinline__ void bulk_prefetch(const void* src, int bytes) { asm volatile("cp.async.bulk.prefetch.L2.global [%0], %1;" ::"l"(src), "r"(bytes) : "memory"); }
__device__ __forceinline__ void tma2d(uint32_t dst, const CUtensorMap* m, int c0, int c1, uint32_t mb) {
  asm volatile("cp.async.bulk.tensor.2d.shared::cluster.global.mbarrier::complete_tx::bytes [%0], [%1, {%3, %4}], [%2];" ::"r"(dst), "l"(m), "r"(mb), "r"(c0), "r"(c1) : "memory");
}
__device__ __forceinline__ void tma3d(uint32_t dst, const CUtensorMap* m, int c0, int c1, int c2, uint32_t mb) {
  asm volatile("cp.async.bulk.tensor.3d.shared::cluster.global.mbarrier::complete_tx::bytes [%0], [%1, {%3, %4, %5}], [%2];" ::"r"(dst), "l"(m), "r"(mb), "r"(c0), "r"(c1), "r"(c2) : "memory");
}
__device__ __forceinline__ unsigned frag_col(unsigned l) { return (l & 0x61) | ((l & 6) << (2 - (l >> 6))) | ((l >> 2) & 6); }
__device__ __forceinline__ void tma5d(uint32_t dst, const CUtensorMap* m, int c0, int c4, uint32_t mb) {
  asm volatile("cp.async.bulk.tensor.5d.shared::cluster.global.mbarrier::complete_tx::bytes [%0], [%1, {%3, %5, %5, %5, %4}], [%2];" ::"r"(dst), "l"(m), "r"(mb), "r"(c0), "r"(c4), "r"(0) : "memory");
}
__device__ __forceinline__ uint64_t dsc(uint32_t lo, uint32_t hi) { return ((uint64_t)hi << 32) | lo; }
__device__ __forceinline__ void wg_fence() { asm volatile("wgmma.fence.sync.aligned;" ::: "memory"); }
__device__ __forceinline__ void wg_commit() { asm volatile("wgmma.commit_group.sync.aligned;" ::: "memory"); }
template <int N> __device__ __forceinline__ void wg_wait() { asm volatile("wgmma.wait_group.sync.aligned %0;" ::"n"(N) : "memory"); }
__device__ __forceinline__ void wgmma_n192(float (&d)[96], uint64_t da, uint64_t db, int scale_d) {
  asm volatile("{\n.reg .pred p;\nsetp.ne.b32 p, %98, 0;\n"
    "wgmma.mma_async.sync.aligned.m64n192k16.f32.bf16.bf16 "
    "{"
    "%0, %1, %2, %3, %4, %5, %6, %7, %8, %9, %10, %11, %12, %13, %14, %15, "
    "%16, %17, %18, %19, %20, %21, %22, %23, %24, %25, %26, %27, %28, %29, %30, %31, "
    "%32, %33, %34, %35, %36, %37, %38, %39, %40, %41, %42, %43, %44, %45, %46, %47, "
    "%48, %49, %50, %51, %52, %53, %54, %55, %56, %57, %58, %59, %60, %61, %62, %63, "
    "%64, %65, %66, %67, %68, %69, %70, %71, %72, %73, %74, %75, %76, %77, %78, %79, "
    "%80, %81, %82, %83, %84, %85, %86, %87, %88, %89, %90, %91, %92, %93, %94, %95"
    "}, "
    "%96, %97, p, 1, 1, 0, 1;\n}\n"
    : "+f"(d[0]), "+f"(d[1]), "+f"(d[2]), "+f"(d[3]), "+f"(d[4]), "+f"(d[5]), "+f"(d[6]), "+f"(d[7]),
      "+f"(d[8]), "+f"(d[9]), "+f"(d[10]), "+f"(d[11]), "+f"(d[12]), "+f"(d[13]), "+f"(d[14]), "+f"(d[15]),
      "+f"(d[16]), "+f"(d[17]), "+f"(d[18]), "+f"(d[19]), "+f"(d[20]), "+f"(d[21]), "+f"(d[22]), "+f"(d[23]),
      "+f"(d[24]), "+f"(d[25]), "+f"(d[26]), "+f"(d[27]), "+f"(d[28]), "+f"(d[29]), "+f"(d[30]), "+f"(d[31]),
      "+f"(d[32]), "+f"(d[33]), "+f"(d[34]), "+f"(d[35]), "+f"(d[36]), "+f"(d[37]), "+f"(d[38]), "+f"(d[39]),
      "+f"(d[40]), "+f"(d[41]), "+f"(d[42]), "+f"(d[43]), "+f"(d[44]), "+f"(d[45]), "+f"(d[46]), "+f"(d[47]),
      "+f"(d[48]), "+f"(d[49]), "+f"(d[50]), "+f"(d[51]), "+f"(d[52]), "+f"(d[53]), "+f"(d[54]), "+f"(d[55]),
      "+f"(d[56]), "+f"(d[57]), "+f"(d[58]), "+f"(d[59]), "+f"(d[60]), "+f"(d[61]), "+f"(d[62]), "+f"(d[63]),
      "+f"(d[64]), "+f"(d[65]), "+f"(d[66]), "+f"(d[67]), "+f"(d[68]), "+f"(d[69]), "+f"(d[70]), "+f"(d[71]),
      "+f"(d[72]), "+f"(d[73]), "+f"(d[74]), "+f"(d[75]), "+f"(d[76]), "+f"(d[77]), "+f"(d[78]), "+f"(d[79]),
      "+f"(d[80]), "+f"(d[81]), "+f"(d[82]), "+f"(d[83]), "+f"(d[84]), "+f"(d[85]), "+f"(d[86]), "+f"(d[87]),
      "+f"(d[88]), "+f"(d[89]), "+f"(d[90]), "+f"(d[91]), "+f"(d[92]), "+f"(d[93]), "+f"(d[94]), "+f"(d[95])
    : "l"(da), "l"(db), "r"(scale_d));
}

__device__ __forceinline__ void wgmma_n80(float (&d)[40], uint64_t da, uint64_t db, int scale_d) {
  asm volatile("{\n.reg .pred p;\nsetp.ne.b32 p, %42, 0;\n"
    "wgmma.mma_async.sync.aligned.m64n80k16.f32.bf16.bf16 "
    "{"
    "%0, %1, %2, %3, %4, %5, %6, %7, %8, %9, %10, %11, %12, %13, %14, %15, "
    "%16, %17, %18, %19, %20, %21, %22, %23, %24, %25, %26, %27, %28, %29, %30, %31, "
    "%32, %33, %34, %35, %36, %37, %38, %39"
    "}, "
    "%40, %41, p, 1, 1, 0, 1;\n}\n"
    : "+f"(d[0]), "+f"(d[1]), "+f"(d[2]), "+f"(d[3]), "+f"(d[4]), "+f"(d[5]), "+f"(d[6]), "+f"(d[7]),
      "+f"(d[8]), "+f"(d[9]), "+f"(d[10]), "+f"(d[11]), "+f"(d[12]), "+f"(d[13]), "+f"(d[14]), "+f"(d[15]),
      "+f"(d[16]), "+f"(d[17]), "+f"(d[18]), "+f"(d[19]), "+f"(d[20]), "+f"(d[21]), "+f"(d[22]), "+f"(d[23]),
      "+f"(d[24]), "+f"(d[25]), "+f"(d[26]), "+f"(d[27]), "+f"(d[28]), "+f"(d[29]), "+f"(d[30]), "+f"(d[31]),
      "+f"(d[32]), "+f"(d[33]), "+f"(d[34]), "+f"(d[35]), "+f"(d[36]), "+f"(d[37]), "+f"(d[38]), "+f"(d[39])
    : "l"(da), "l"(db), "r"(scale_d));
}

__device__ __forceinline__ void hmma(float* c, uint32_t a0, uint32_t a1, uint32_t a2, uint32_t a3, uint32_t b0, uint32_t b1) {
  asm volatile("mma.sync.aligned.m16n8k16.row.col.f32.f16.f16.f32 {%0,%1,%2,%3}, {%4,%5,%6,%7}, {%8,%9}, {%0,%1,%2,%3};"
      : "+f"(c[0]), "+f"(c[1]), "+f"(c[2]), "+f"(c[3]) : "r"(a0), "r"(a1), "r"(a2), "r"(a3), "r"(b0), "r"(b1));
}
__device__ __forceinline__ void ldsm4(uint32_t* r, uint32_t a) { asm volatile("ldmatrix.sync.aligned.m8n8.x4.shared.b16 {%0,%1,%2,%3}, [%4];" : "=r"(r[0]), "=r"(r[1]), "=r"(r[2]), "=r"(r[3]) : "r"(a) : "memory"); }
__device__ __forceinline__ void ldsm4t(uint32_t* r, uint32_t a) { asm volatile("ldmatrix.sync.aligned.m8n8.x4.trans.shared.b16 {%0,%1,%2,%3}, [%4];" : "=r"(r[0]), "=r"(r[1]), "=r"(r[2]), "=r"(r[3]) : "r"(a) : "memory"); }
__device__ __forceinline__ void stsm4(uint32_t a, uint32_t r0, uint32_t r1, uint32_t r2, uint32_t r3) { asm volatile("stmatrix.sync.aligned.m8n8.x4.shared.b16 [%0], {%1,%2,%3,%4};" ::"r"(a), "r"(r0), "r"(r1), "r"(r2), "r"(r3) : "memory"); }
__device__ __forceinline__ void stsm4t(uint32_t a, uint32_t r0, uint32_t r1, uint32_t r2, uint32_t r3) { asm volatile("stmatrix.sync.aligned.m8n8.x4.trans.shared.b16 [%0], {%1,%2,%3,%4};" ::"r"(a), "r"(r0), "r"(r1), "r"(r2), "r"(r3) : "memory"); }
__device__ __forceinline__ uint32_t lds32(uint32_t a) { uint32_t v; asm volatile("ld.shared.u32 %0, [%1];" : "=r"(v) : "r"(a) : "memory"); return v; }
__device__ __forceinline__ uint2 lds64(uint32_t a) { uint2 v; asm volatile("ld.shared.v2.u32 {%0,%1}, [%2];" : "=r"(v.x), "=r"(v.y) : "r"(a) : "memory"); return v; }
__device__ __forceinline__ uint4 lds128(uint32_t a) { uint4 v; asm volatile("ld.shared.v4.u32 {%0,%1,%2,%3}, [%4];" : "=r"(v.x), "=r"(v.y), "=r"(v.z), "=r"(v.w) : "r"(a) : "memory"); return v; }
__device__ __forceinline__ void sts16(uint32_t a, uint32_t v) { asm volatile("st.shared.u16 [%0], %1;" ::"r"(a), "h"((unsigned short)v) : "memory"); }
__device__ __forceinline__ void sts32(uint32_t a, uint32_t v) { asm volatile("st.shared.u32 [%0], %1;" ::"r"(a), "r"(v) : "memory"); }
__device__ __forceinline__ void sts64(uint32_t a, uint32_t x, uint32_t y) { asm volatile("st.shared.v2.u32 [%0], {%1,%2};" ::"r"(a), "r"(x), "r"(y) : "memory"); }
__device__ __forceinline__ void sts128(uint32_t a, uint32_t x, uint32_t y, uint32_t z, uint32_t w) { asm volatile("st.shared.v4.u32 [%0], {%1,%2,%3,%4};" ::"r"(a), "r"(x), "r"(y), "r"(z), "r"(w) : "memory"); }
__device__ __forceinline__ float bflo(uint32_t v) { return __uint_as_float(v << 16); }
__device__ __forceinline__ float bfhi(uint32_t v) { return __uint_as_float(v & 0xffff0000u); }
__device__ __forceinline__ uint32_t pack_bf(float lo, float hi) { uint32_t r; asm("cvt.rn.bf16x2.f32 %0, %1, %2;" : "=r"(r) : "f"(hi), "f"(lo)); return r; }
__device__ __forceinline__ uint32_t pack_h(float lo, float hi) { uint32_t r; asm("cvt.rn.f16x2.f32 %0, %1, %2;" : "=r"(r) : "f"(hi), "f"(lo)); return r; }
__device__ __forceinline__ float rnd_bf(float v) { return __bfloat162float(__float2bfloat16_rn(v)); }
__device__ __forceinline__ float ex2a(float v) { float r; asm("ex2.approx.ftz.f32 %0, %1;" : "=f"(r) : "f"(v)); return r; }
__device__ __forceinline__ float tanha(float v) { float r; asm("tanh.approx.f32 %0, %1;" : "=f"(r) : "f"(v)); return r; }
__device__ __forceinline__ uint32_t hadd(uint32_t a, uint32_t b) { uint32_t r; asm("add.rn.f16x2 %0, %1, %2;" : "=r"(r) : "r"(a), "r"(b)); return r; }
__device__ __forceinline__ uint32_t badd(uint32_t a, uint32_t b) { uint32_t r; asm("add.rn.bf16x2 %0, %1, %2;" : "=r"(r) : "r"(a), "r"(b)); return r; }
__device__ __forceinline__ uint32_t bmul(uint32_t a, uint32_t b) { uint32_t r; asm("mul.rn.bf16x2 %0, %1, %2;" : "=r"(r) : "r"(a), "r"(b)); return r; }
__device__ __forceinline__ uint32_t bsub(uint32_t a, uint32_t b) { uint32_t r; asm("sub.rn.bf16x2 %0, %1, %2;" : "=r"(r) : "r"(a), "r"(b)); return r; }
__device__ __forceinline__ uint32_t dup(uint32_t v, uint32_t nz) { uint32_t r; asm volatile("add.rn.f32 %0, %1, %2;" : "=r"(r) : "r"(v), "r"(nz)); return r; }
__device__ __forceinline__ void bmma(float* c, uint32_t a0, uint32_t a1, uint32_t a2, uint32_t a3, uint32_t b0, uint32_t b1) {
  asm("mma.sync.aligned.m16n8k16.row.col.f32.bf16.bf16.f32 {%0,%1,%2,%3}, {%4,%5,%6,%7}, {%8,%9}, {%0,%1,%2,%3};"
      : "+f"(c[0]), "+f"(c[1]), "+f"(c[2]), "+f"(c[3]) : "r"(a0), "r"(a1), "r"(a2), "r"(a3), "r"(b0), "r"(b1));
}
__device__ __forceinline__ uint32_t odd_pair(uint32_t a, uint32_t b) { return __byte_perm(a, b, 0x5432); }
__device__ __forceinline__ int upos(int c) { return c ^ ((c >> 5) & 7) ^ ((c >> 3) & 1); }
__device__ __forceinline__ int uoff(int pos) { return (pos >> 1) * 160 + (pos & 1) * 16; }

struct cf { float r, i; };
__device__ __forceinline__ cf cmul(cf a, cf b) { cf o; o.r = fmaf(a.r, b.r, -a.i * b.i); o.i = fmaf(a.r, b.i, a.i * b.r); return o; }
__device__ __forceinline__ cf cmulj(cf a, cf b) { cf o; o.r = fmaf(a.r, b.r, a.i * b.i); o.i = fmaf(a.i, b.r, -a.r * b.i); return o; }
__device__ __forceinline__ cf csq(cf a) { cf o; o.r = fmaf(a.r, a.r, -a.i * a.i); o.i = (a.r + a.r) * a.i; return o; }
struct hp { uint32_t r, i; };
__device__ __forceinline__ hp hpack(cf a, cf b) { hp o; o.r = pack_h(a.r, b.r); o.i = pack_h(a.i, b.i); return o; }
__device__ __forceinline__ hp hmulc(hp a, uint32_t c) {
  __half2 ar = *reinterpret_cast<__half2*>(&a.r), ai = *reinterpret_cast<__half2*>(&a.i), cc = *reinterpret_cast<__half2*>(&c);
  __half2 orr = __hfma2(ar, __low2half2(cc), __hneg2(__hmul2(ai, __high2half2(cc))));
  __half2 oi = __hfma2(ar, __high2half2(cc), __hmul2(ai, __low2half2(cc)));
  hp o; o.r = *reinterpret_cast<uint32_t*>(&orr); o.i = *reinterpret_cast<uint32_t*>(&oi); return o;
}
__device__ __forceinline__ hp hmulj(hp a, uint32_t c) {
  __half2 ar = *reinterpret_cast<__half2*>(&a.r), ai = *reinterpret_cast<__half2*>(&a.i), cc = *reinterpret_cast<__half2*>(&c);
  __half2 orr = __hfma2(ar, __low2half2(cc), __hmul2(ai, __high2half2(cc)));
  __half2 oi = __hfma2(ai, __low2half2(cc), __hneg2(__hmul2(ar, __high2half2(cc))));
  hp o; o.r = *reinterpret_cast<uint32_t*>(&orr); o.i = *reinterpret_cast<uint32_t*>(&oi); return o;
}
__device__ __forceinline__ void sts_tile(uint32_t a, const hp* t) {
  sts128(a, t[0].r, t[1].r, t[2].r, t[3].r);
  sts128(a + 512, t[0].i, t[1].i, t[2].i, t[3].i);
}
template <int STEP> __device__ __forceinline__ void put2(uint32_t a0, uint32_t a1, uint32_t h, uint32_t sel) {
  const uint32_t x = __byte_perm(h, h, sel), y = x >> 16;
  sts16(a0, x); sts16(a0 + STEP * 4 + 2, x);
  sts16(a1, y); sts16(a1 + STEP * 4 + 2, y);
}

__device__ __forceinline__ void spare_work(const Params& p, const CUtensorMap* tmW1, int k, int tid) {
  const int lane = tid & 31;
  unsigned ep = 0;
  if (tid >= 480) ep = p.scr->epoch[128 + k] + 1;
  if (tid == 480) {
    for (int i = 0; i < 8; i++) mbar_init(bar + 8 * i, i < 4 ? 1 : 12);
    asm volatile("fence.mbarrier_init.release.cluster;" ::: "memory");
    fence_async_smem();
  }
  __syncthreads();
  float a[2][4] = {{0.f, 0.f, 0.f, 0.f}, {0.f, 0.f, 0.f, 0.f}};
  if (tid >= 480) {
    if (elect1()) {
      if (SPARE_NS) __nanosleep(SPARE_NS);
#pragma unroll 1
      for (int s = 0; s < 10; s++) {
        mbar_wait(bar + 8 * (4 + (s & 3)), ((s >> 2) & 1) ^ 1);
        mbar_expect(bar + 8 * (s & 3), 49152);
#pragma unroll 1
        for (int b = 0; b < 2; b++) tma3d(sb + (s & 3) * 49152 + b * 24576, tmW1, 0, s * 64, k * 6 + b * 3, bar + 8 * (s & 3));
      }
    }
    __syncwarp();
  } else if (tid < 384) {
    const uint32_t idn = (lane >> 3) == (lane & 3) ? ((lane & 4) ? 0x3f800000u : 0x3f80u) : 0u;
#pragma unroll 1
    for (int s = 0; s < 10; s++) {
      mbar_wait(bar + 8 * (s & 3), (s >> 2) & 1);
      const uint32_t ad = sb + (s & 3) * 49152 + (tid >> 6) * 8192 + (tid & 63) * 16;
#pragma unroll
      for (int i = 0; i < 8; i += 2) {
        const uint4 v = lds128(ad + i * 1024), w = lds128(ad + i * 1024 + 1024);
        bmma(a[0], v.x, v.y, w.x, w.y, idn, idn);
        bmma(a[1], v.z, v.w, w.z, w.w, idn, idn);
      }
      __syncwarp();
      if (lane == 0) mbar_arrive(bar + 8 * (4 + (s & 3)));
    }
    const int rho = (tid >> 3) & 7;
    const uint32_t ad = sb + 196608 + rho * 1536 + ((tid >> 6) * 8 + ((tid & 7) ^ rho)) * 32;
    sts128(ad, __float_as_uint(a[0][0]), __float_as_uint(a[0][1]), __float_as_uint(a[0][2]), __float_as_uint(a[0][3]));
    sts128(ad + 16, __float_as_uint(a[1][0]), __float_as_uint(a[1][1]), __float_as_uint(a[1][2]), __float_as_uint(a[1][3]));
  }
  __syncthreads();
  if (tid < 384) {
    float s = 0.f;
#pragma unroll
    for (int r = 0; r < 8; r++) s += __uint_as_float(lds32(sb + 196608 + r * 1536 + tid * 4));
    p.scr->cs[k * 384 + tid] = s;
  }
  __syncthreads();
  if (tid == 480) {
    publish(p.scr->cnt + C_CS * 32);
    p.scr->epoch[128 + k] = ep;
    poll_cnt(p.scr->cnt + C_LN * 32, ep * 128);
  }
}

__device__ __forceinline__ void load1(int s, const CUtensorMap* tmX, const CUtensorMap* tmW1, int rg1, int j1) {
  const uint32_t d = sb + (s & 3) * SLOT1, mb = bar + 8 * (B_FULL1 + s);
  mbar_expect(mb, SLOT1);
  tma2d(d, tmX, s * 64, rg1 * 128, mb);
  tma3d(d + 16384, tmW1, 0, s * 64, j1 * 3, mb);
}
__device__ __forceinline__ void load_x(uint32_t (&xv)[2][10], const __nv_bfloat16* xc, int rstep, int q) {
#pragma unroll
  for (int r = 0; r < 2; r++) {
    const uint4 a = __ldg((const uint4*)(xc + r * rstep) + q), b = __ldg((const uint4*)(xc + r * rstep) + 4 + q);
    const uint2 c = __ldg((const uint2*)(xc + r * rstep + 64) + q);
    xv[r][0] = a.x; xv[r][1] = a.y; xv[r][2] = a.z; xv[r][3] = a.w; xv[r][4] = b.x; xv[r][5] = b.y; xv[r][6] = b.z; xv[r][7] = b.w;
    xv[r][8] = c.x; xv[r][9] = c.y;
  }
}

__device__ __forceinline__ uint32_t pin(uint32_t v, uint32_t z) { uint32_t r; asm volatile("add.u32 %0, %1, %2;" : "=r"(r) : "r"(v), "r"(z)); return r; }
struct Comb { uint32_t o[7]; };
__device__ __forceinline__ Comb comb_setup(int tid, uint32_t z) {
  Comb k;
  const int c = tid & 127, c1 = c < 112 ? c + 32 : c - 112, c2 = c < 112 ? c + 144 : c - 96;
  const uint32_t zr = ZA1 + (c & 7) * 16, a2 = ZA2 + ((c & ~15) - 32 + ((((c >> 1) & 7) + (c & 1) * 8) ^ ((c & 1) * 4))) * 16;
  k.o[0] = uoff(upos(c1)); k.o[1] = uoff(upos(c2));
  k.o[2] = c < 112 ? ZA1 + 512 + ((2 * c) ^ ((c >> 2) & 1)) * 16 : zr;
  k.o[3] = c1 >= 64 ? a2 : zr; k.o[4] = c < 112 ? a2 + 112 * 16 : zr;
  k.o[5] = ((c1 >> 4) * 1280 + (c & 15)) * 16; k.o[6] = ((c2 >> 4) * 1280 + (c & 15)) * 16;
#pragma unroll
  for (int i = 0; i < 7; i++) k.o[i] = pin(k.o[i], z);
  return k;
}
__device__ __forceinline__ void combine(const Comb& k, int ch, int wid, uint4* sT) {
  const uint32_t ub = sb + OFF_U + ch * 32, zb = sb + OFF_Z + ch * ZSZ;
  const int row = (wid & 15) * 5 + ch;
  char* dst = (char*)(sT + ((wid >> 4) * 16 * 80 + row) * 16);
  mbar_wait(bar + 8 * (B_PART + ch), 0);
  const uint32_t sc = lds32(sb + OFF_CHC + ch * 8);
  const uint4 y0 = lds128(zb + k.o[2]), y1 = lds128(zb + (k.o[2] ^ 16));
  const uint4 v2 = lds128(zb + k.o[3]), u2 = lds128(zb + k.o[4]);
  const uint4 v0 = lds128(ub + k.o[0]), u0 = lds128(ub + k.o[1]);
  fence_async_smem();
  *(uint4*)(dst + (k.o[5] ^ ((row & 7) * 16))) =
      make_uint4(bmul(badd(badd(y0.x, v2.x), v0.x), sc), bmul(badd(badd(y0.y, v2.y), v0.y), sc),
                 bmul(badd(badd(y1.x, v2.z), v0.z), sc), bmul(badd(badd(y1.y, v2.w), v0.w), sc));
  *(uint4*)(dst + (k.o[6] ^ ((row & 7) * 16))) =
      make_uint4(bmul(badd(badd(y0.z, u2.x), u0.x), sc), bmul(badd(badd(y0.w, u2.y), u0.y), sc),
                 bmul(badd(badd(y1.z, u2.z), u0.z), sc), bmul(badd(badd(y1.w, u2.w), u0.w), sc));
  __syncwarp();
  if (elect1()) mbar_arrive(bar + 8 * (B_FREE + ch));
}

template <bool USE_SMID>
__global__ void __launch_bounds__(512, 1)
fused_s4_ffn_kernel(const Params p, const __grid_constant__ CUtensorMap tmX, const __grid_constant__ CUtensorMap tmW1,
                    const __grid_constant__ CUtensorMap tmU, const __grid_constant__ CUtensorMap tmW2) {
  extern __shared__ __align__(1024) unsigned char smem_raw[];
  const int tid = threadIdx.x, lane = tid & 31;
  uint32_t sid;
  if (USE_SMID) asm("mov.u32 %0, %smid;" : "=r"(sid)); else sid = blockIdx.x;
  const int wid = sid < 120 ? sid : sid - 4;
  uint32_t pa[6], pld, pds;
  {
    const unsigned w = min(tid >> 5, 14), part = (w * 13) >> 6;
    const unsigned ch = (wid >> 4) * 80 + frag_col(((wid & 15) - part) * 5 + w);
    const unsigned o = (ch * 3 + part) * 32 + lane;
    pa[4] = __ldg((const uint32_t*)p.cre + o); pa[5] = __ldg((const uint32_t*)p.cim + o);
    pa[2] = __ldg((const uint32_t*)p.bre + o); pa[3] = __ldg((const uint32_t*)p.bim + o);
    pa[0] = __ldg((const uint32_t*)p.are + o); pa[1] = __ldg((const uint32_t*)p.aim + o);
    pld = __ldg((const unsigned short*)p.logdt + ch);
    pds = __ldg((const unsigned short*)p.dskip + ch);
  }
  const int warp = __shfl_sync(0xffffffffu, tid >> 5, 0);
  const int g = lane >> 2, q = lane & 3;
  if (sid - 120u < 4u) { spare_work(p, &tmW1, sid - 120, tid); return; }
  unsigned* const cnt = p.scr->cnt;

  float kacc[5][4];
  const int kch = warp - 10;
  float dt, k0;
  uint32_t xv[2][10], xs[2], mw;
  {
    unsigned ep0;
    if (warp == 15) {
      ep0 = p.scr->epoch[wid];
      if ((uint32_t)__cvta_generic_to_shared(smem_raw) != sb) __trap();
    }
    if (elect1()) {
      const int gi = (warp + 1) & 15;
#pragma unroll
      for (int i = 0; i < 6; i++) mbar_init(bar + 48 * gi + 8 * i, gi < 7 ? 1 : gi == 7 ? 2 : gi < 10 ? 4 : 8);
      asm volatile("fence.mbarrier_init.release.cluster;" ::: "memory");
    }
    if (warp == 15) {
      sts32(sb + OFF_ZERO + lane * 4, 0);
      int gpc, i;
      if (sid < 64) { gpc = (sid & 15) >> 1; i = sid >> 4; }
      else if (sid < 120) { const int t = sid - 64; i = t / 14; gpc = 1 + ((t - i * 14) >> 1); i += 4; }
      else { gpc = 0; i = 4 + ((sid - 124) >> 1); }
      const int qi = ((0x52741630 >> (4 * i)) & 7) * 2 + (sid & 1);
      const int rg = 4 * (gpc >> 1) + (qi >> 2), jc = 4 * (gpc & 1) + (qi & 3);
      sts64(sb + OFF_EP + 8, rg, jc);
      __syncwarp();
      if (GATE) sts32(sb + OFF_EP + 4, pa[0] ^ pa[1] ^ pa[2] ^ pa[3] ^ pa[4] ^ pa[5]);
      if (elect1()) {
        if (DELAY_NS) __nanosleep(DELAY_NS);
        bulk_prefetch(p.x + wid * 16 * DM, 16 * DM * 2);
#pragma unroll 1
        for (int s = 0; s < 4; s++) load1(s, &tmX, &tmW1, rg, jc);
        bulk_prefetch(p.w1 + wid * 5 * FF, 5 * FF * 2);
        bulk_prefetch(p.w2 + wid * 12 * DM, 12 * DM * 2);
        asm volatile("prefetch.tensormap [%0];\nprefetch.tensormap [%1];" ::"l"(&tmU), "l"(&tmW2) : "memory");
      }
    }
#pragma unroll
    for (int j = 0; j < 5; j++) { kacc[j][0] = kacc[j][1] = kacc[j][2] = kacc[j][3] = 0.f; }
    float zr, th, zr1, th1;
    cf c, c1;
    const uint32_t ks = sb + OFF_KS + warp * 4096;
    if (warp < 15) {
      dt = rnd_bf(expf(bflo(pld)));
      c = cmul(cf{bflo(pa[4]), bflo(pa[5])}, cf{bflo(pa[2]), bflo(pa[3])});
      c1 = cmul(cf{bfhi(pa[4]), bfhi(pa[5])}, cf{bfhi(pa[2]), bfhi(pa[3])});
      mw = __reduce_max_sync(0xffffffffu, __float_as_uint(fmaxf(fmaxf(fabsf(c.r), fabsf(c.i)), fmaxf(fabsf(c1.r), fabsf(c1.i)))));
      mw = min(max(mw & 0x7f800000u, 20u << 23), 240u << 23);
      const float sc = __uint_as_float((259u << 23) - mw), dl2 = dt * 1.4426950408889634f;
      k0 = c.r + c1.r;
      zr = bflo(pa[0]) * dl2; th = bflo(pa[1]) * dt; zr1 = bfhi(pa[0]) * dl2; th1 = bfhi(pa[1]) * dt;
      c.r *= sc; c.i *= -sc; c1.r *= sc; c1.i *= -sc;
    }
    __syncwarp();
    if (warp >= 8) {
      const __nv_bfloat16* xr = p.x + (wid * 16 + ((g >> 1) << 2) + (g & 1)) * DM;
      load_x(xv, xr + (warp - 8) * 80, 2 * DM, q);
      xs[0] = __ldg((const uint32_t*)xr); xs[1] = __ldg((const uint32_t*)(xr + 2 * DM));
    }
    {
      const uint32_t ka = ks + (lane >> 3) * 512 + (lane & 7) * 16;
      const uint32_t kb = ks + ((lane >> 3) & 1) * 512 + ((lane >> 4) * 8 + (lane & 7)) * 16;
#pragma unroll 1
      for (int it = 0; it < 2; it++) {
        if (it == 1 && warp >= 8) {
          float sm[4] = {0.f, 0.f, 0.f, 0.f}, g0[4] = {0.f, 0.f, 0.f, 0.f}, g1[4] = {0.f, 0.f, 0.f, 0.f};
#pragma unroll
          for (int r = 0; r < 2; r++)
            xs[r] = fabsf(bflo(xs[r]) - bfhi(xs[r])) * 8.f < fabsf(bflo(xs[r])) ? __byte_perm(xs[r], 0, 0x1010) : 0u;
#pragma unroll
          for (int i = 0; i < 10; i += 2) {
            const uint32_t a0 = bsub(xv[0][i], xs[0]), a1 = bsub(xv[1][i], xs[1]), a2 = bsub(xv[0][i + 1], xs[0]), a3 = bsub(xv[1][i + 1], xs[1]);
            bmma(sm, a0, a1, a2, a3, 0x3f803f80u, 0x3f803f80u);
            bmma(g0, a0, a1, a2, a3, xv[0][i], xv[0][i + 1]);
            bmma(g1, a0, a1, a2, a3, xv[1][i], xv[1][i + 1]);
          }
          if (q == (g >> 1))
            sts128(sb + OFF_LNP + (warp - 8) * 128 + g * 16, __float_as_uint(sm[0]), __float_as_uint((g & 1) ? g0[1] : g0[0]),
                   __float_as_uint(sm[2]), __float_as_uint((g & 1) ? g1[3] : g1[2]));
          if (warp < 15) bar_arrive(1, 256);
        }
        if (warp == 15) continue;
        float m = ex2a(zr);
        const cf w1 = cf{m * __cosf(th), m * __sinf(th)};
        m = ex2a(zr * 8.f);
        const cf w8 = cf{m * __cosf(th * 8.f), m * __sinf(th * 8.f)};
        const cf w16 = csq(w8), w32 = csq(w16), w64 = csq(w32), w128 = csq(w64), w256 = csq(w128), w512 = csq(w256), w1024 = csq(w512);
        hp lo[8];
        lo[0] = hpack(cf{1.f, 0.f}, w8);
        lo[1] = hmulc(lo[0], pack_h(w16.r, w16.i));
        { const uint32_t k = pack_h(w32.r, w32.i); lo[2] = hmulc(lo[0], k); lo[3] = hmulc(lo[1], k); }
        { const uint32_t k = pack_h(w64.r, w64.i);
#pragma unroll
          for (int i = 0; i < 4; i++) lo[4 + i] = hmulc(lo[i], k); }
        const uint32_t st = ks + lane * 16;
        sts128(st + 512, lo[4].r, lo[5].r, lo[6].r, lo[7].r);
        sts128(st + 1536, lo[4].i, lo[5].i, lo[6].i, lo[7].i);
        sts128(st, lo[0].r, lo[1].r, lo[2].r, lo[3].r);
        sts128(st + 1024, lo[0].i, lo[1].i, lo[2].i, lo[3].i);
        const uint32_t k128 = pack_h(w128.r, w128.i), k256 = pack_h(w256.r, w256.i), k512 = pack_h(w512.r, w512.i);
        const cf t8 = cmulj(c, w8);
        hp T0[4], T1[4], T2[4], T3[4], T4[4];
        { const cf u0 = cmulj(t8, w1024), u1 = cmulj(u0, w128);
          T4[0] = hpack(u0, u1); T4[1] = hmulj(T4[0], k256); T4[2] = hmulj(T4[0], k512); T4[3] = hmulj(T4[1], k512); }
        sts_tile(st + 2048, T4);
        __syncwarp();
        uint32_t af[4][4];
#pragma unroll
        for (int mg = 0; mg < 4; mg++) ldsm4t(af[mg], ka + mg * 128);
#pragma unroll
        for (int mg = 0; mg < 4; mg += 2) {
          uint32_t b[4];
          ldsm4t(b, kb + 2048 + mg * 128);
          hmma(kacc[4], af[mg][0], af[mg][1], af[mg][2], af[mg][3], b[0], b[1]);
          hmma(kacc[4], af[mg + 1][0], af[mg + 1][1], af[mg + 1][2], af[mg + 1][3], b[2], b[3]);
        }
        const cf t1 = cmulj(c, w1), t2 = cmulj(t1, w1), t3 = cmulj(t2, w1), t4 = cmulj(t3, w1);
        const cf t5 = cmulj(t4, w1), t6 = cmulj(t5, w1), t7 = cmulj(t6, w1);
        T0[0] = hpack(t4, t8); T0[1] = hpack(t2, t6); T0[2] = hpack(t1, t5); T0[3] = hpack(t3, t7);
#pragma unroll
        for (int i = 0; i < 4; i++) T1[i] = hmulj(T0[i], k128);
        T2[0] = hmulj(T0[0], k256); T2[1] = hmulj(T0[1], k256); T2[2] = hmulj(T1[0], k256); T2[3] = hmulj(T1[1], k256);
        T3[0] = hmulj(T0[0], k512); T3[1] = hmulj(T1[0], k512); T3[2] = hmulj(T2[0], k512); T3[3] = hmulj(T2[2], k512);
        __syncwarp();
        sts_tile(st + 3072, T3);
        sts_tile(st + 2048, T2);
        sts_tile(st + 1024, T1);
        sts_tile(st, T0);
        __syncwarp();
#pragma unroll
        for (int mg = 0; mg < 4; mg += 2)
#pragma unroll
          for (int j = 3; j >= 0; j--) {
            uint32_t b[4];
            ldsm4t(b, kb + j * 1024 + mg * 128);
            hmma(kacc[j], af[mg][0], af[mg][1], af[mg][2], af[mg][3], b[0], b[1]);
            hmma(kacc[j], af[mg + 1][0], af[mg + 1][1], af[mg + 1][2], af[mg + 1][3], b[2], b[3]);
          }
        __syncwarp();
        zr = zr1; th = th1; c = c1;
      }
    }
    if (warp < 10) {
#pragma unroll
      for (int j = 0; j < 5; j++)
        sts128(ks + j * 512 + lane * 16, __float_as_uint(kacc[j][0]), __float_as_uint(kacc[j][1]), __float_as_uint(kacc[j][2]), __float_as_uint(kacc[j][3]));
      sts64(ks + 2560 + lane * 8, __float_as_uint(k0), mw);
    } else if (warp == 15) {
      if (lane == 0) { p.scr->epoch[wid] = ep0 + 1; sts32(sb + OFF_EP, ep0 + 1); }
      bar_sync(1, 256);
      float s1 = 0.f, s2 = 0.f;
#pragma unroll
      for (int w = 0; w < 8; w++) {
        const uint2 v = lds64(sb + OFF_LNP + w * 128 + g * 16 + (q & 1) * 8);
        s1 += __uint_as_float(v.x); s2 += __uint_as_float(v.y);
      }
      const float md = s1 * (1.f / DM), mean = bflo((q & 1) ? xs[1] : xs[0]) + md;
      const float var = fmaxf(fmaf(-md, mean, s2 * (1.f / DM)), 0.f);
      const float m = rnd_bf(mean);
      float sd, ri;
      asm("sqrt.approx.f32 %0, %1;" : "=f"(sd) : "f"(rnd_bf(rnd_bf(var) + 1e-5f)));
      asm("rcp.approx.f32 %0, %1;" : "=f"(ri) : "f"(rnd_bf(sd)));
      if (q < 2) {
        p.scr->stats[wid * 16 + ((g >> 1) << 2) + (g & 1) + 2 * q] = make_float2(-m, 0.5f * ri);
        sts64(sb + OFF_STAT + g * 16 + q * 8, __float_as_uint(-m * ri), __float_as_uint(ri));
      }
    }
  }
  __syncthreads();

  if (warp < 8) {
    float acc[96];
    const uint32_t alo = ((sb >> 4) | (1 << 16)) + (warp >> 2) * 512;
#pragma unroll 1
    for (int s = 0; s < 10; s++) {
      const uint32_t so = (s & 3) * (SLOT1 >> 4);
      mbar_wait(bar + 8 * (B_FULL1 + s), 0);
      wg_fence();
#pragma unroll
      for (int kk = 0; kk < 4; kk++)
        wgmma_n192(acc, dsc(alo + so + kk * 2, 0x40000040u), dsc((((sb + 16384) >> 4) | (512 << 16)) + so + kk * 128, 0x40000040u), (s | kk) != 0);
      wg_commit();
      wg_wait<1>();
      if (lane == 0) mbar_arrive(bar + 8 * (B_REL1 + s));
    }
    wg_wait<0>();
    bar_arrive(14, 384);
    bar_arrive(7, 384);
    mbar_wait(bar + 8 * B_EPI, 0);
    const uint2 s0 = lds64(sb + OFF_STAT + (warp * 16 + g) * 8), s1 = lds64(sb + OFF_STAT + (warp * 16 + g + 8) * 8);
    const float nm0 = __uint_as_float(s0.x), r0 = __uint_as_float(s0.y), nm1 = __uint_as_float(s1.x), r1 = __uint_as_float(s1.y);
    const uint4 erj = lds128(sb + OFF_EP);
    const unsigned ep = erj.x;
    const int rg1 = erj.z, j1 = erj.w;
    uint4* hd = p.scr->h + (rg1 * 24 + j1) * 1024 + warp * 128 + q * 8 + g;
#pragma unroll
    for (int grp = 0; grp < 6; grp++) {
      uint32_t o0[4], o1[4];
#pragma unroll
      for (int tl = 0; tl < 4; tl++) {
        const int nt = grp * 4 + tl;
        const uint2 cs = lds64(sb + OFF_CS + (nt * 8 + 2 * q) * 4);
        const float ca = __uint_as_float(cs.x), cb = __uint_as_float(cs.y);
        const float a = fmaf(nm0, ca, acc[4 * nt]) * r0, b = fmaf(nm0, cb, acc[4 * nt + 1]) * r0;
        const float c = fmaf(nm1, ca, acc[4 * nt + 2]) * r1, d = fmaf(nm1, cb, acc[4 * nt + 3]) * r1;
        o0[tl] = pack_bf(fmaf(a, tanha(a), a), fmaf(b, tanha(b), b));
        o1[tl] = pack_bf(fmaf(c, tanha(c), c), fmaf(d, tanha(d), d));
      }
      uint4* dst = hd + (grp >> 1) * 8192 + (grp & 1) * 32;
      dst[0] = make_uint4(o0[0], o0[1], o0[2], o0[3]);
      dst[64] = make_uint4(o1[0], o1[1], o1[2], o1[3]);
      if (PACE_NS) __nanosleep(PACE_NS);
      if (grp == 1) {
        if (warp == 7) { bar_sync(2, 448); if (lane == 0) publish(cnt + C_H0 * 32); __syncwarp(); }
        else bar_arrive(2, 448);
      }
    }
    if (warp == 6) { bar_sync(11, 256); if (lane == 0) publish(cnt + (C_H1 + rg1) * 32); __syncwarp(); }
    else bar_arrive(11, 256);
    const int go = (rg1 * 128 + warp * 16 + g) * DM + j1 * 80;
    load_x(xv, p.x + go, 8 * DM, q);
    if (warp < 4) {
      const Comb cmb = comb_setup(tid, 0);
#pragma unroll 1
      for (int ch = 0; ch < 3; ch++) {
        combine(cmb, ch, wid, p.scr->sT);
      }
    } else if (warp == 4) {
      if (elect1()) {
        poll_cnt(cnt + C_H0 * 32, ep * 128);
#pragma unroll 1
        for (int s = 0; s < NS2 - 2; s++) {
          if (s == 3) poll_cnt(cnt + (C_H1 + rg1) * 32, ep * 8);
          if (s == 3) mbar_wait(bar + 8 * B_FREE, 0);
          if (s >= 3) mbar_wait(bar + 8 * (B_FREE + s - 2), 0);
          const uint32_t mb = bar + 8 * (B_FULL2 + s);
          mbar_expect(mb, SLOT2);
          bulk_g2s(sb + s * SLOT2, p.scr->h + (rg1 * 24 + s) * 1024, 16384, mb);
          bulk_g2s(sb + s * SLOT2 + 16384, p.scr->w2p + (j1 * 24 + s) * 640, 10240, mb);
        }
      }
      __syncwarp();
    }
    float acc2[40];
    bar_sync(8, 512);
    {
      const uint32_t al2 = ((sb >> 4) | (8 << 16)) + (warp >> 2) * 512;
      uint32_t so = 0;
#pragma unroll 1
      for (int s = 0; s < 24; s++) {
        mbar_wait(bar + 8 * (B_FULL2 + s), 0);
        wg_fence();
#pragma unroll
        for (int kk = 0; kk < 4; kk++)
          wgmma_n80(acc2, dsc(al2 + so + kk * 16, 64), dsc((((sb + 16384) >> 4) | (80 << 16)) + so + kk * 160, 8), (s | kk) != 0);
        wg_commit();
        so = so == (NS2 - 1) * (SLOT2 >> 4) ? 0 : so + (SLOT2 >> 4);
        wg_wait<1>();
        if (lane == 0) mbar_arrive(bar + 8 * (B_REL2 + s));
      }
    }
    mbar_wait(bar + 8 * B_SFULL, 0);
    uint32_t sv[5][4];
    {
      const int i = lane & 7, mi = lane >> 3;
      const uint32_t a = sb + OFF_U + ((mi >> 1) * 8 + i) * 256 + (((2 * warp + (mi & 1)) ^ i) << 4);
#pragma unroll
      for (int k = 0; k < 5; k++) ldsm4t(sv[k], a + k * 4096);
    }
    wg_wait<0>();
#pragma unroll
    for (int hh = 0; hh < 2; hh++) {
      uint32_t o[10];
#pragma unroll
      for (int tl = 0; tl < 10; tl++) {
        const uint32_t xw = xv[hh][tl];
        const uint32_t sw = sv[tl >> 1][(tl & 1) * 2 + hh];
        const float a = acc2[4 * tl + 2 * hh], b = acc2[4 * tl + 2 * hh + 1];
        o[tl] = pack_bf(fmaf(bflo(sw), fmaf(a, tanha(a), a), bflo(xw)), fmaf(bfhi(sw), fmaf(b, tanha(b), b), bfhi(xw)));
      }
      __nv_bfloat16* op = p.out + go + hh * 8 * DM;
      ((uint4*)op)[q] = make_uint4(o[0], o[1], o[2], o[3]);
      ((uint4*)op)[4 + q] = make_uint4(o[4], o[5], o[6], o[7]);
      ((uint2*)(op + 64))[q] = make_uint2(o[8], o[9]);
    }
  } else {
    const int cw = warp - 8;
    const uint4 erj = lds128(sb + OFF_EP);
    const unsigned ep = erj.x;
    const int rg1 = erj.z, j1 = erj.w;
    {
      const uint4 st = lds128(sb + OFF_STAT + g * 16);
      const float n0 = __uint_as_float(st.x), r0 = __uint_as_float(st.y), n1 = __uint_as_float(st.z), r1 = __uint_as_float(st.w);
      const int up = upos(2 * wid);
      uint2* dst = (uint2*)p.scr->uT + ((up >> 1) * DM + cw * 80) * 4 + (lane ^ ((up & 1) << 1));
#pragma unroll
      for (int i = 0; i < 10; i++) {
        const uint32_t a = movm(pack_h(fmaf(bflo(xv[0][i]), r0, n0), fmaf(bfhi(xv[0][i]), r0, n0)));
        const uint32_t b = movm(pack_h(fmaf(bflo(xv[1][i]), r1, n1), fmaf(bfhi(xv[1][i]), r1, n1)));
        dst[i * 32] = make_uint2(a, b);
      }
    }
    if (warp == 8) {
      bar_sync(12, 256);
      if (lane == 0) publish(cnt + C_LN * 32);
      __syncwarp();
    } else bar_arrive(12, 256);
    if (warp == 15) {
      if (elect1()) {
#pragma unroll 1
        for (int s = 4; s < 10; s++) {
          mbar_wait(bar + 8 * (B_REL1 + s - 3), 0);
          load1(s, &tmX, &tmW1, rg1, j1);
        }
      }
      __syncwarp();
    }
    if (warp >= 10 && warp < 15) {
      const uint32_t pb = sb + OFF_P + kch * 3072, pk = sb + OFF_KS + kch * 4096;
      const uint2 e0 = lds64(pk + 2560 + lane * 8), e1 = lds64(pk + 5 * 4096 + 2560 + lane * 8);
      const float dsk = bflo(pds);
      uint32_t kex = __float_as_uint(fmaxf(__uint_as_float(max(max(e0.y, e1.y), mw)) * dt, fabsf(dsk) * (1.f / 256.f))) >> 23;
      kex = min(max(kex, 20u), 240u);
      const float s2 = __uint_as_float((258 - kex) << 23), sd = s2 * dt * (1.f / 32.f);
      const float f0 = __uint_as_float(e0.y) * sd, f1 = __uint_as_float(e1.y) * sd, f2 = __uint_as_float(mw) * sd;
      k0 += __uint_as_float(e0.x) + __uint_as_float(e1.x);
#pragma unroll
      for (int o = 16; o; o >>= 1) k0 += __shfl_xor_sync(0xffffffffu, k0, o);
      const float k0n = fmaf(k0, dt, dsk) * s2;
      uint32_t h[5][2];
#pragma unroll
      for (int j = 0; j < 5; j++) {
        const uint4 a = lds128(pk + j * 512 + lane * 16), b = lds128(pk + 5 * 4096 + j * 512 + lane * 16);
#pragma unroll
        for (int e = 0; e < 4; e++) kacc[j][e] = fmaf(__uint_as_float((&a.x)[e]), f0, fmaf(__uint_as_float((&b.x)[e]), f1, kacc[j][e] * f2));
        if (j == 1) {
          const float k256 = __shfl_sync(0xffffffffu, kacc[1][3], 28);
          if (lane == 31) kacc[1][3] -= k256;
        }
        if (j == 2 || j == 3) { h[j][0] = pack_h(kacc[j][0], kacc[j][2]); h[j][1] = pack_h(kacc[j][1], kacc[j][3]); }
        else { h[j][0] = pack_h(kacc[j][0], kacc[j][1]); h[j][1] = pack_h(kacc[j][2], kacc[j][3]); }
      }
      fence_async_smem();
      bar_arrive(4, 192);
#pragma unroll
      for (int i = 0; i < 6; i++) sts128(pb + i * 512 + lane * 16, 0, 0, 0, 0);
      __syncwarp();
      {
        const int sw = g >> 2;
        const uint32_t sel = sw ? 0x1032 : 0x3210;
        const uint32_t a = pb + (P0 + 8 * g + ((0x3124 >> (4 * q)) & 7)) * 4, a0 = a + sw * 16, a1 = a + 16 - sw * 16;
        put2<1>(a0, a1, h[0][0], sel);
        put2<1>(a0 + 256, a1 + 256, h[0][1], sel);
        put2<1>(a0 + 512, a1 + 512, h[1][0], sel);
        put2<1>(lane == 28 ? pb + PB1 * 4 : a0 + 768, a1 + 768, h[1][1], sel);
      }
      {
        const int sw = q >> 1;
        const uint32_t sel = sw ? 0x1032 : 0x3210;
        uint32_t a = pb + (((q & 1) ? PA1 : PB1 + 1) + 32 * sw + 2 * g) * 4;
        put2<1>(a + sw * 64, a + 64 - sw * 64, h[2][0], sel);
        put2<1>(a + 4 + sw * 64, a + 68 - sw * 64, h[2][1], sel);
        a = pb + (PA2 + g + 16 * q) * 4;
        put2<2>(a + sw * 32, a + 32 - sw * 32, h[3][0], sel);
        put2<2>(a + (PB2 - PA2) * 4 + sw * 32, a + (PB2 - PA2) * 4 + 32 - sw * 32, h[3][1], sel);
        a = pb + (((g & 1) ? PB3 : PA3) + (g >> 1) + 16 * q) * 4;
        const uint32_t hx = sw ? h[4][1] : h[4][0], hy = sw ? h[4][0] : h[4][1];
        put2<1>(a + sw * 16, a + 32 + sw * 16, hx, 0x3210);
        put2<1>(a + 16 - sw * 16, a + 48 - sw * 16, hy, 0x3210);
      }
      if (lane == 30) put2<1>(pb + P0 * 4, pb + (PA1 + 64) * 4, pack_h(k0n, kacc[2][3]), 0x3210);
      if (lane == 31) sts64(sb + OFF_CHC + kch * 8, (kex - 4) * 0x00800080u, __byte_perm(h[3][1], 0, 0x3232));
    }
    if (warp == 8) {
      bar_sync(13, 64);
      if (elect1()) {
        mbar_expect(bar + 8 * B_UFULL, 144 * 160);
        mbar_expect(bar + 8 * B_EPI, 1024 + 768);
        poll_cnt(cnt + C_LN * 32, ep * 128);
        tma2d(sb + OFF_U - 16 * 160, &tmU, wid * 80, -16, bar + 8 * B_UFULL);
        bulk_g2s(sb + OFF_STAT, p.scr->stats + rg1 * 128, 1024, bar + 8 * B_EPI);
      }
      __syncwarp();
      bar_arrive(15, 224);
    } else if (warp == 9) {
      bar_sync(4, 192);
      bar_arrive(13, 64);
      if (elect1()) {
        mbar_expect(bar + 8 * B_W2, 96 * 176);
        tma5d(sb + OFF_W2S, &tmW2, (wid & 7) * 80, (wid >> 3) * 3, bar + 8 * B_W2);
        poll_cnt(cnt + C_CS * 32, ep * 4);
        bulk_g2s(sb + OFF_CS, p.scr->cs + j1 * 192, 768, bar + 8 * B_EPI);
      }
      __syncwarp();
    }
    if (warp >= 9 && warp < 15) {
      const int uu = (warp - 9) >> 1, G = (warp - 9) & 1;
      const int grp = (wid >> 3) * 3 + uu, jj = grp / 6, rem = grp - jj * 6;
      const uint32_t a = sb + OFF_W2S + (uu * 32 + lane) * 176;
      uint4* dst = p.scr->w2p + ((wid & 7) * 24 + 8 * (rem >> 1) + jj) * 640 + ((rem & 1) * 4 + (lane >> 3)) * 80 + (lane & 7);
      mbar_wait(bar + 8 * B_W2, 0);
      const uint4 wv[4] = {lds128(a + G * 64), lds128(a + G * 64 + 16), lds128(a + G * 64 + 32), lds128(a + G * 64 + 48)};
      const uint4 t0 = lds128(a + 128), t1 = lds128(a + 144);
      uint32_t w[20];
#pragma unroll
      for (int i = 0; i < 16; i++) w[i] = bmul((&wv[i >> 2].x)[i & 3], 0x3f003f00u);
      w[16] = bmul(G ? t0.y : t0.x, 0x3f003f00u); w[17] = bmul(G ? t0.w : t0.z, 0x3f003f00u);
      w[18] = bmul(G ? t1.y : t1.x, 0x3f003f00u); w[19] = bmul(G ? t1.w : t1.z, 0x3f003f00u);
      bar_sync(15, 224);
#pragma unroll
      for (int i = 0; i < 4; i++) dst[G * 32 + 8 * i] = make_uint4(w[i], w[4 + i], w[8 + i], w[12 + i]);
      dst[64 + G * 8] = make_uint4(w[16], w[17], w[18], w[19]);
      bar_arrive(2, 448);
      if (warp == 12) bar_arrive(3, 64);
    } else if (warp == 15) bar_sync(3, 64);
    const int wg = warp >> 2, role = (warp + 2 * wg) & 3;
    uint32_t co[6], cpa = (g - 2 * q) * 4;
    if (role < 2) {
#pragma unroll
      for (int gm = 0; gm < 3; gm++) {
        const int hb = 2 * (lane & 7) + role - 2 + gm, l3 = ((lane >> 3) ^ (hb >> 1)) & 7;
        co[2 * gm] = hb * 1280 + uoff(l3); co[2 * gm + 1] = hb * 1280 + uoff(l3 ^ 4);
      }
    } else {
      const int mi = lane >> 3, hf = (lane >> 2) & 1;
      co[0] = hf * 1792 + (mi ^ hf) * 64 + ((q ^ (mi >> 1) ^ (hf * 2)) << 4);
      co[1] = co[0] ^ 96;
      co[2] = (lane ^ (role == 2 ? (mi & 1) : ((lane >> 1) & 4))) << 4;
      co[3] = lane * 16;
      co[4] = (g >> 1) == q ? ((g & 1) ? 0xffff0000u : 0xffffu) : 0u;
      co[5] = 2 * cpa;
    }
    const uint32_t zero = lds32(sb + OFF_ZERO), nz = zero | 0x80000000u;
#pragma unroll
    for (int i = 0; i < 6; i++) co[i] = pin(co[i], zero);
    cpa = pin(cpa, zero);
    const Comb cmb = comb_setup(tid, zero);
    mbar_wait(bar + 8 * B_UFULL, 0);
#pragma unroll 1
    for (int ch = (cw >> 2) * 4; ch >= (cw >> 2); ch--) {
      if (ch < 4) mbar_wait(bar + 8 * (B_REL1 + (ch ? 8 : 7)), 0);
      const int qt = (cw + ch) & 3, j = qt * 32 + lane;
      const uint32_t ub = sb + OFF_U + ch * 32, zb = sb + OFF_Z + ch * ZSZ;
      uint32_t w_[20], o_[20], d_[20], b3_[20];
      uint32_t *w = w_ + 8, *o = o_ + 8, *d = d_ + 8, *b3 = b3_ + 8;
      {
        const uint32_t am = ub + uoff(upos(2 * j - 2)), a0 = ub + uoff(upos(2 * j));
        const uint2 a = lds64(am + 8);
        const uint4 b = lds128(am ^ 16), c = lds128(a0), e = lds128(a0 ^ 16);
        w[8] = lds32(ub + uoff(upos((2 * j + 2) & 255)));
        w[-6] = a.x; w[-5] = a.y; w[-4] = b.x; w[-3] = b.y; w[-2] = b.z; w[-1] = b.w;
        w[0] = c.x; w[1] = c.y; w[2] = c.z; w[3] = c.w; w[4] = e.x; w[5] = e.y; w[6] = e.z; w[7] = e.w;
      }
#pragma unroll
      for (int i = -1; i <= 7; i++) o[i] = odd_pair(w[i], w[i + 1]);
#pragma unroll
      for (int i = 0; i <= 7; i++) { d[i] = hadd(w[i], o[i]); b3[i] = hadd(d[i], o[i - 1]); }
      if (j < 112) {
        const int gr = j >> 1;
        const uint32_t a1 = zb + ZA1 + 512 + (gr ^ ((gr >> 2) & 1)) * 64 + ((gr >> 1) & 3) * 16 + (j & 1) * 8;
#pragma unroll
        for (int pp = 0; pp < 4; pp++) {
          const uint32_t sel = (pp & 1) ? 0x7632 : 0x5410;
          const int k = pp >> 1;
          sts64(a1 ^ (pp * 16), __byte_perm(w[k - 1], w[k + 1], sel), __byte_perm(w[k + 3], w[k + 5], sel));
          sts64((a1 ^ (pp * 16)) + (ZB1 - ZA1), __byte_perm(b3[k], b3[k + 2], sel), __byte_perm(b3[k + 4], b3[k + 6], sel));
        }
      } else {
        const uint32_t a1 = zb + ZA1 + ((lane ^ 7) & 15) * 16;
        sts128(a1, 0, 0, 0, 0); sts128(a1 + 256, 0, 0, 0, 0); sts128(a1 + ZB1 - ZA1, 0, 0, 0, 0);
        sts128(a1 + ZB1 - ZA1 + 256, 0, 0, 0, j == 127 ? w[8] << 16 : 0u);
      }
      if (qt < 3) {
        uint32_t e_[20], b5_[20];
        uint32_t *e = e_ + 8, *b5 = b5_ + 8;
#pragma unroll
        for (int i = -6; i <= -2; i++) o[i] = odd_pair(w[i], w[i + 1]);
#pragma unroll
        for (int i = -6; i <= -1; i++) d[i] = hadd(w[i], o[i]);
#pragma unroll
        for (int i = -5; i <= -1; i++) b3[i] = hadd(d[i], o[i - 1]);
#pragma unroll
        for (int i = -5; i <= 4; i++) e[i] = hadd(d[i - 1], d[i]);
#pragma unroll
        for (int i = -4; i <= 4; i++) b5[i] = hadd(e[i], w[i + 1]);
        const uint32_t a2 = zb + ((j >> 3) * 16 + (j & 7)) * 16;
        sts128(a2 + ZA2, b3[-2], b3[-1], b3[0], b3[1]);
        sts128(a2 + ZA2 + 128, b3[2], b3[3], b3[4], b3[5]);
        sts128(a2 + ZB2, b5[-4], b5[-3], b5[-2], b5[-1]);
        sts128(a2 + ZB2 + 128, b5[0], b5[1], b5[2], b5[3]);
        if (qt < 2) {
          sts128(a2 + ZS, d[-2], d[-1], d[0], d[1]);
          sts128(a2 + ZS + 128, d[2], d[3], d[4], d[5]);
          uint32_t b7[8], b9[8];
#pragma unroll
          for (int i = -4; i <= 3; i++) { b7[i + 4] = hadd(b3[i - 1], e[i + 1]); b9[i + 4] = hadd(e[i - 1], b5[i + 1]); }
          const uint32_t a3 = zb + ((j >> 4) * 32 + (j & 15)) * 16;
          sts128(a3 + ZA3, b7[0], b7[1], b7[2], b7[3]);
          sts128(a3 + ZA3 + 256, b7[4], b7[5], b7[6], b7[7]);
          sts128(a3 + ZB3 + 256, b9[0], b9[1], b9[2], b9[3]);
          if (j < 63) sts128(a3 + ZB3 + ((j & 15) == 15 ? 272 : 16), b9[4], b9[5], b9[6], b9[7]);
          else sts128(zb + ZB3, 0, 0, 0, 0);
        }
      }
    }
    if (wg == 3) bar_arrive(0, 256);
    bar_sync(wg == 2 ? 14 : 7, 384);
#pragma unroll 1
    for (int ch = wg - 2; ch < 5; ch += 2) {
      const uint32_t ub = sb + OFF_U + ch * 32, zb = sb + OFF_Z + ch * ZSZ, pb = sb + OFF_P + ch * 3072;
      if (ch == 2) bar_sync(0, 256);
      const uint32_t pa = pb + cpa;
      if (role < 2) {
        float acc[8][4];
#pragma unroll
        for (int r = 0; r < 8; r++) { acc[r][0] = acc[r][1] = acc[r][2] = acc[r][3] = 0.f; }
        float fix = 0.f;
        if (role == 1 && lane == 28) {
          const uint32_t k = lds32(pb + PB1 * 4), u0 = lds32(ub);
          fix = __low2float(*reinterpret_cast<const __half2*>(&k)) * __low2float(*reinterpret_cast<const __half2*>(&u0));
        }
        uint32_t b[12][4], A[17][4];
#pragma unroll
        for (int i = 11; i >= 8; i--) ldsm4(b[i], ub + (co[4 + (i & 1)] ^ (((i >> 1) & 1) * 16)) + ((i >> 1) & 1) * 640);
        A[0][0] = lds32(pa + P0 * 4); A[0][1] = lds32(pa + P0 * 4 + 32); A[0][2] = lds32(sb + OFF_ZERO + 4);
#pragma unroll
        for (int m = 0; m <= 16; m++) {
          if (m < 16) {
            A[m + 1][0] = lds32(pa + P0 * 4 + (2 * m + 2) * 32);
            A[m + 1][1] = m < 15 ? lds32(pa + P0 * 4 + (2 * m + 3) * 32) : lds32(sb + OFF_ZERO + 8);
          }
          if ((m & 1) == 0 && m < 16) {
            const int i = 7 - (m >> 1);
            ldsm4(b[i], ub + (co[2 * (i >> 2) + (i & 1)] ^ (((i >> 1) & 1) * 16)) + ((i >> 1) & 1) * 640);
          }
          if (m == 9 && elect1()) mbar_arrive(bar + 8 * (B_PAIR + ch));
          A[m][3] = dup(A[m][0], nz);
          if (m < 16) A[m + 1][2] = dup(A[m][1], nz);
#pragma unroll
          for (int r = 7; r >= 0; r--) {
            const int f = 16 + r - m;
            hmma(acc[r], A[m][0], A[m][1], A[m][2], A[m][3], b[f >> 1][(f & 1) * 2], b[f >> 1][(f & 1) * 2 + 1]);
          }
        }
        acc[7][2] += fix;
        mbar_wait(bar + 8 * (B_PAIR + ch), 0);
#pragma unroll
        for (int i = 3; i >= 0; i--)
          stsm4t(ub + (co[4 + (i & 1)] ^ (((i >> 1) & 1) * 16)) + ((i >> 1) & 1) * 640, pack_bf(acc[2 * i][0], acc[2 * i][1]), pack_bf(acc[2 * i][2], acc[2 * i][3]),
                 pack_bf(acc[2 * i + 1][0], acc[2 * i + 1][1]), pack_bf(acc[2 * i + 1][2], acc[2 * i + 1][3]));
      } else if (role == 2) {
        float acc[14][4];
#pragma unroll
        for (int r = 0; r < 14; r++) { acc[r][0] = acc[r][1] = acc[r][2] = acc[r][3] = 0.f; }
#pragma unroll
        for (int arr = 0; arr < 2; arr++) {
          uint32_t A[5][4];
#pragma unroll
          for (int m = 0; m < 5; m++) {
            A[m][0] = lds32(pa + (arr ? PB1 : PA1) * 4 + m * 64);
            A[m][1] = m < 4 ? lds32(pa + (arr ? PB1 : PA1) * 4 + m * 64 + 32) : lds32(sb + OFF_ZERO + 4 + arr * 8);
          }
#pragma unroll
          for (int m = 4; m >= 1; m--) { A[m][2] = dup(A[m - 1][1], nz); A[m][3] = dup(A[m][0], nz); }
          A[0][2] = lds32(sb + OFF_ZERO + 8 + arr * 8); A[0][3] = dup(A[0][0], nz);
#pragma unroll
          for (int ip = 0; ip < 9; ip++) {
            uint32_t b[4];
            ldsm4(b, zb + co[ip & 1] + (arr ? ZB1 : ZA1) + ip * 256);
#pragma unroll
            for (int hh = 0; hh < 2; hh++)
#pragma unroll
              for (int m = 0; m < 5; m++) {
                const int i = 2 * ip + hh - 4 + m;
                if (i >= 0 && i < 14) hmma(acc[i], A[m][0], A[m][1], A[m][2], A[m][3], b[2 * hh], b[2 * hh + 1]);
              }
          }
        }
        const uint32_t a = zb + ZA1 + 512 + co[2];
#pragma unroll
        for (int i = 0; i < 7; i++)
          stsm4(a + i * 512, pack_bf(acc[2 * i][0], acc[2 * i][1]), pack_bf(acc[2 * i][2], acc[2 * i][3]),
                pack_bf(acc[2 * i + 1][0], acc[2 * i + 1][1]), pack_bf(acc[2 * i + 1][2], acc[2 * i + 1][3]));
      } else {
        float acc[12][4];
        const uint32_t za = zb + co[3];
        {
          float d[4][2][4];
#pragma unroll
          for (int r = 0; r < 8; r++) { d[r >> 1][r & 1][0] = d[r >> 1][r & 1][1] = d[r >> 1][r & 1][2] = d[r >> 1][r & 1][3] = 0.f; }
#pragma unroll
          for (int arr = 0; arr < 2; arr++) {
            uint32_t A[4][4];
#pragma unroll
            for (int m = 0; m < 4; m++) { A[m][0] = lds32(pa + (arr ? PB3 : PA3) * 4 + m * 64); A[m][1] = lds32(pa + (arr ? PB3 : PA3) * 4 + m * 64 + 32); }
#pragma unroll
            for (int m = 0; m < 4; m++) { A[m][2] = m ? dup(A[m - 1][1], nz) : lds32(sb + OFF_ZERO + 4 + arr * 4); A[m][3] = dup(A[m][0], nz); }
#pragma unroll
            for (int io = 0; io < 4; io++) {
              uint32_t b[4];
              ldsm4t(b, za + (arr ? ZB3 : ZA3) + io * 512);
#pragma unroll
              for (int m = 0; m + io < 4; m++) {
                hmma(d[io + m][0], A[m][0], A[m][1], A[m][2], A[m][3], b[0], b[1]);
                hmma(d[io + m][1], A[m][0], A[m][1], A[m][2], A[m][3], b[2], b[3]);
              }
            }
          }
#pragma unroll
          for (int r = 0; r < 4; r++) {
            acc[r][0] = acc[r][1] = acc[r][2] = acc[r][3] = 0.f;
            acc[4 + 2 * r][0] = d[r][0][0]; acc[4 + 2 * r][1] = d[r][0][1]; acc[4 + 2 * r][2] = d[r][1][0]; acc[4 + 2 * r][3] = d[r][1][1];
            acc[5 + 2 * r][0] = d[r][0][2]; acc[5 + 2 * r][1] = d[r][0][3]; acc[5 + 2 * r][2] = d[r][1][2]; acc[5 + 2 * r][3] = d[r][1][3];
          }
        }
        {
          const uint32_t k0 = lds32(sb + OFF_CHC + ch * 8 + 4) & co[4];
          const uint32_t k1 = lds32(sb + OFF_ZERO + 12), k2 = lds32(sb + OFF_ZERO + 16), k3 = dup(k0, nz);
#pragma unroll
          for (int ip = 0; ip < 4; ip++) {
            uint32_t b[4];
            ldsm4t(b, za + ZS + ip * 512);
            hmma(acc[4 + 2 * ip], k0, k1, k2, k3, b[0], b[1]);
            hmma(acc[5 + 2 * ip], k0, k1, k2, k3, b[2], b[3]);
          }
        }
        const uint32_t pa2 = pb + co[5];
#pragma unroll
        for (int arr = 0; arr < 2; arr++) {
          uint32_t A[5][4];
#pragma unroll
          for (int m = 0; m < 5; m++) {
            const uint2 v = lds64(pa2 + (arr ? PB2 : PA2) * 4 + m * 64);
            A[m][0] = v.x; A[m][1] = v.y; A[m][2] = lds32(pa2 + (arr ? PB2 : PA2) * 4 + m * 64 - 4);
          }
#pragma unroll
          for (int m = 0; m < 5; m++) A[m][3] = dup(A[m][0], nz);
#pragma unroll
          for (int ip = 0; ip < 6; ip++) {
            uint32_t b[4];
            ldsm4t(b, za + (arr ? ZB2 : ZA2) + ip * 512);
#pragma unroll
            for (int hh = 0; hh < 2; hh++)
#pragma unroll
              for (int m = 0; m < 5; m++) {
                const int i = 2 * ip + hh + m;
                if (i < 12) hmma(acc[i], A[m][0], A[m][1], A[m][2], A[m][3], b[2 * hh], b[2 * hh + 1]);
              }
          }
        }
        const uint32_t a = zb + ZA2 + co[2];
#pragma unroll
        for (int i = 0; i < 6; i++)
          stsm4(a + i * 512, pack_bf(acc[2 * i][0], acc[2 * i][1]), pack_bf(acc[2 * i][2], acc[2 * i][3]),
                pack_bf(acc[2 * i + 1][0], acc[2 * i + 1][1]), pack_bf(acc[2 * i + 1][2], acc[2 * i + 1][3]));
      }
      __syncwarp();
      if (elect1()) mbar_arrive(bar + 8 * (B_PART + ch));
    }
    bar_arrive(8, 512);
    combine(cmb, 6 - wg, wid, p.scr->sT);
    if (warp == 12) {
      if (elect1()) {
        const uint4* srcA = p.scr->h + (rg1 * 24 + NS2 - 2) * 1024;
        const uint4* srcB = p.scr->w2p + (j1 * 24 + NS2 - 2) * 640;
        uint32_t d = sb + (NS2 - 2) * SLOT2;
        mbar_wait(bar + 8 * (B_FULL2 + 4), 0);
        asm volatile("fence.proxy.async.global;" ::: "memory");
#pragma unroll 1
        for (int s = NS2 - 2; s < 24; s++) {
          mbar_wait(bar + 8 * (s < NS2 ? B_FREE + s - 2 : B_REL2 + s - NS2 + 1), 0);
          const uint32_t mb = bar + 8 * (B_FULL2 + s);
          mbar_expect(mb, SLOT2);
          bulk_g2s(d, srcA, 16384, mb);
          bulk_g2s(d + 16384, srcB, 10240, mb);
          srcA += 1024; srcB += 640;
          d = d == sb + (NS2 - 1) * SLOT2 ? sb : d + SLOT2;
        }
      }
      __syncwarp();
    } else if (warp == 13) {
      if (elect1()) {
#pragma unroll 1
        for (int c = 2; c < 5; c++) mbar_wait(bar + 8 * (B_FREE + c), 0);
        publish(cnt + (C_S + (wid >> 4)) * 32);
        mbar_expect(bar + 8 * B_SFULL, 20480);
        poll_cnt(cnt + (C_S + j1) * 32, ep * 16);
        mbar_wait(bar + 8 * (B_REL2 + 24 - NS2), 0);
        bulk_g2s(sb + OFF_U, p.scr->sT + (j1 * 16 + rg1) * 1280, 20480, bar + 8 * B_SFULL);
      }
      __syncwarp();
    }
  }
}

typedef CUresult (*EncodeFn)(CUtensorMap*, CUtensorMapDataType, cuuint32_t, void*, const cuuint64_t*, const cuuint64_t*,
                             const cuuint32_t*, const cuuint32_t*, CUtensorMapInterleave, CUtensorMapSwizzle,
                             CUtensorMapL2promotion, CUtensorMapFloatOOBfill);

}

extern "C" void kernel_launch(void* const* d_in, const int* in_sizes, int n_in, void* d_out, int out_size) {
  static EncodeFn enc = nullptr;
  static int nsm = 0;
  static void* scr = nullptr;
  if (!enc) {
    void* fn = nullptr;
    cudaDriverEntryPointQueryResult qr;
    cudaGetDriverEntryPoint("cuTensorMapEncodeTiled", &fn, cudaEnableDefault, &qr);
    enc = (EncodeFn)fn;
    int dev = 0;
    cudaGetDevice(&dev);
    cudaDeviceGetAttribute(&nsm, cudaDevAttrMultiProcessorCount, dev);
    cudaFuncSetAttribute(fused_s4_ffn_kernel<true>, cudaFuncAttributeMaxDynamicSharedMemorySize, SMEM_BYTES);
    cudaFuncSetAttribute(fused_s4_ffn_kernel<false>, cudaFuncAttributeMaxDynamicSharedMemorySize, SMEM_BYTES);
    cudaGetSymbolAddress(&scr, g_scr);
  }
  Params p;
  p.x = (const __nv_bfloat16*)d_in[0];
  p.are = (const __nv_bfloat16*)d_in[1]; p.aim = (const __nv_bfloat16*)d_in[2];
  p.bre = (const __nv_bfloat16*)d_in[3]; p.bim = (const __nv_bfloat16*)d_in[4];
  p.cre = (const __nv_bfloat16*)d_in[5]; p.cim = (const __nv_bfloat16*)d_in[6];
  p.logdt = (const __nv_bfloat16*)d_in[7]; p.dskip = (const __nv_bfloat16*)d_in[8];
  p.w1 = (const __nv_bfloat16*)d_in[10]; p.w2 = (const __nv_bfloat16*)d_in[11];
  p.out = (__nv_bfloat16*)d_out;
  p.scr = (Scratch*)scr;
  CUtensorMap tmX, tmW1, tmU, tmW2;
  const cuuint32_t es[5] = {1, 1, 1, 1, 1};
  {
    const cuuint64_t gd[5] = {DM, 2, 4, 4, FF / 32}, gs[4] = {DM * 2, DM * 16, DM * 4, DM * 64};
    const cuuint32_t bx[5] = {88, 2, 4, 4, 3};
    enc(&tmW2, CU_TENSOR_MAP_DATA_TYPE_BFLOAT16, 5, d_in[11], gd, gs, bx, es, CU_TENSOR_MAP_INTERLEAVE_NONE,
        CU_TENSOR_MAP_SWIZZLE_NONE, CU_TENSOR_MAP_L2_PROMOTION_NONE, CU_TENSOR_MAP_FLOAT_OOB_FILL_NONE);
  }
  {
    const cuuint64_t gd[2] = {16 * DM, 128}, gs[1] = {DM * 32};
    const cuuint32_t bx[2] = {80, 144};
    enc(&tmU, CU_TENSOR_MAP_DATA_TYPE_FLOAT16, 2, p.scr->uT, gd, gs, bx, es, CU_TENSOR_MAP_INTERLEAVE_NONE,
        CU_TENSOR_MAP_SWIZZLE_NONE, CU_TENSOR_MAP_L2_PROMOTION_NONE, CU_TENSOR_MAP_FLOAT_OOB_FILL_NONE);
  }
  {
    const cuuint64_t gd[2] = {DM, SEQ}, gs[1] = {DM * 2};
    const cuuint32_t bx[2] = {64, 128};
    enc(&tmX, CU_TENSOR_MAP_DATA_TYPE_BFLOAT16, 2, d_in[0], gd, gs, bx, es, CU_TENSOR_MAP_INTERLEAVE_NONE,
        CU_TENSOR_MAP_SWIZZLE_128B, CU_TENSOR_MAP_L2_PROMOTION_L2_128B, CU_TENSOR_MAP_FLOAT_OOB_FILL_NONE);
  }
  {
    const cuuint64_t gd[3] = {64, DM, FF / 64}, gs[2] = {FF * 2, 128};
    const cuuint32_t bx[3] = {64, 64, 3};
    enc(&tmW1, CU_TENSOR_MAP_DATA_TYPE_BFLOAT16, 3, d_in[10], gd, gs, bx, es, CU_TENSOR_MAP_INTERLEAVE_NONE,
        CU_TENSOR_MAP_SWIZZLE_128B, CU_TENSOR_MAP_L2_PROMOTION_L2_128B, CU_TENSOR_MAP_FLOAT_OOB_FILL_NONE);
  }
  if (nsm == 132) fused_s4_ffn_kernel<true><<<132, 512, SMEM_BYTES>>>(p, tmX, tmW1, tmU, tmW2);
  else fused_s4_ffn_kernel<false><<<132, 512, SMEM_BYTES>>>(p, tmX, tmW1, tmU, tmW2);
}
```

```cpp
#include <cuda_runtime.h>
#include <cuda_bf16.h>
#include <cuda_fp16.h>
#include <cuda.h>
#include <stdint.h>

namespace {

constexpr int SEQ = 2048, DM = 640, FF = 1536;

constexpr int SLOT1 = 40960;
constexpr int SLOT2 = 26624;
constexpr int NS2 = 7;
#define GATE 0
#define SPARE_NS 300
#define DELAY_NS 200
#define PACE_NS 60
constexpr int OFF_Z = 85504, ZSZ = 20480;
constexpr int ZA3 = 0, ZB3 = 2048, ZS = 4096, ZA2 = 6144, ZB2 = 9216, ZA1 = 12288, ZB1 = 16384;
constexpr int OFF_U = 190464;
constexpr int OFF_P = 210944;
constexpr int OFF_LNP = OFF_U;
constexpr int OFF_W2S = OFF_U + 1152;
constexpr int KBUF = 13312;
constexpr int OFF_MISC = 226304;
constexpr int OFF_CHC = OFF_MISC + 16;
constexpr int OFF_EP = OFF_MISC + 64;
constexpr int OFF_K0 = OFF_MISC + 256;
constexpr int OFF_ZERO = OFF_MISC + 128;
constexpr int OFF_STAT = OFF_MISC + 1024;
constexpr int OFF_CS = OFF_MISC + 2048;
constexpr int OFF_BAR = OFF_MISC + 2816;
constexpr int SMEM_BYTES = OFF_MISC + 6144;
constexpr int P0 = 8, PA1 = 280, PB1 = 360, PA2 = 448, PB2 = 544, PA3 = 632, PB3 = 704;
enum { B_FULL1 = 0, B_FULL2 = 10, B_UFULL = 34, B_EPI = 35, B_SFULL = 36, B_W2 = 37,
       B_PAIR = 42,
       B_FREE = 48, B_PART = 54,
       B_REL1 = 60, B_REL2 = 70 };
enum { C_LN = 0, C_CS = 1, C_H0 = 2, C_H1 = 18, C_S = 34, C_W2 = 42, C_NUM = 43 };

struct Scratch {
  unsigned cnt[64 * 32];
  unsigned epoch[256];
  float2 stats[SEQ];
  float cs[FF];
  uint4 uT[DM * 256];
  uint4 w2p[8 * 24 * 640];
  uint4 sT[8 * 16 * 1280];
  uint4 h[16 * 24 * 1024];
};
__device__ __align__(1024) Scratch g_scr;
constexpr uint32_t sb = 1024;
constexpr uint32_t bar = sb + OFF_BAR;

struct Params {
  const __nv_bfloat16 *are, *aim, *bre, *bim, *cre, *cim, *logdt, *dskip, *x, *w1, *w2;
  __nv_bfloat16* out;
  Scratch* scr;
};

__device__ __forceinline__ void mbar_init(uint32_t a, int c) { asm volatile("mbarrier.init.shared::cta.b64 [%0], %1;" ::"r"(a), "r"(c)); }
__device__ __forceinline__ void mbar_expect(uint32_t a, int b) { asm volatile("mbarrier.arrive.expect_tx.shared::cta.b64 _, [%0], %1;" ::"r"(a), "r"(b) : "memory"); }
__device__ __forceinline__ void mbar_arrive(uint32_t a) { asm volatile("mbarrier.arrive.shared::cta.b64 _, [%0];" ::"r"(a) : "memory"); }
__device__ __forceinline__ void mbar_wait(uint32_t a, int ph) {
  asm volatile(
      "{\n.reg .pred p;\n.reg .u32 n;\n"
      "mbarrier.try_wait.parity.shared::cta.b64 p, [%0], %1;\n@p bra LD;\nmov.u32 n, 0;\n"
      "LW:\nmbarrier.try_wait.parity.shared::cta.b64 p, [%0], %1, 20000;\n@p bra LD;\n"
      "add.u32 n, n, 1;\nsetp.lt.u32 p, n, 100000;\n@p bra LW;\ntrap;\nLD:\n}\n" ::"r"(a), "r"(ph) : "memory");
}
__device__ __forceinline__ void poll_cnt(const unsigned* p, unsigned target) {
  asm volatile(
      "{\n.reg .pred p;\n.reg .u32 n;\n.reg .s32 v;\nmov.u32 n, 0;\n"
      "LW:\nld.relaxed.gpu.global.u32 v, [%0];\nsub.s32 v, v, %1;\nsetp.ge.s32 p, v, 0;\n@p bra LD;\n"
      "nanosleep.u32 64;\nadd.u32 n, n, 1;\nsetp.lt.u32 p, n, 4000000;\n@p bra LW;\ntrap;\n"
      "LD:\nfence.acquire.gpu;\nfence.proxy.async.global;\n}\n" ::"l"(p), "r"(target) : "memory");
}
__device__ __forceinline__ void publish(unsigned* p) {
  asm volatile("fence.proxy.async.global;\nfence.release.gpu;\nred.relaxed.gpu.global.add.u32 [%0], 1;" ::"l"(p) : "memory");
}
__device__ __forceinline__ uint32_t movm(uint32_t v) { uint32_t r; asm volatile("movmatrix.sync.aligned.m8n8.trans.b16 %0, %1;" : "=r"(r) : "r"(v)); return r; }
__device__ __forceinline__ void fence_async_smem() { asm volatile("fence.proxy.async.shared::cta;" ::: "memory"); }
__device__ __forceinline__ bool elect1() { uint32_t p; asm volatile("{\n.reg .pred P;\nelect.sync _|P, 0xffffffff;\nselp.u32 %0,1,0,P;\n}\n" : "=r"(p)); return p; }
__device__ __forceinline__ void bar_sync(int id, int n) { asm volatile("bar.sync %0, %1;" ::"r"(id), "r"(n) : "memory"); }
__device__ __forceinline__ void bar_arrive(int id, int n) { asm volatile("bar.arrive %0, %1;" ::"r"(id), "r"(n) : "memory"); }
__device__ __forceinline__ void bulk_g2s(uint32_t dst, const void* src, int bytes, uint32_t mb) {
  asm volatile("cp.async.bulk.shared::cluster.global.mbarrier::complete_tx::bytes [%0], [%1], %2, [%3];" ::"r"(dst), "l"(src), "r"(bytes), "r"(mb) : "memory");
}
__device__ __forceinline__ void bulk_prefetch(const void* src, int bytes) { asm volatile("cp.async.bulk.prefetch.L2.global [%0], %1;" ::"l"(src), "r"(bytes) : "memory"); }
__device__ __forceinline__ void tma2d(uint32_t dst, const CUtensorMap* m, int c0, int c1, uint32_t mb) {
  asm volatile("cp.async.bulk.tensor.2d.shared::cluster.global.mbarrier::complete_tx::bytes [%0], [%1, {%3, %4}], [%2];" ::"r"(dst), "l"(m), "r"(mb), "r"(c0), "r"(c1) : "memory");
}
__device__ __forceinline__ void tma3d(uint32_t dst, const CUtensorMap* m, int c0, int c1, int c2, uint32_t mb) {
  asm volatile("cp.async.bulk.tensor.3d.shared::cluster.global.mbarrier::complete_tx::bytes [%0], [%1, {%3, %4, %5}], [%2];" ::"r"(dst), "l"(m), "r"(mb), "r"(c0), "r"(c1), "r"(c2) : "memory");
}
__device__ __forceinline__ unsigned frag_col(unsigned l) { return (l & 0x61) | ((l & 6) << (2 - (l >> 6))) | ((l >> 2) & 6); }
__device__ __forceinline__ void tma5d(uint32_t dst, const CUtensorMap* m, int c0, int c4, uint32_t mb) {
  asm volatile("cp.async.bulk.tensor.5d.shared::cluster.global.mbarrier::complete_tx::bytes [%0], [%1, {%3, %5, %5, %5, %4}], [%2];" ::"r"(dst), "l"(m), "r"(mb), "r"(c0), "r"(c4), "r"(0) : "memory");
}
__device__ __forceinline__ uint64_t dsc(uint32_t lo, uint32_t hi) { return ((uint64_t)hi << 32) | lo; }
__device__ __forceinline__ void wg_fence() { asm volatile("wgmma.fence.sync.aligned;" ::: "memory"); }
__device__ __forceinline__ void wg_commit() { asm volatile("wgmma.commit_group.sync.aligned;" ::: "memory"); }
template <int N> __device__ __forceinline__ void wg_wait() { asm volatile("wgmma.wait_group.sync.aligned %0;" ::"n"(N) : "memory"); }
__device__ __forceinline__ void wgmma_n192(float (&d)[96], uint64_t da, uint64_t db, int scale_d) {
  asm volatile("{\n.reg .pred p;\nsetp.ne.b32 p, %98, 0;\n"
    "wgmma.mma_async.sync.aligned.m64n192k16.f32.bf16.bf16 "
    "{"
    "%0, %1, %2, %3, %4, %5, %6, %7, %8, %9, %10, %11, %12, %13, %14, %15, "
    "%16, %17, %18, %19, %20, %21, %22, %23, %24, %25, %26, %27, %28, %29, %30, %31, "
    "%32, %33, %34, %35, %36, %37, %38, %39, %40, %41, %42, %43, %44, %45, %46, %47, "
    "%48, %49, %50, %51, %52, %53, %54, %55, %56, %57, %58, %59, %60, %61, %62, %63, "
    "%64, %65, %66, %67, %68, %69, %70, %71, %72, %73, %74, %75, %76, %77, %78, %79, "
    "%80, %81, %82, %83, %84, %85, %86, %87, %88, %89, %90, %91, %92, %93, %94, %95"
    "}, "
    "%96, %97, p, 1, 1, 0, 1;\n}\n"
    : "+f"(d[0]), "+f"(d[1]), "+f"(d[2]), "+f"(d[3]), "+f"(d[4]), "+f"(d[5]), "+f"(d[6]), "+f"(d[7]),
      "+f"(d[8]), "+f"(d[9]), "+f"(d[10]), "+f"(d[11]), "+f"(d[12]), "+f"(d[13]), "+f"(d[14]), "+f"(d[15]),
      "+f"(d[16]), "+f"(d[17]), "+f"(d[18]), "+f"(d[19]), "+f"(d[20]), "+f"(d[21]), "+f"(d[22]), "+f"(d[23]),
      "+f"(d[24]), "+f"(d[25]), "+f"(d[26]), "+f"(d[27]), "+f"(d[28]), "+f"(d[29]), "+f"(d[30]), "+f"(d[31]),
      "+f"(d[32]), "+f"(d[33]), "+f"(d[34]), "+f"(d[35]), "+f"(d[36]), "+f"(d[37]), "+f"(d[38]), "+f"(d[39]),
      "+f"(d[40]), "+f"(d[41]), "+f"(d[42]), "+f"(d[43]), "+f"(d[44]), "+f"(d[45]), "+f"(d[46]), "+f"(d[47]),
      "+f"(d[48]), "+f"(d[49]), "+f"(d[50]), "+f"(d[51]), "+f"(d[52]), "+f"(d[53]), "+f"(d[54]), "+f"(d[55]),
      "+f"(d[56]), "+f"(d[57]), "+f"(d[58]), "+f"(d[59]), "+f"(d[60]), "+f"(d[61]), "+f"(d[62]), "+f"(d[63]),
      "+f"(d[64]), "+f"(d[65]), "+f"(d[66]), "+f"(d[67]), "+f"(d[68]), "+f"(d[69]), "+f"(d[70]), "+f"(d[71]),
      "+f"(d[72]), "+f"(d[73]), "+f"(d[74]), "+f"(d[75]), "+f"(d[76]), "+f"(d[77]), "+f"(d[78]), "+f"(d[79]),
      "+f"(d[80]), "+f"(d[81]), "+f"(d[82]), "+f"(d[83]), "+f"(d[84]), "+f"(d[85]), "+f"(d[86]), "+f"(d[87]),
      "+f"(d[88]), "+f"(d[89]), "+f"(d[90]), "+f"(d[91]), "+f"(d[92]), "+f"(d[93]), "+f"(d[94]), "+f"(d[95])
    : "l"(da), "l"(db), "r"(scale_d));
}

__device__ __forceinline__ void wgmma_n80(float (&d)[40], uint64_t da, uint64_t db, int scale_d) {
  asm volatile("{\n.reg .pred p;\nsetp.ne.b32 p, %42, 0;\n"
    "wgmma.mma_async.sync.aligned.m64n80k16.f32.bf16.bf16 "
    "{"
    "%0, %1, %2, %3, %4, %5, %6, %7, %8, %9, %10, %11, %12, %13, %14, %15, "
    "%16, %17, %18, %19, %20, %21, %22, %23, %24, %25, %26, %27, %28, %29, %30, %31, "
    "%32, %33, %34, %35, %36, %37, %38, %39"
    "}, "
    "%40, %41, p, 1, 1, 0, 1;\n}\n"
    : "+f"(d[0]), "+f"(d[1]), "+f"(d[2]), "+f"(d[3]), "+f"(d[4]), "+f"(d[5]), "+f"(d[6]), "+f"(d[7]),
      "+f"(d[8]), "+f"(d[9]), "+f"(d[10]), "+f"(d[11]), "+f"(d[12]), "+f"(d[13]), "+f"(d[14]), "+f"(d[15]),
      "+f"(d[16]), "+f"(d[17]), "+f"(d[18]), "+f"(d[19]), "+f"(d[20]), "+f"(d[21]), "+f"(d[22]), "+f"(d[23]),
      "+f"(d[24]), "+f"(d[25]), "+f"(d[26]), "+f"(d[27]), "+f"(d[28]), "+f"(d[29]), "+f"(d[30]), "+f"(d[31]),
      "+f"(d[32]), "+f"(d[33]), "+f"(d[34]), "+f"(d[35]), "+f"(d[36]), "+f"(d[37]), "+f"(d[38]), "+f"(d[39])
    : "l"(da), "l"(db), "r"(scale_d));
}

__device__ __forceinline__ void wgmma_n40(float (&d)[20], uint64_t da, uint64_t db, int scale_d) {
  asm volatile("{\n.reg .pred p;\nsetp.ne.b32 p, %22, 0;\n"
    "wgmma.mma_async.sync.aligned.m64n40k16.f32.f16.f16 "
    "{"
    "%0, %1, %2, %3, %4, %5, %6, %7, %8, %9, %10, %11, %12, %13, %14, %15, "
    "%16, %17, %18, %19"
    "}, "
    "%20, %21, p, 1, 1, 1, 1;\n}\n"
    : "+f"(d[0]), "+f"(d[1]), "+f"(d[2]), "+f"(d[3]), "+f"(d[4]), "+f"(d[5]), "+f"(d[6]), "+f"(d[7]),
      "+f"(d[8]), "+f"(d[9]), "+f"(d[10]), "+f"(d[11]), "+f"(d[12]), "+f"(d[13]), "+f"(d[14]), "+f"(d[15]),
      "+f"(d[16]), "+f"(d[17]), "+f"(d[18]), "+f"(d[19])
    : "l"(da), "l"(db), "r"(scale_d));
}

__device__ __forceinline__ void hmma(float* c, uint32_t a0, uint32_t a1, uint32_t a2, uint32_t a3, uint32_t b0, uint32_t b1) {
  asm volatile("mma.sync.aligned.m16n8k16.row.col.f32.f16.f16.f32 {%0,%1,%2,%3}, {%4,%5,%6,%7}, {%8,%9}, {%0,%1,%2,%3};"
      : "+f"(c[0]), "+f"(c[1]), "+f"(c[2]), "+f"(c[3]) : "r"(a0), "r"(a1), "r"(a2), "r"(a3), "r"(b0), "r"(b1));
}
__device__ __forceinline__ void ldsm4(uint32_t* r, uint32_t a) { asm volatile("ldmatrix.sync.aligned.m8n8.x4.shared.b16 {%0,%1,%2,%3}, [%4];" : "=r"(r[0]), "=r"(r[1]), "=r"(r[2]), "=r"(r[3]) : "r"(a) : "memory"); }
__device__ __forceinline__ void ldsm4t(uint32_t* r, uint32_t a) { asm volatile("ldmatrix.sync.aligned.m8n8.x4.trans.shared.b16 {%0,%1,%2,%3}, [%4];" : "=r"(r[0]), "=r"(r[1]), "=r"(r[2]), "=r"(r[3]) : "r"(a) : "memory"); }
__device__ __forceinline__ void stsm4(uint32_t a, uint32_t r0, uint32_t r1, uint32_t r2, uint32_t r3) { asm volatile("stmatrix.sync.aligned.m8n8.x4.shared.b16 [%0], {%1,%2,%3,%4};" ::"r"(a), "r"(r0), "r"(r1), "r"(r2), "r"(r3) : "memory"); }
__device__ __forceinline__ void stsm4t(uint32_t a, uint32_t r0, uint32_t r1, uint32_t r2, uint32_t r3) { asm volatile("stmatrix.sync.aligned.m8n8.x4.trans.shared.b16 [%0], {%1,%2,%3,%4};" ::"r"(a), "r"(r0), "r"(r1), "r"(r2), "r"(r3) : "memory"); }
__device__ __forceinline__ uint32_t lds32(uint32_t a) { uint32_t v; asm volatile("ld.shared.u32 %0, [%1];" : "=r"(v) : "r"(a) : "memory"); return v; }
__device__ __forceinline__ uint2 lds64(uint32_t a) { uint2 v; asm volatile("ld.shared.v2.u32 {%0,%1}, [%2];" : "=r"(v.x), "=r"(v.y) : "r"(a) : "memory"); return v; }
__device__ __forceinline__ uint4 lds128(uint32_t a) { uint4 v; asm volatile("ld.shared.v4.u32 {%0,%1,%2,%3}, [%4];" : "=r"(v.x), "=r"(v.y), "=r"(v.z), "=r"(v.w) : "r"(a) : "memory"); return v; }
__device__ __forceinline__ void sts16(uint32_t a, uint32_t v) { asm volatile("st.shared.u16 [%0], %1;" ::"r"(a), "h"((unsigned short)v) : "memory"); }
__device__ __forceinline__ void sts32(uint32_t a, uint32_t v) { asm volatile("st.shared.u32 [%0], %1;" ::"r"(a), "r"(v) : "memory"); }
__device__ __forceinline__ void sts64(uint32_t a, uint32_t x, uint32_t y) { asm volatile("st.shared.v2.u32 [%0], {%1,%2};" ::"r"(a), "r"(x), "r"(y) : "memory"); }
__device__ __forceinline__ void sts128(uint32_t a, uint32_t x, uint32_t y, uint32_t z, uint32_t w) { asm volatile("st.shared.v4.u32 [%0], {%1,%2,%3,%4};" ::"r"(a), "r"(x), "r"(y), "r"(z), "r"(w) : "memory"); }
__device__ __forceinline__ uint32_t ldg32(const void* a) { uint32_t v; asm volatile("ld.global.nc.u32 %0, [%1];" : "=r"(v) : "l"(a)); return v; }
__device__ __forceinline__ uint32_t ldg16(const void* a) { uint32_t v; asm volatile("ld.global.nc.u16 %0, [%1];" : "=r"(v) : "l"(a)); return v; }
__device__ __forceinline__ float bflo(uint32_t v) { return __uint_as_float(v << 16); }
__device__ __forceinline__ float bfhi(uint32_t v) { return __uint_as_float(v & 0xffff0000u); }
__device__ __forceinline__ uint32_t pack_bf(float lo, float hi) { uint32_t r; asm("cvt.rn.bf16x2.f32 %0, %1, %2;" : "=r"(r) : "f"(hi), "f"(lo)); return r; }
__device__ __forceinline__ uint32_t pack_h(float lo, float hi) { uint32_t r; asm("cvt.rn.f16x2.f32 %0, %1, %2;" : "=r"(r) : "f"(hi), "f"(lo)); return r; }
__device__ __forceinline__ float rnd_bf(float v) { return __bfloat162float(__float2bfloat16_rn(v)); }
__device__ __forceinline__ float ex2a(float v) { float r; asm("ex2.approx.ftz.f32 %0, %1;" : "=f"(r) : "f"(v)); return r; }
__device__ __forceinline__ float tanha(float v) { float r; asm("tanh.approx.f32 %0, %1;" : "=f"(r) : "f"(v)); return r; }
__device__ __forceinline__ uint32_t hadd(uint32_t a, uint32_t b) { uint32_t r; asm("add.rn.f16x2 %0, %1, %2;" : "=r"(r) : "r"(a), "r"(b)); return r; }
__device__ __forceinline__ uint32_t badd(uint32_t a, uint32_t b) { uint32_t r; asm("add.rn.bf16x2 %0, %1, %2;" : "=r"(r) : "r"(a), "r"(b)); return r; }
__device__ __forceinline__ uint32_t bmul(uint32_t a, uint32_t b) { uint32_t r; asm("mul.rn.bf16x2 %0, %1, %2;" : "=r"(r) : "r"(a), "r"(b)); return r; }
__device__ __forceinline__ uint32_t bfma(uint32_t a, uint32_t b, uint32_t c) { uint32_t r; asm("fma.rn.bf16x2 %0, %1, %2, %3;" : "=r"(r) : "r"(a), "r"(b), "r"(c)); return r; }
__device__ __forceinline__ float tanhv(float v) { float r; asm volatile("tanh.approx.f32 %0, %1;" : "=f"(r) : "f"(v)); return r; }
__device__ __forceinline__ uint32_t bsub(uint32_t a, uint32_t b) { uint32_t r; asm("sub.rn.bf16x2 %0, %1, %2;" : "=r"(r) : "r"(a), "r"(b)); return r; }
__device__ __forceinline__ uint32_t dup(uint32_t v, uint32_t nz) { uint32_t r; asm volatile("add.rn.f32 %0, %1, %2;" : "=r"(r) : "r"(v), "r"(nz)); return r; }
__device__ __forceinline__ void bmma(float* c, uint32_t a0, uint32_t a1, uint32_t a2, uint32_t a3, uint32_t b0, uint32_t b1) {
  asm("mma.sync.aligned.m16n8k16.row.col.f32.bf16.bf16.f32 {%0,%1,%2,%3}, {%4,%5,%6,%7}, {%8,%9}, {%0,%1,%2,%3};"
      : "+f"(c[0]), "+f"(c[1]), "+f"(c[2]), "+f"(c[3]) : "r"(a0), "r"(a1), "r"(a2), "r"(a3), "r"(b0), "r"(b1));
}
__device__ __forceinline__ uint32_t odd_pair(uint32_t a, uint32_t b) { return __byte_perm(a, b, 0x5432); }
__device__ __forceinline__ int upos(int c) { return c ^ ((c >> 5) & 7) ^ ((c >> 3) & 1); }
__device__ __forceinline__ int uoff(int pos) { return (pos >> 1) * 160 + (pos & 1) * 16; }

template <int V> struct IC { static constexpr int value = V; };
struct cf { float r, i; };
__device__ __forceinline__ cf cmul(cf a, cf b) { cf o; o.r = fmaf(a.r, b.r, -a.i * b.i); o.i = fmaf(a.r, b.i, a.i * b.r); return o; }
__device__ __forceinline__ cf csq(cf a) { cf o; o.r = fmaf(a.r, a.r, -a.i * a.i); o.i = (a.r + a.r) * a.i; return o; }
struct hp { uint32_t r, i; };
__device__ __forceinline__ hp hpack(cf a, cf b) { hp o; o.r = pack_h(a.r, b.r); o.i = pack_h(a.i, b.i); return o; }
__device__ __forceinline__ hp hmulc(hp a, uint32_t c) {
  __half2 ar = *reinterpret_cast<__half2*>(&a.r), ai = *reinterpret_cast<__half2*>(&a.i), cc = *reinterpret_cast<__half2*>(&c);
  __half2 orr = __hfma2(ar, __low2half2(cc), __hneg2(__hmul2(ai, __high2half2(cc))));
  __half2 oi = __hfma2(ar, __high2half2(cc), __hmul2(ai, __low2half2(cc)));
  hp o; o.r = *reinterpret_cast<uint32_t*>(&orr); o.i = *reinterpret_cast<uint32_t*>(&oi); return o;
}
__device__ __forceinline__ uint32_t zmul(uint32_t x, uint32_t k, uint32_t kr) {
  const __half2 xx = *reinterpret_cast<__half2*>(&x);
  const __half2 o = __hfma2(__low2half2(xx), *reinterpret_cast<__half2*>(&k), __hmul2(__high2half2(xx), *reinterpret_cast<__half2*>(&kr)));
  return *reinterpret_cast<const uint32_t*>(&o);
}
__device__ __forceinline__ cf cexp2(float zr, float th) { const float m = ex2a(zr); return cf{m * __cosf(th), m * __sinf(th)}; }
template <int STEP> __device__ __forceinline__ void put_tap(uint32_t a, uint32_t h) { sts16(a, h); sts16(a + STEP * 4 + 2, h); }

__device__ __forceinline__ void spare_work(const Params& p, const CUtensorMap* tmW1, int k, int tid) {
  const int lane = tid & 31;
  unsigned ep = 0;
  if (tid >= 480) ep = p.scr->epoch[128 + k] + 1;
  if (tid == 480) {
    for (int i = 0; i < 8; i++) mbar_init(bar + 8 * i, i < 4 ? 1 : 12);
    asm volatile("fence.mbarrier_init.release.cluster;" ::: "memory");
    fence_async_smem();
  }
  __syncthreads();
  float a[2][4] = {{0.f, 0.f, 0.f, 0.f}, {0.f, 0.f, 0.f, 0.f}};
  if (tid >= 480) {
    if (elect1()) {
      if (SPARE_NS) __nanosleep(SPARE_NS);
#pragma unroll 1
      for (int s = 0; s < 10; s++) {
        mbar_wait(bar + 8 * (4 + (s & 3)), ((s >> 2) & 1) ^ 1);
        mbar_expect(bar + 8 * (s & 3), 49152);
#pragma unroll 1
        for (int b = 0; b < 2; b++) tma3d(sb + (s & 3) * 49152 + b * 24576, tmW1, 0, s * 64, k * 6 + b * 3, bar + 8 * (s & 3));
      }
    }
    __syncwarp();
  } else if (tid < 384) {
    const uint32_t idn = (lane >> 3) == (lane & 3) ? ((lane & 4) ? 0x3f800000u : 0x3f80u) : 0u;
#pragma unroll 1
    for (int s = 0; s < 10; s++) {
      mbar_wait(bar + 8 * (s & 3), (s >> 2) & 1);
      const uint32_t ad = sb + (s & 3) * 49152 + (tid >> 6) * 8192 + (tid & 63) * 16;
#pragma unroll
      for (int i = 0; i < 8; i += 2) {
        const uint4 v = lds128(ad + i * 1024), w = lds128(ad + i * 1024 + 1024);
        bmma(a[0], v.x, v.y, w.x, w.y, idn, idn);
        bmma(a[1], v.z, v.w, w.z, w.w, idn, idn);
      }
      __syncwarp();
      if (lane == 0) mbar_arrive(bar + 8 * (4 + (s & 3)));
    }
    const int rho = (tid >> 3) & 7;
    const uint32_t ad = sb + 196608 + rho * 1536 + ((tid >> 6) * 8 + ((tid & 7) ^ rho)) * 32;
    sts128(ad, __float_as_uint(a[0][0]), __float_as_uint(a[0][1]), __float_as_uint(a[0][2]), __float_as_uint(a[0][3]));
    sts128(ad + 16, __float_as_uint(a[1][0]), __float_as_uint(a[1][1]), __float_as_uint(a[1][2]), __float_as_uint(a[1][3]));
  }
  __syncthreads();
  if (tid < 384) {
    float s = 0.f;
#pragma unroll
    for (int r = 0; r < 8; r++) s += __uint_as_float(lds32(sb + 196608 + r * 1536 + tid * 4));
    p.scr->cs[k * 384 + tid] = s;
  }
  __syncthreads();
  if (tid == 480) {
    publish(p.scr->cnt + C_CS * 32);
    p.scr->epoch[128 + k] = ep;
    poll_cnt(p.scr->cnt + C_LN * 32, ep * 128);
  }
}

__device__ __forceinline__ void load1(int s, const CUtensorMap* tmX, const CUtensorMap* tmW1, int rg1, int j1) {
  const uint32_t d = sb + (s & 3) * SLOT1, mb = bar + 8 * (B_FULL1 + s);
  mbar_expect(mb, SLOT1);
  tma2d(d, tmX, s * 64, rg1 * 128, mb);
  tma3d(d + 16384, tmW1, 0, s * 64, j1 * 3, mb);
}
__device__ __forceinline__ void load_x(uint32_t (&xv)[2][10], const __nv_bfloat16* xc, int rstep, int q) {
#pragma unroll
  for (int r = 0; r < 2; r++) {
    const uint4 a = __ldg((const uint4*)(xc + r * rstep) + q), b = __ldg((const uint4*)(xc + r * rstep) + 4 + q);
    const uint2 c = __ldg((const uint2*)(xc + r * rstep + 64) + q);
    xv[r][0] = a.x; xv[r][1] = a.y; xv[r][2] = a.z; xv[r][3] = a.w; xv[r][4] = b.x; xv[r][5] = b.y; xv[r][6] = b.z; xv[r][7] = b.w;
    xv[r][8] = c.x; xv[r][9] = c.y;
  }
}

__device__ __forceinline__ uint32_t pin(uint32_t v, uint32_t z) { uint32_t r; asm volatile("add.u32 %0, %1, %2;" : "=r"(r) : "r"(v), "r"(z)); return r; }
struct Comb { uint32_t o[7]; };
__device__ __forceinline__ Comb comb_setup(int tid, uint32_t z) {
  Comb k;
  const int c = tid & 127, c1 = c < 112 ? c + 32 : c - 112, c2 = c < 112 ? c + 144 : c - 96;
  const uint32_t zr = ZA1 + (c & 7) * 16, a2 = ZA2 + ((c & ~15) - 32 + ((((c >> 1) & 7) + (c & 1) * 8) ^ ((c & 1) * 4))) * 16;
  k.o[0] = uoff(upos(c1)); k.o[1] = uoff(upos(c2));
  k.o[2] = c < 112 ? ZA1 + 512 + ((2 * c) ^ ((c >> 2) & 1)) * 16 : zr;
  k.o[3] = c1 >= 64 ? a2 : zr; k.o[4] = c < 112 ? a2 + 112 * 16 : zr;
  k.o[5] = ((c1 >> 4) * 1280 + (c & 15)) * 16; k.o[6] = ((c2 >> 4) * 1280 + (c & 15)) * 16;
#pragma unroll
  for (int i = 0; i < 7; i++) k.o[i] = pin(k.o[i], z);
  return k;
}
template <class F> __device__ __forceinline__ void combine(const Comb& k, int ch, int wid, uint4* sT, F&& after_reads) {
  const uint32_t ub = sb + OFF_U + ch * 32, zb = sb + OFF_Z + ch * ZSZ;
  const int row = (wid & 15) * 5 + ch;
  char* dst = (char*)(sT + ((wid >> 4) * 16 * 80 + row) * 16);
  mbar_wait(bar + 8 * (B_PART + ch), 0);
  const uint32_t sc = lds32(sb + OFF_CHC + ch * 8);
  const uint4 y0 = lds128(zb + k.o[2]), y1 = lds128(zb + (k.o[2] ^ 16));
  const uint4 v2 = lds128(zb + k.o[3]), u2 = lds128(zb + k.o[4]);
  const uint4 v0 = lds128(ub + k.o[0]), u0 = lds128(ub + k.o[1]);
  fence_async_smem();
  after_reads();
  *(uint4*)(dst + (k.o[5] ^ ((row & 7) * 16))) =
      make_uint4(bmul(badd(badd(y0.x, v2.x), v0.x), sc), bmul(badd(badd(y0.y, v2.y), v0.y), sc),
                 bmul(badd(badd(y1.x, v2.z), v0.z), sc), bmul(badd(badd(y1.y, v2.w), v0.w), sc));
  *(uint4*)(dst + (k.o[6] ^ ((row & 7) * 16))) =
      make_uint4(bmul(badd(badd(y0.z, u2.x), u0.x), sc), bmul(badd(badd(y0.w, u2.y), u0.y), sc),
                 bmul(badd(badd(y1.z, u2.z), u0.z), sc), bmul(badd(badd(y1.w, u2.w), u0.w), sc));
  __syncwarp();
  if (elect1()) mbar_arrive(bar + 8 * (B_FREE + ch));
}

__device__ __forceinline__ void load2(int s, uint32_t d, const uint4* srcA, const uint4* srcB) {
  const uint32_t mb = bar + 8 * (B_FULL2 + s);
  mbar_expect(mb, SLOT2);
  bulk_g2s(d, srcA, 16384, mb);
  bulk_g2s(d + 16384, srcB, 10240, mb);
}

template <bool USE_SMID>
__global__ void __launch_bounds__(512, 1)
fused_s4_ffn_kernel(const Params p, const __grid_constant__ CUtensorMap tmX, const __grid_constant__ CUtensorMap tmW1,
                    const __grid_constant__ CUtensorMap tmU, const __grid_constant__ CUtensorMap tmW2) {
  extern __shared__ __align__(1024) unsigned char smem_raw[];
  const int tid = threadIdx.x, lane = tid & 31;
  uint32_t sid;
  if (USE_SMID) asm("mov.u32 %0, %smid;" : "=r"(sid)); else sid = blockIdx.x;
  const int wid = sid < 120 ? sid : sid - 4;
  const int warp = __shfl_sync(0xffffffffu, tid >> 5, 0);
  const bool hi = ((warp >> 1) ^ (warp >> 2)) & 1;
  uint32_t pa[6][2], pld, pds;
  auto load_params = [&](int lc) {
    const unsigned ch = (wid >> 4) * 80 + frag_col((wid & 15) * 5 + lc);
    const unsigned o = ch * 96 + (tid & 63);
    pld = ldg16(p.logdt + ch);
#pragma unroll
    for (int i = 0; i < 2; i++) { pa[0][i] = ldg32((const uint32_t*)p.are + o + 32 * i); pa[1][i] = ldg32((const uint32_t*)p.aim + o + 32 * i); }
    if (hi) {
#pragma unroll
      for (int i = 0; i < 2; i++) {
        pa[2][i] = ldg32((const uint32_t*)p.bre + o + 32 * i); pa[3][i] = ldg32((const uint32_t*)p.bim + o + 32 * i);
        pa[4][i] = ldg32((const uint32_t*)p.cre + o + 32 * i); pa[5][i] = ldg32((const uint32_t*)p.cim + o + 32 * i);
      }
      pds = ldg16(p.dskip + ch);
    }
  };
  load_params(tid >> 7);
  const int g = lane >> 2, q = lane & 3;
  unsigned* const cnt = p.scr->cnt;
  if (sid - 120u < 4u) { spare_work(p, &tmW1, sid - 120, tid); return; }
  if (elect1()) {
    const int gi = (warp + 1) & 15;
#pragma unroll
    for (int i = 0; i < 6; i++) mbar_init(bar + 48 * gi + 8 * i, gi < 7 ? 1 : gi == 7 ? 2 : gi < 10 ? 4 : 8);
    asm volatile("fence.mbarrier_init.release.cluster;" ::: "memory");
  }
  bar_sync(14, 512);
  if (warp == 14) {
    if ((uint32_t)__cvta_generic_to_shared(smem_raw) != sb) __trap();
    sts32(sb + OFF_ZERO + lane * 4, 0);
    if (lane == 0) { const unsigned e = p.scr->epoch[wid] + 1; p.scr->epoch[wid] = e; sts32(sb + OFF_EP, e); }
    __syncwarp();
  } else if (warp == 15) {
    int gpc, i;
    if (sid < 64) { gpc = (sid & 15) >> 1; i = sid >> 4; }
    else if (sid < 120) { const int t = sid - 64; i = t / 14; gpc = 1 + ((t - i * 14) >> 1); i += 4; }
    else { gpc = 0; i = 4 + ((sid - 124) >> 1); }
    const int qi = ((0x52741630 >> (4 * i)) & 7) * 2 + (sid & 1);
    sts64(sb + OFF_EP + 8, 4 * (gpc >> 1) + (qi >> 2), 4 * (gpc & 1) + (qi & 3));
    if (elect1()) {
      asm volatile("prefetch.tensormap [%0];\nprefetch.tensormap [%1];\nprefetch.tensormap [%2];\nprefetch.tensormap [%3];" ::"l"(&tmX), "l"(&tmW1), "l"(&tmU), "l"(&tmW2) : "memory");
      if (DELAY_NS) __nanosleep(DELAY_NS);
      bulk_prefetch(p.x + wid * 16 * DM, 16 * DM * 2);
    }
    __syncwarp();
  }
  uint32_t xv[2][10];

  float kacc[20];
  uint32_t k0h;
  auto kgen = [&](auto pass_c) {
    constexpr int pass = decltype(pass_c)::value;
    const int hsh = (warp & 1) * 16;
    const int wg = warp >> 2, kch = pass ? 4 : wg;
    const uint32_t pb = sb + OFF_P + kch * 3072;
    uint32_t xs[2];
    sts128(pb + (tid & 127) * 16, 0, 0, 0, 0);
    sts64(pb + 2048 + (tid & 127) * 8, 0, 0);
    const float dt = rnd_bf(expf(bflo(pld)));
    uint32_t ar = __funnelshift_r(pa[0][0], pa[0][1], hsh), ai = __funnelshift_r(pa[1][0], pa[1][1], hsh);
    const uint32_t ar1 = pa[0][1] >> hsh, ai1 = pa[1][1] >> hsh;
    cf c0, c1, c2;
    if (hi) {
      uint32_t w[4], v[4];
#pragma unroll
      for (int i = 0; i < 4; i++) { w[i] = __funnelshift_r(pa[2 + i][0], pa[2 + i][1], hsh); v[i] = pa[2 + i][1] >> hsh; }
      c0 = cmul(cf{bflo(w[2]), bflo(w[3])}, cf{bflo(w[0]), bflo(w[1])});
      c1 = cmul(cf{bfhi(w[2]), bfhi(w[3])}, cf{bfhi(w[0]), bfhi(w[1])});
      c2 = cmul(cf{bflo(v[2]), bflo(v[3])}, cf{bflo(v[0]), bflo(v[1])});
      const float mx = fmaxf(fmaxf(fmaxf(fabsf(c0.r), fabsf(c0.i)), fmaxf(fabsf(c1.r), fabsf(c1.i))), fmaxf(fabsf(c2.r), fabsf(c2.i)));
      const uint32_t mw = __reduce_max_sync(0xffffffffu, __float_as_uint(mx));
      float k0 = c0.r + c1.r + c2.r;
#pragma unroll
      for (int o = 16; o; o >>= 1) k0 += __shfl_xor_sync(0xffffffffu, k0, o);
      sts64(sb + OFF_K0 + kch * 16 + (warp & 1) * 8, __float_as_uint(k0), mw);
      bar_sync(3 + wg, 64);
      const uint4 e = lds128(sb + OFF_K0 + kch * 16);
      uint32_t kex = __float_as_uint(fmaxf(__uint_as_float(max(e.y, e.w)) * dt, fabsf(bflo(pds)) * (1.f / 256.f))) >> 23;
      kex = min(max(kex, 20u), 240u);
      const float s2 = __uint_as_float((259 - kex) << 23), sc = s2 * dt;
      k0h = pack_h(fmaf(__uint_as_float(e.x) + __uint_as_float(e.z), sc, bflo(pds) * s2), 0.f);
      sts32(sb + OFF_CHC + kch * 8, (kex - 5) * 0x00800080u);
      c0.r *= sc; c0.i *= sc; c1.r *= sc; c1.i *= sc; c2.r *= sc; c2.i *= sc;
    }
    if (pass == 0 && warp >= 8) {
      const __nv_bfloat16* xr = p.x + (wid * 16 + ((g >> 1) << 2) + (g & 1)) * DM;
      load_x(xv, xr + (warp - 8) * 80, 2 * DM, q);
      xs[0] = __ldg((const uint32_t*)xr); xs[1] = __ldg((const uint32_t*)(xr + 2 * DM));
    }
    const uint32_t kb0 = sb + (wg < 2 ? 81920 + wg * KBUF : 163840 + (wg - 2) * KBUF), kb1 = sb + (pass ? 163840 + KBUF : 81920 + (2 + wg) * KBUF);
    const float dl2 = dt * 1.4426950408889634f;
#pragma unroll 1
    for (int u = 0; u < 3; u++) {
      const uint32_t kb = (u & 1) ? kb1 : kb0, st = kb + (tid & 63) * 16;
      if (pass == 0) {
        if (warp == 15) {
          if (elect1()) {
            const uint2 rj = lds64(sb + OFF_EP + 8);
            if (u < 2) load1(u, &tmX, &tmW1, rj.x, rj.y);
            if (u) bulk_prefetch((u == 1 ? p.w1 : p.w2) + wid * 7680, 15360);
          }
          __syncwarp();
        }
        if (u == 2 && warp >= 8) {
          float sm[4] = {0.f, 0.f, 0.f, 0.f}, g0[4] = {0.f, 0.f, 0.f, 0.f}, g1[4] = {0.f, 0.f, 0.f, 0.f};
#pragma unroll
          for (int r = 0; r < 2; r++)
            xs[r] = fabsf(bflo(xs[r]) - bfhi(xs[r])) * 8.f < fabsf(bflo(xs[r])) ? __byte_perm(xs[r], 0, 0x1010) : 0u;
#pragma unroll
          for (int i = 0; i < 10; i += 2) {
            const uint32_t a0 = bsub(xv[0][i], xs[0]), a1 = bsub(xv[1][i], xs[1]), a2 = bsub(xv[0][i + 1], xs[0]), a3 = bsub(xv[1][i + 1], xs[1]);
            bmma(sm, a0, a1, a2, a3, 0x3f803f80u, 0x3f803f80u);
            bmma(g0, a0, a1, a2, a3, xv[0][i], xv[0][i + 1]);
            bmma(g1, a0, a1, a2, a3, xv[1][i], xv[1][i + 1]);
          }
          if (q == (g >> 1))
            sts128(sb + OFF_LNP + (warp - 8) * 128 + g * 16, __float_as_uint(sm[0]), __float_as_uint((g & 1) ? g0[1] : g0[0]),
                   __float_as_uint(sm[2]), __float_as_uint((g & 1) ? g1[3] : g1[2]));
          if (warp == 8) sts64(sb + OFF_LNP + 1024 + g * 8, xs[0], xs[1]);
          __syncwarp();
          bar_arrive(1, 288);
        }
      }
      const float zr = bflo(ar) * dl2, th = bflo(ai) * dt;
      if (!hi) {
        const cf w8 = cexp2(zr * 8.f, th * 8.f), w16 = csq(w8), w32 = csq(w16), w64 = csq(w32), w128 = csq(w64);
        hp lo[16];
        lo[0] = hpack(cf{1.f, 0.f}, w8);
        lo[1] = hmulc(lo[0], pack_h(w16.r, w16.i));
        { const uint32_t k = pack_h(w32.r, w32.i); lo[2] = hmulc(lo[0], k); lo[3] = hmulc(lo[1], k); }
        { const uint32_t k = pack_h(w64.r, w64.i);
#pragma unroll
          for (int i = 0; i < 4; i++) lo[4 + i] = hmulc(lo[i], k); }
        { const uint32_t k = pack_h(w128.r, w128.i);
#pragma unroll
          for (int i = 0; i < 8; i++) lo[8 + i] = hmulc(lo[i], k); }
#pragma unroll
        for (int j = 0; j < 4; j++) {
          const int w = (0x1302 >> (4 * j)) & 3;
          sts128(st + w * 2048, lo[4 * w].r, lo[4 * w + 1].r, lo[4 * w + 2].r, lo[4 * w + 3].r);
          sts128(st + w * 2048 + 1024, lo[4 * w].i, lo[4 * w + 1].i, lo[4 * w + 2].i, lo[4 * w + 3].i);
        }
      } else {
        const cf w1 = cexp2(zr, th), w256 = cexp2(zr * 256.f, th * 256.f), w512 = csq(w256), w1024 = csq(w512);
        uint32_t X[8], b2[4], b3[4];
        cf t = c0;
#pragma unroll
        for (int i = 0; i < 8; i++) { t = cmul(t, w1); X[i] = pack_h(t.r, t.i); }
        sts128(st + 8192, X[0], X[2], X[4], X[6]);
        { const uint32_t k = pack_h(w256.r, w256.i), kr = pack_h(-w256.i, w256.r);
#pragma unroll
          for (int i = 0; i < 4; i++) b2[i] = zmul(X[2 * i + 1], k, kr); }
        { const uint32_t k = pack_h(w512.r, w512.i), kr = pack_h(-w512.i, w512.r);
          b3[0] = zmul(X[3], k, kr); b3[1] = zmul(X[7], k, kr); b3[2] = zmul(b2[1], k, kr); b3[3] = zmul(b2[3], k, kr); }
        { const uint32_t k = pack_h(w1024.r, w1024.i), kr = pack_h(-w1024.i, w1024.r);
          sts128(st + 8192 + 4096, zmul(X[7], k, kr), zmul(b2[3], k, kr), zmul(b3[1], k, kr), zmul(b3[3], k, kr)); }
        sts128(st + 8192 + 1024, X[1], X[3], X[5], X[7]);
        sts128(st + 8192 + 2048, b2[0], b2[1], b2[2], b2[3]);
        sts128(st + 8192 + 3072, b3[0], b3[1], b3[2], b3[3]);
        c0 = c1; c1 = c2;
      }
      ar = odd_pair(ar, ar1); ai = odd_pair(ai, ai1);
      fence_async_smem();
      wg_wait<0>();
      bar_sync(8 + wg, 128);
      wg_fence();
#pragma unroll
      for (int kk = 0; kk < 4; kk++)
        wgmma_n40(kacc, dsc(((kb >> 4) | (8 << 16)) + kk * 16, 64), dsc(((kb >> 4) | (8 << 16)) + 512 + kk * 16, 64), (u | kk) != 0);
      wg_commit();
    }
  };
  auto taps = [&](int kch) {
    const uint32_t pb = sb + OFF_P + kch * 3072;
    wg_wait<0>();
    float kv[5];
#pragma unroll
    for (int b = 0; b < 5; b++) kv[b] = kacc[4 * b] - kacc[4 * b + 3];
    {
      const int i = (warp & 3) * 8 + g;
      const bool last = (tid & 127) == 127;
      const uint32_t h01 = pack_h(last ? 0.f : kv[1], last ? kv[0] - kv[1] : kv[0]), h23 = pack_h(kv[2], kv[3]), h4 = pack_h(kv[4], kv[1]);
      const uint32_t a = pb + (P0 + 8 * i + 2 * q + 1) * 4;
      sts16(a, h01 >> 16); sts32(a + 4, h01); sts16(a + 10, h01);
      put_tap<1>(pb + (((q & 1) ? PB1 + 1 : PA1) + 2 * i + (q >> 1)) * 4, h23);
      put_tap<2>(pb + (((q & 1) ? PB2 : PA2) + i + 32 * (q >> 1)) * 4, h23 >> 16);
      put_tap<1>(pb + (((g & 1) ? PB3 : PA3) + (i >> 1) + 16 * q) * 4, h4);
      if (last) {
        put_tap<1>(pb + PB1 * 4, h4 >> 16);
        put_tap<1>(pb + (PA1 + 64) * 4, h23);
        sts32(sb + OFF_CHC + kch * 8 + 4, __byte_perm(h23, 0, 0x3232));
      }
      if (hi && (tid & 63) == 0) put_tap<1>(pb + P0 * 4, k0h);
      __syncwarp();
    }
  };
  kgen(IC<0>{});

  if (warp < 8) {
    taps(warp >> 2);
    if (warp == 0) {
      bar_sync(2, 256);
      if (elect1()) { const uint2 rj = lds64(sb + OFF_EP + 8); load1(2, &tmX, &tmW1, rj.x, rj.y); }
      __syncwarp();
    } else bar_arrive(2, 256);
    if (warp == 1) {
      bar_sync(1, 288);
      float s1 = 0.f, s2 = 0.f;
#pragma unroll
      for (int w = 0; w < 8; w++) {
        const uint2 v = lds64(sb + OFF_LNP + w * 128 + g * 16 + (q & 1) * 8);
        s1 += __uint_as_float(v.x); s2 += __uint_as_float(v.y);
      }
      const float md = s1 * (1.f / DM), mean = bflo(lds32(sb + OFF_LNP + 1024 + g * 8 + (q & 1) * 4)) + md;
      const float var = fmaxf(fmaf(-md, mean, s2 * (1.f / DM)), 0.f);
      const float m = rnd_bf(mean);
      float sd, ri;
      asm("sqrt.approx.f32 %0, %1;" : "=f"(sd) : "f"(rnd_bf(rnd_bf(var) + 1e-5f)));
      asm("rcp.approx.f32 %0, %1;" : "=f"(ri) : "f"(rnd_bf(sd)));
      if (q < 2) {
        p.scr->stats[wid * 16 + ((g >> 1) << 2) + (g & 1) + 2 * q] = make_float2(-m, 0.5f * ri);
        sts64(sb + OFF_STAT + g * 16 + q * 8, __float_as_uint(-m * ri), __float_as_uint(ri));
      }
      __syncwarp();
    }
    float acc[96];
    const uint32_t alo = ((sb >> 4) | (1 << 16)) + (warp >> 2) * 512;
    bar_sync(0, 512);
#pragma unroll 1
    for (int s = 0; s < 10; s++) {
      const uint32_t so = (s & 3) * (SLOT1 >> 4);
      mbar_wait(bar + 8 * (B_FULL1 + s), 0);
      wg_fence();
#pragma unroll
      for (int kk = 0; kk < 4; kk++)
        wgmma_n192(acc, dsc(alo + so + kk * 2, 0x40000040u), dsc((((sb + 16384) >> 4) | (512 << 16)) + so + kk * 128, 0x40000040u), (s | kk) != 0);
      wg_commit();
      wg_wait<1>();
      if (lane == 0) mbar_arrive(bar + 8 * (B_REL1 + s));
    }
    wg_wait<0>();
    bar_arrive(14, 384);
    bar_arrive(7, 384);
    mbar_wait(bar + 8 * B_EPI, 0);
    const uint2 s0 = lds64(sb + OFF_STAT + (warp * 16 + g) * 8), s1 = lds64(sb + OFF_STAT + (warp * 16 + g + 8) * 8);
    const float nm0 = __uint_as_float(s0.x), r0 = __uint_as_float(s0.y), nm1 = __uint_as_float(s1.x), r1 = __uint_as_float(s1.y);
    const uint4 erj = lds128(sb + OFF_EP);
    const unsigned ep = erj.x;
    const int rg1 = erj.z, j1 = erj.w;
    uint4* hd = p.scr->h + (rg1 * 24 + j1) * 1024 + warp * 128 + q * 8 + g;
#pragma unroll
    for (int grp = 0; grp < 6; grp++) {
      uint32_t o0[4], o1[4];
#pragma unroll
      for (int tl = 0; tl < 4; tl++) {
        const int nt = grp * 4 + tl;
        const uint2 cs = lds64(sb + OFF_CS + (nt * 8 + 2 * q) * 4);
        const float ca = __uint_as_float(cs.x), cb = __uint_as_float(cs.y);
        const float a = fmaf(nm0, ca, acc[4 * nt]) * r0, b = fmaf(nm0, cb, acc[4 * nt + 1]) * r0;
        const float c = fmaf(nm1, ca, acc[4 * nt + 2]) * r1, d = fmaf(nm1, cb, acc[4 * nt + 3]) * r1;
        o0[tl] = pack_bf(fmaf(a, tanha(a), a), fmaf(b, tanha(b), b));
        o1[tl] = pack_bf(fmaf(c, tanha(c), c), fmaf(d, tanha(d), d));
      }
      uint4* dst = hd + (grp >> 1) * 8192 + (grp & 1) * 32;
      dst[0] = make_uint4(o0[0], o0[1], o0[2], o0[3]);
      dst[64] = make_uint4(o1[0], o1[1], o1[2], o1[3]);
      if (PACE_NS) __nanosleep(PACE_NS);
      if (grp == 1) {
        if (warp == 7) { bar_sync(2, 448); if (lane == 0) publish(cnt + C_H0 * 32); __syncwarp(); }
        else bar_arrive(2, 448);
      }
    }
    if (warp == 6) { bar_sync(11, 256); if (lane == 0) publish(cnt + (C_H1 + rg1) * 32); __syncwarp(); }
    else bar_arrive(11, 256);
    const int go = (rg1 * 128 + warp * 16 + g) * DM + j1 * 80;
    load_x(xv, p.x + go, 8 * DM, q);
    if (warp < 4) {
      const Comb cmb = comb_setup(tid, 0);
#pragma unroll 1
      for (int ch = 0; ch < 3; ch++) {
        combine(cmb, ch, wid, p.scr->sT, [] {});
      }
    } else if (warp == 4) {
      if (elect1()) {
        poll_cnt(cnt + C_H0 * 32, ep * 128);
#pragma unroll 1
        for (int s = 0; s < NS2 - 2; s++) {
          if (s == 4) poll_cnt(cnt + (C_H1 + rg1) * 32, ep * 8);
          if (s == 3) mbar_wait(bar + 8 * B_FREE, 0);
          if (s >= 3) mbar_wait(bar + 8 * (B_FREE + s - 2), 0);
          load2(s, sb + s * SLOT2, p.scr->h + (rg1 * 24 + s) * 1024, p.scr->w2p + (j1 * 24 + s) * 640);
        }
      }
      __syncwarp();
    }
    float acc2[40];
    bar_sync(8, 512);
    {
      const uint32_t al2 = ((sb >> 4) | (8 << 16)) + (warp >> 2) * 512;
      uint32_t so = 0;
#pragma unroll 1
      for (int s = 0; s < 24; s++) {
        mbar_wait(bar + 8 * (B_FULL2 + s), 0);
        wg_fence();
#pragma unroll
        for (int kk = 0; kk < 4; kk++)
          wgmma_n80(acc2, dsc(al2 + so + kk * 16, 64), dsc((((sb + 16384) >> 4) | (80 << 16)) + so + kk * 160, 8), (s | kk) != 0);
        wg_commit();
        so = so == (NS2 - 1) * (SLOT2 >> 4) ? 0 : so + (SLOT2 >> 4);
        wg_wait<1>();
        if (lane == 0) mbar_arrive(bar + 8 * (B_REL2 + s));
      }
    }
    mbar_wait(bar + 8 * B_SFULL, 0);
    uint32_t sv[5][4];
    {
      const int i = lane & 7, mi = lane >> 3;
      const uint32_t a = sb + OFF_U + ((mi >> 1) * 8 + i) * 256 + (((2 * warp + (mi & 1)) ^ i) << 4);
#pragma unroll
      for (int k = 0; k < 5; k++) ldsm4t(sv[k], a + k * 4096);
    }
    wg_wait<0>();
#pragma unroll
    for (int hh = 0; hh < 2; hh++) {
      uint32_t o[10];
      __nv_bfloat16* op = p.out + go + hh * 8 * DM;
#pragma unroll
      for (int tl = 0; tl < 10; tl++) {
        const float a = acc2[4 * tl + 2 * hh], b = acc2[4 * tl + 2 * hh + 1];
        o[tl] = bfma(sv[tl >> 1][(tl & 1) * 2 + hh], pack_bf(fmaf(a, tanhv(a), a), fmaf(b, tanhv(b), b)), xv[hh][tl]);
        if ((tl & 3) == 3)
          asm volatile("st.global.v4.u32 [%0], {%1, %2, %3, %4};" ::"l"((uint4*)op + (tl >> 2) * 4 + q), "r"(o[tl - 3]), "r"(o[tl - 2]), "r"(o[tl - 1]), "r"(o[tl]) : "memory");
      }
      asm volatile("st.global.v2.u32 [%0], {%1, %2};" ::"l"((uint2*)(op + 64) + q), "r"(o[8]), "r"(o[9]) : "memory");
    }
  } else {
    const int cw = warp - 8;
    if (warp < 12) load_params(4);
    bar_sync(0, 512);
    const uint4 erj = lds128(sb + OFF_EP);
    const unsigned ep = erj.x;
    const int rg1 = erj.z, j1 = erj.w;
    {
      if (warp == 15) {
        if (elect1()) load1(3, &tmX, &tmW1, rg1, j1);
        __syncwarp();
      }
      const uint4 st = lds128(sb + OFF_STAT + g * 16);
      const float n0 = __uint_as_float(st.x), r0 = __uint_as_float(st.y), n1 = __uint_as_float(st.z), r1 = __uint_as_float(st.w);
      const int up = upos(2 * wid);
      uint2* dst = (uint2*)p.scr->uT + ((up >> 1) * DM + (warp - 8) * 80) * 4 + (lane ^ ((up & 1) << 1));
#pragma unroll
      for (int i = 0; i < 10; i++) {
        const uint32_t a = movm(pack_h(fmaf(bflo(xv[0][i]), r0, n0), fmaf(bfhi(xv[0][i]), r0, n0)));
        const uint32_t b = movm(pack_h(fmaf(bflo(xv[1][i]), r1, n1), fmaf(bfhi(xv[1][i]), r1, n1)));
        dst[i * 32] = make_uint2(a, b);
      }
      if (warp != 12) bar_arrive(12, 256);
      wg_wait<0>();
      if (warp >= 12) bar_arrive(13, 256);
      if (warp == 12) {
        bar_sync(12, 256);
        if (elect1()) publish(cnt + C_LN * 32);
        __syncwarp();
      }
      if (warp == 15) {
        if (elect1()) {
#pragma unroll 1
          for (int s = 4; s < 10; s++) {
            mbar_wait(bar + 8 * (B_REL1 + s - 3), 0);
            load1(s, &tmX, &tmW1, rg1, j1);
          }
          poll_cnt(cnt + C_CS * 32, ep * 4);
          bulk_g2s(sb + OFF_CS, p.scr->cs + j1 * 192, 768, bar + 8 * B_EPI);
        }
        __syncwarp();
      }
    }
    taps(warp >> 2);
    if (warp < 12) {
      bar_sync(13, 256);
      kgen(IC<1>{});
      taps(4);
    }
    if (warp == 12) {
      if (elect1()) {
        mbar_expect(bar + 8 * B_UFULL, 144 * 160);
        mbar_expect(bar + 8 * B_EPI, 1024 + 768);
        poll_cnt(cnt + C_LN * 32, ep * 128);
        bulk_g2s(sb + OFF_STAT, p.scr->stats + rg1 * 128, 1024, bar + 8 * B_EPI);
      }
      bar_sync(15, 224);
      if (elect1()) tma2d(sb + OFF_U - 16 * 160, &tmU, wid * 80, -16, bar + 8 * B_UFULL);
      __syncwarp();
    } else if (warp != 15) {
      if (warp == 13 && elect1()) {
        mbar_expect(bar + 8 * B_W2, 96 * 176);
        tma5d(sb + OFF_W2S, &tmW2, (wid & 7) * 80, (wid >> 3) * 3, bar + 8 * B_W2);
      }
      const int tk = cw - (cw >> 2), uu = tk >> 1, G = tk & 1;
      const int grp = (wid >> 3) * 3 + uu, jj = grp / 6, rem = grp - jj * 6;
      const uint32_t a = sb + OFF_W2S + (uu * 32 + lane) * 176;
      uint4* dst = p.scr->w2p + ((wid & 7) * 24 + 8 * (rem >> 1) + jj) * 640 + ((rem & 1) * 4 + (lane >> 3)) * 80 + (lane & 7);
      mbar_wait(bar + 8 * B_W2, 0);
      const uint4 wv[4] = {lds128(a + G * 64), lds128(a + G * 64 + 16), lds128(a + G * 64 + 32), lds128(a + G * 64 + 48)};
      const uint4 t0 = lds128(a + 128), t1 = lds128(a + 144);
      uint32_t w[20];
#pragma unroll
      for (int i = 0; i < 16; i++) w[i] = bmul((&wv[i >> 2].x)[i & 3], 0x3f003f00u);
      w[16] = bmul(G ? t0.y : t0.x, 0x3f003f00u); w[17] = bmul(G ? t0.w : t0.z, 0x3f003f00u);
      w[18] = bmul(G ? t1.y : t1.x, 0x3f003f00u); w[19] = bmul(G ? t1.w : t1.z, 0x3f003f00u);
      fence_async_smem();
      bar_sync(15, 224);
#pragma unroll
      for (int i = 0; i < 4; i++) dst[G * 32 + 8 * i] = make_uint4(w[i], w[4 + i], w[8 + i], w[12 + i]);
      dst[64 + G * 8] = make_uint4(w[16], w[17], w[18], w[19]);
      bar_arrive(2, 448);
    }
    const int wg = warp >> 2, role = (warp + 2 * wg) & 3;
    uint32_t co[6], cpa = (g - 2 * q) * 4;
    if (role < 2) {
#pragma unroll
      for (int gm = 0; gm < 3; gm++) {
        const int hb = 2 * (lane & 7) + role - 2 + gm, l3 = ((lane >> 3) ^ (hb >> 1)) & 7;
        co[2 * gm] = hb * 1280 + uoff(l3); co[2 * gm + 1] = hb * 1280 + uoff(l3 ^ 4);
      }
    } else {
      const int mi = lane >> 3, hf = (lane >> 2) & 1;
      co[0] = hf * 1792 + (mi ^ hf) * 64 + ((q ^ (mi >> 1) ^ (hf * 2)) << 4);
      co[1] = co[0] ^ 96;
      co[2] = (lane ^ (role == 2 ? (mi & 1) : ((lane >> 1) & 4))) << 4;
      co[3] = lane * 16;
      co[4] = (g >> 1) == q ? ((g & 1) ? 0xffff0000u : 0xffffu) : 0u;
      co[5] = 2 * cpa;
    }
    const uint32_t zero = lds32(sb + OFF_ZERO), nz = zero | 0x80000000u;
#pragma unroll
    for (int i = 0; i < 6; i++) co[i] = pin(co[i], zero);
    cpa = pin(cpa, zero);
    const Comb cmb = comb_setup(tid, zero);
    mbar_wait(bar + 8 * B_UFULL, 0);
#pragma unroll 1
    for (unsigned seq = (cw >> 2) ? 0xb9ac : 0x8; seq; seq >>= 4) {
      const int ch = seq & 7;
      if (ch == 1) bar_arrive(0, 256);
      if (ch < 4) mbar_wait(bar + 8 * (B_REL1 + (ch ? 8 : 7)), 0);
      const int qt = (cw + ch) & 3, j = qt * 32 + lane;
      const uint32_t ub = sb + OFF_U + ch * 32, zb = sb + OFF_Z + ch * ZSZ;
      uint32_t w_[20], o_[20], d_[20], b3_[20];
      uint32_t *w = w_ + 8, *o = o_ + 8, *d = d_ + 8, *b3 = b3_ + 8;
      {
        const uint32_t am = ub + uoff(upos(2 * j - 2)), a0 = ub + uoff(upos(2 * j));
        const uint2 a = lds64(am + 8);
        const uint4 b = lds128(am ^ 16), c = lds128(a0), e = lds128(a0 ^ 16);
        w[8] = lds32(ub + uoff(upos((2 * j + 2) & 255)));
        w[-6] = a.x; w[-5] = a.y; w[-4] = b.x; w[-3] = b.y; w[-2] = b.z; w[-1] = b.w;
        w[0] = c.x; w[1] = c.y; w[2] = c.z; w[3] = c.w; w[4] = e.x; w[5] = e.y; w[6] = e.z; w[7] = e.w;
      }
#pragma unroll
      for (int i = -1; i <= 7; i++) o[i] = odd_pair(w[i], w[i + 1]);
#pragma unroll
      for (int i = 0; i <= 7; i++) { d[i] = hadd(w[i], o[i]); b3[i] = hadd(d[i], o[i - 1]); }
      if (j < 112) {
        const int gr = j >> 1;
        const uint32_t a1 = zb + ZA1 + 512 + (gr ^ ((gr >> 2) & 1)) * 64 + ((gr >> 1) & 3) * 16 + (j & 1) * 8;
#pragma unroll
        for (int pp = 0; pp < 4; pp++) {
          const uint32_t sel = (pp & 1) ? 0x7632 : 0x5410;
          const int k = pp >> 1;
          sts64(a1 ^ (pp * 16), __byte_perm(w[k - 1], w[k + 1], sel), __byte_perm(w[k + 3], w[k + 5], sel));
          sts64((a1 ^ (pp * 16)) + (ZB1 - ZA1), __byte_perm(b3[k], b3[k + 2], sel), __byte_perm(b3[k + 4], b3[k + 6], sel));
        }
      } else {
        const uint32_t a1 = zb + ZA1 + ((lane ^ 7) & 15) * 16;
        sts128(a1, 0, 0, 0, 0); sts128(a1 + 256, 0, 0, 0, 0); sts128(a1 + ZB1 - ZA1, 0, 0, 0, 0);
        sts128(a1 + ZB1 - ZA1 + 256, 0, 0, 0, j == 127 ? w[8] << 16 : 0u);
      }
      if (qt < 3) {
        uint32_t e_[20], b5_[20];
        uint32_t *e = e_ + 8, *b5 = b5_ + 8;
#pragma unroll
        for (int i = -6; i <= -2; i++) o[i] = odd_pair(w[i], w[i + 1]);
#pragma unroll
        for (int i = -6; i <= -1; i++) d[i] = hadd(w[i], o[i]);
#pragma unroll
        for (int i = -5; i <= -1; i++) b3[i] = hadd(d[i], o[i - 1]);
#pragma unroll
        for (int i = -5; i <= 4; i++) e[i] = hadd(d[i - 1], d[i]);
#pragma unroll
        for (int i = -4; i <= 4; i++) b5[i] = hadd(e[i], w[i + 1]);
        const uint32_t a2 = zb + ((j >> 3) * 16 + (j & 7)) * 16;
        sts128(a2 + ZA2, b3[-2], b3[-1], b3[0], b3[1]);
        sts128(a2 + ZA2 + 128, b3[2], b3[3], b3[4], b3[5]);
        sts128(a2 + ZB2, b5[-4], b5[-3], b5[-2], b5[-1]);
        sts128(a2 + ZB2 + 128, b5[0], b5[1], b5[2], b5[3]);
        if (qt < 2) {
          sts128(a2 + ZS, d[-2], d[-1], d[0], d[1]);
          sts128(a2 + ZS + 128, d[2], d[3], d[4], d[5]);
          uint32_t b7[8], b9[8];
#pragma unroll
          for (int i = -4; i <= 3; i++) { b7[i + 4] = hadd(b3[i - 1], e[i + 1]); b9[i + 4] = hadd(e[i - 1], b5[i + 1]); }
          const uint32_t a3 = zb + ((j >> 4) * 32 + (j & 15)) * 16;
          sts128(a3 + ZA3, b7[0], b7[1], b7[2], b7[3]);
          sts128(a3 + ZA3 + 256, b7[4], b7[5], b7[6], b7[7]);
          sts128(a3 + ZB3 + 256, b9[0], b9[1], b9[2], b9[3]);
          if (j < 63) sts128(a3 + ZB3 + ((j & 15) == 15 ? 272 : 16), b9[4], b9[5], b9[6], b9[7]);
          else sts128(zb + ZB3, 0, 0, 0, 0);
        }
      }
    }
    bar_sync(wg == 2 ? 14 : 7, 384);
#pragma unroll 1
    for (int ch = wg - 2; ch < 5; ch += 2) {
      const uint32_t ub = sb + OFF_U + ch * 32, zb = sb + OFF_Z + ch * ZSZ, pb = sb + OFF_P + ch * 3072;
      if (ch == 2) bar_sync(0, 256);
      const uint32_t pa = pb + cpa;
      if (role < 2) {
        float acc[8][4];
#pragma unroll
        for (int r = 0; r < 8; r++) { acc[r][0] = acc[r][1] = acc[r][2] = acc[r][3] = 0.f; }
        float fix = 0.f;
        if (role == 1 && lane == 28) {
          const uint32_t k = lds32(pb + PB1 * 4), u0 = lds32(ub);
          fix = __low2float(*reinterpret_cast<const __half2*>(&k)) * __low2float(*reinterpret_cast<const __half2*>(&u0));
        }
        uint32_t b[12][4], A[17][4];
#pragma unroll
        for (int i = 11; i >= 8; i--) ldsm4(b[i], ub + (co[4 + (i & 1)] ^ (((i >> 1) & 1) * 16)) + ((i >> 1) & 1) * 640);
        A[0][0] = lds32(pa + P0 * 4); A[0][1] = lds32(pa + P0 * 4 + 32); A[0][2] = lds32(sb + OFF_ZERO + 4);
#pragma unroll
        for (int m = 0; m <= 16; m++) {
          if (m < 16) {
            A[m + 1][0] = lds32(pa + P0 * 4 + (2 * m + 2) * 32);
            A[m + 1][1] = m < 15 ? lds32(pa + P0 * 4 + (2 * m + 3) * 32) : lds32(sb + OFF_ZERO + 8);
          }
          if ((m & 1) == 0 && m < 16) {
            const int i = 7 - (m >> 1);
            ldsm4(b[i], ub + (co[2 * (i >> 2) + (i & 1)] ^ (((i >> 1) & 1) * 16)) + ((i >> 1) & 1) * 640);
          }
          if (m == 9 && elect1()) mbar_arrive(bar + 8 * (B_PAIR + ch));
          A[m][3] = dup(A[m][0], nz);
          if (m < 16) A[m + 1][2] = dup(A[m][1], nz);
#pragma unroll
          for (int r = 7; r >= 0; r--) {
            const int f = 16 + r - m;
            hmma(acc[r], A[m][0], A[m][1], A[m][2], A[m][3], b[f >> 1][(f & 1) * 2], b[f >> 1][(f & 1) * 2 + 1]);
          }
        }
        acc[7][2] += fix;
        mbar_wait(bar + 8 * (B_PAIR + ch), 0);
#pragma unroll
        for (int i = 3; i >= 0; i--)
          stsm4t(ub + (co[4 + (i & 1)] ^ (((i >> 1) & 1) * 16)) + ((i >> 1) & 1) * 640, pack_bf(acc[2 * i][0], acc[2 * i][1]), pack_bf(acc[2 * i][2], acc[2 * i][3]),
                 pack_bf(acc[2 * i + 1][0], acc[2 * i + 1][1]), pack_bf(acc[2 * i + 1][2], acc[2 * i + 1][3]));
      } else if (role == 2) {
        float acc[14][4];
#pragma unroll
        for (int r = 0; r < 14; r++) { acc[r][0] = acc[r][1] = acc[r][2] = acc[r][3] = 0.f; }
#pragma unroll
        for (int arr = 0; arr < 2; arr++) {
          uint32_t A[5][4];
#pragma unroll
          for (int m = 0; m < 5; m++) {
            A[m][0] = lds32(pa + (arr ? PB1 : PA1) * 4 + m * 64);
            A[m][1] = m < 4 ? lds32(pa + (arr ? PB1 : PA1) * 4 + m * 64 + 32) : lds32(sb + OFF_ZERO + 4 + arr * 8);
          }
#pragma unroll
          for (int m = 4; m >= 1; m--) { A[m][2] = dup(A[m - 1][1], nz); A[m][3] = dup(A[m][0], nz); }
          A[0][2] = lds32(sb + OFF_ZERO + 8 + arr * 8); A[0][3] = dup(A[0][0], nz);
#pragma unroll
          for (int ip = 0; ip < 9; ip++) {
            uint32_t b[4];
            ldsm4(b, zb + co[ip & 1] + (arr ? ZB1 : ZA1) + ip * 256);
#pragma unroll
            for (int hh = 0; hh < 2; hh++)
#pragma unroll
              for (int m = 0; m < 5; m++) {
                const int i = 2 * ip + hh - 4 + m;
                if (i >= 0 && i < 14) hmma(acc[i], A[m][0], A[m][1], A[m][2], A[m][3], b[2 * hh], b[2 * hh + 1]);
              }
          }
        }
        const uint32_t a = zb + ZA1 + 512 + co[2];
#pragma unroll
        for (int i = 0; i < 7; i++)
          stsm4(a + i * 512, pack_bf(acc[2 * i][0], acc[2 * i][1]), pack_bf(acc[2 * i][2], acc[2 * i][3]),
                pack_bf(acc[2 * i + 1][0], acc[2 * i + 1][1]), pack_bf(acc[2 * i + 1][2], acc[2 * i + 1][3]));
      } else {
        float acc[12][4];
        const uint32_t za = zb + co[3];
        {
          float d[4][2][4];
#pragma unroll
          for (int r = 0; r < 8; r++) { d[r >> 1][r & 1][0] = d[r >> 1][r & 1][1] = d[r >> 1][r & 1][2] = d[r >> 1][r & 1][3] = 0.f; }
#pragma unroll
          for (int arr = 0; arr < 2; arr++) {
            uint32_t A[4][4];
#pragma unroll
            for (int m = 0; m < 4; m++) { A[m][0] = lds32(pa + (arr ? PB3 : PA3) * 4 + m * 64); A[m][1] = lds32(pa + (arr ? PB3 : PA3) * 4 + m * 64 + 32); }
#pragma unroll
            for (int m = 0; m < 4; m++) { A[m][2] = m ? dup(A[m - 1][1], nz) : lds32(sb + OFF_ZERO + 4 + arr * 4); A[m][3] = dup(A[m][0], nz); }
#pragma unroll
            for (int io = 0; io < 4; io++) {
              uint32_t b[4];
              ldsm4t(b, za + (arr ? ZB3 : ZA3) + io * 512);
#pragma unroll
              for (int m = 0; m + io < 4; m++) {
                hmma(d[io + m][0], A[m][0], A[m][1], A[m][2], A[m][3], b[0], b[1]);
                hmma(d[io + m][1], A[m][0], A[m][1], A[m][2], A[m][3], b[2], b[3]);
              }
            }
          }
#pragma unroll
          for (int r = 0; r < 4; r++) {
            acc[r][0] = acc[r][1] = acc[r][2] = acc[r][3] = 0.f;
            acc[4 + 2 * r][0] = d[r][0][0]; acc[4 + 2 * r][1] = d[r][0][1]; acc[4 + 2 * r][2] = d[r][1][0]; acc[4 + 2 * r][3] = d[r][1][1];
            acc[5 + 2 * r][0] = d[r][0][2]; acc[5 + 2 * r][1] = d[r][0][3]; acc[5 + 2 * r][2] = d[r][1][2]; acc[5 + 2 * r][3] = d[r][1][3];
          }
        }
        {
          const uint32_t k0 = lds32(sb + OFF_CHC + ch * 8 + 4) & co[4];
          const uint32_t k1 = lds32(sb + OFF_ZERO + 12), k2 = lds32(sb + OFF_ZERO + 16), k3 = dup(k0, nz);
#pragma unroll
          for (int ip = 0; ip < 4; ip++) {
            uint32_t b[4];
            ldsm4t(b, za + ZS + ip * 512);
            hmma(acc[4 + 2 * ip], k0, k1, k2, k3, b[0], b[1]);
            hmma(acc[5 + 2 * ip], k0, k1, k2, k3, b[2], b[3]);
          }
        }
        const uint32_t pa2 = pb + co[5];
#pragma unroll
        for (int arr = 0; arr < 2; arr++) {
          uint32_t A[5][4];
#pragma unroll
          for (int m = 0; m < 5; m++) {
            const uint2 v = lds64(pa2 + (arr ? PB2 : PA2) * 4 + m * 64);
            A[m][0] = v.x; A[m][1] = v.y; A[m][2] = lds32(pa2 + (arr ? PB2 : PA2) * 4 + m * 64 - 4);
          }
#pragma unroll
          for (int m = 0; m < 5; m++) A[m][3] = dup(A[m][0], nz);
#pragma unroll
          for (int ip = 0; ip < 6; ip++) {
            uint32_t b[4];
            ldsm4t(b, za + (arr ? ZB2 : ZA2) + ip * 512);
#pragma unroll
            for (int hh = 0; hh < 2; hh++)
#pragma unroll
              for (int m = 0; m < 5; m++) {
                const int i = 2 * ip + hh + m;
                if (i < 12) hmma(acc[i], A[m][0], A[m][1], A[m][2], A[m][3], b[2 * hh], b[2 * hh + 1]);
              }
          }
        }
        const uint32_t a = zb + ZA2 + co[2];
#pragma unroll
        for (int i = 0; i < 6; i++)
          stsm4(a + i * 512, pack_bf(acc[2 * i][0], acc[2 * i][1]), pack_bf(acc[2 * i][2], acc[2 * i][3]),
                pack_bf(acc[2 * i + 1][0], acc[2 * i + 1][1]), pack_bf(acc[2 * i + 1][2], acc[2 * i + 1][3]));
      }
      __syncwarp();
      if (elect1()) mbar_arrive(bar + 8 * (B_PART + ch));
    }
    const uint4* srcA = p.scr->h + (rg1 * 24 + NS2 - 2) * 1024;
    const uint4* srcB = p.scr->w2p + (j1 * 24 + NS2 - 2) * 640;
    combine(cmb, 6 - wg, wid, p.scr->sT, [&] {
      if (warp == 12) {
        bar_sync(8, 512);
        if (elect1()) {
          asm volatile("fence.proxy.async.global;" ::: "memory");
          load2(NS2 - 2, sb + (NS2 - 2) * SLOT2, srcA, srcB);
          load2(NS2 - 1, sb + (NS2 - 1) * SLOT2, srcA + 1024, srcB + 640);
        }
        __syncwarp();
      } else bar_arrive(8, 512);
    });
    if (warp == 12) {
      if (elect1()) {
        uint32_t d = sb;
#pragma unroll 1
        for (int s = NS2; s < 24; s++) {
          mbar_wait(bar + 8 * (B_REL2 + s - NS2 + 1), 0);
          load2(s, d, srcA + 2048, srcB + 1280);
          srcA += 1024; srcB += 640;
          d = d == sb + (NS2 - 1) * SLOT2 ? sb : d + SLOT2;
        }
      }
      __syncwarp();
    } else if (warp == 13) {
      if (elect1()) {
#pragma unroll 1
        for (int c = 2; c < 5; c++) mbar_wait(bar + 8 * (B_FREE + c), 0);
        publish(cnt + (C_S + (wid >> 4)) * 32);
        mbar_expect(bar + 8 * B_SFULL, 20480);
        poll_cnt(cnt + (C_S + j1) * 32, ep * 16);
        mbar_wait(bar + 8 * (B_REL2 + 24 - NS2), 0);
        bulk_g2s(sb + OFF_U, p.scr->sT + (j1 * 16 + rg1) * 1280, 20480, bar + 8 * B_SFULL);
      }
      __syncwarp();
    }
  }
}

typedef CUresult (*EncodeFn)(CUtensorMap*, CUtensorMapDataType, cuuint32_t, void*, const cuuint64_t*, const cuuint64_t*,
                             const cuuint32_t*, const cuuint32_t*, CUtensorMapInterleave, CUtensorMapSwizzle,
                             CUtensorMapL2promotion, CUtensorMapFloatOOBfill);

}

extern "C" void kernel_launch(void* const* d_in, const int* in_sizes, int n_in, void* d_out, int out_size) {
  static EncodeFn enc = nullptr;
  static int nsm = 0;
  static void* scr = nullptr;
  if (!enc) {
    void* fn = nullptr;
    cudaDriverEntryPointQueryResult qr;
    cudaGetDriverEntryPoint("cuTensorMapEncodeTiled", &fn, cudaEnableDefault, &qr);
    enc = (EncodeFn)fn;
    int dev = 0;
    cudaGetDevice(&dev);
    cudaDeviceGetAttribute(&nsm, cudaDevAttrMultiProcessorCount, dev);
    cudaFuncSetAttribute(fused_s4_ffn_kernel<true>, cudaFuncAttributeMaxDynamicSharedMemorySize, SMEM_BYTES);
    cudaFuncSetAttribute(fused_s4_ffn_kernel<false>, cudaFuncAttributeMaxDynamicSharedMemorySize, SMEM_BYTES);
    cudaGetSymbolAddress(&scr, g_scr);
  }
  Params p;
  p.x = (const __nv_bfloat16*)d_in[0];
  p.are = (const __nv_bfloat16*)d_in[1]; p.aim = (const __nv_bfloat16*)d_in[2];
  p.bre = (const __nv_bfloat16*)d_in[3]; p.bim = (const __nv_bfloat16*)d_in[4];
  p.cre = (const __nv_bfloat16*)d_in[5]; p.cim = (const __nv_bfloat16*)d_in[6];
  p.logdt = (const __nv_bfloat16*)d_in[7]; p.dskip = (const __nv_bfloat16*)d_in[8];
  p.w1 = (const __nv_bfloat16*)d_in[10]; p.w2 = (const __nv_bfloat16*)d_in[11];
  p.out = (__nv_bfloat16*)d_out;
  p.scr = (Scratch*)scr;
  CUtensorMap tmX, tmW1, tmU, tmW2;
  const cuuint32_t es[5] = {1, 1, 1, 1, 1};
  {
    const cuuint64_t gd[5] = {DM, 2, 4, 4, FF / 32}, gs[4] = {DM * 2, DM * 16, DM * 4, DM * 64};
    const cuuint32_t bx[5] = {88, 2, 4, 4, 3};
    enc(&tmW2, CU_TENSOR_MAP_DATA_TYPE_BFLOAT16, 5, d_in[11], gd, gs, bx, es, CU_TENSOR_MAP_INTERLEAVE_NONE,
        CU_TENSOR_MAP_SWIZZLE_NONE, CU_TENSOR_MAP_L2_PROMOTION_NONE, CU_TENSOR_MAP_FLOAT_OOB_FILL_NONE);
  }
  {
    const cuuint64_t gd[2] = {16 * DM, 128}, gs[1] = {DM * 32};
    const cuuint32_t bx[2] = {80, 144};
    enc(&tmU, CU_TENSOR_MAP_DATA_TYPE_FLOAT16, 2, p.scr->uT, gd, gs, bx, es, CU_TENSOR_MAP_INTERLEAVE_NONE,
        CU_TENSOR_MAP_SWIZZLE_NONE, CU_TENSOR_MAP_L2_PROMOTION_NONE, CU_TENSOR_MAP_FLOAT_OOB_FILL_NONE);
  }
  {
    const cuuint64_t gd[2] = {DM, SEQ}, gs[1] = {DM * 2};
    const cuuint32_t bx[2] = {64, 128};
    enc(&tmX, CU_TENSOR_MAP_DATA_TYPE_BFLOAT16, 2, d_in[0], gd, gs, bx, es, CU_TENSOR_MAP_INTERLEAVE_NONE,
        CU_TENSOR_MAP_SWIZZLE_128B, CU_TENSOR_MAP_L2_PROMOTION_L2_128B, CU_TENSOR_MAP_FLOAT_OOB_FILL_NONE);
  }
  {
    const cuuint64_t gd[3] = {64, DM, FF / 64}, gs[2] = {FF * 2, 128};
    const cuuint32_t bx[3] = {64, 64, 3};
    enc(&tmW1, CU_TENSOR_MAP_DATA_TYPE_BFLOAT16, 3, d_in[10], gd, gs, bx, es, CU_TENSOR_MAP_INTERLEAVE_NONE,
        CU_TENSOR_MAP_SWIZZLE_128B, CU_TENSOR_MAP_L2_PROMOTION_L2_128B, CU_TENSOR_MAP_FLOAT_OOB_FILL_NONE);
  }
  if (nsm == 132) fused_s4_ffn_kernel<true><<<132, 512, SMEM_BYTES>>>(p, tmX, tmW1, tmU, tmW2);
  else fused_s4_ffn_kernel<false><<<132, 512, SMEM_BYTES>>>(p, tmX, tmW1, tmU, tmW2);
}
```

```cpp
#include <cuda_runtime.h>
#include <cuda_bf16.h>
#include <cuda_fp16.h>
#include <cuda.h>
#include <stdint.h>

namespace {

constexpr int SEQ = 2048, DM = 640, FF = 1536;

constexpr int SLOT1 = 40960;
constexpr int SLOT2 = 26624;
constexpr int NS2 = 7;
#define DELAY2_NS 0
#define DELAY3_NS 300
#define EARLY 0
#define XPF 1
#define GATE 0
#define SPARE_NS 300
#define DELAY_NS 100
#define PACE_NS 60
constexpr int OFF_Z = 85504, ZSZ = 20480;
constexpr int ZA3 = 0, ZB3 = 2048, ZS = 4096, ZA2 = 6144, ZB2 = 9216, ZA1 = 12288, ZB1 = 16384;
constexpr int OFF_W2S = 3 * SLOT1;
constexpr int OFF_U = 190464;
constexpr int OFF_P = 210944;
constexpr int OFF_KS = 163840;
constexpr int OFF_LNP = 225280;
constexpr int OFF_MISC = 226304;
constexpr int OFF_CHC = OFF_MISC + 16;
constexpr int OFF_EP = OFF_MISC + 64;
constexpr int OFF_ZERO = OFF_MISC + 128;
constexpr int OFF_STAT = OFF_MISC + 1024;
constexpr int OFF_CS = OFF_MISC + 2048;
constexpr int OFF_BAR = OFF_MISC + 2816;
constexpr int SMEM_BYTES = OFF_MISC + 6144;
constexpr int P0 = 8, PA1 = 280, PB1 = 360, PA2 = 448, PB2 = 544, PA3 = 632, PB3 = 704;
enum { B_FULL1 = 0, B_FULL2 = 10, B_UFULL = 34, B_EPI = 35, B_SFULL = 36, B_W2 = 37,
       B_PAIR = 42,
       B_FREE = 48, B_PART = 54,
       B_REL1 = 60, B_REL2 = 70 };
enum { C_LN = 0, C_CS = 1, C_H0 = 2, C_H1 = 18, C_S = 34, C_W2 = 42, C_NUM = 43 };

struct Scratch {
  unsigned cnt[64 * 32];
  unsigned epoch[256];
  float2 stats[SEQ];
  float cs[FF];
  uint4 uT[DM * 256];
  uint4 w2p[8 * 24 * 640];
  uint4 sT[8 * 16 * 1280];
  uint4 h[16 * 24 * 1024];
};
__device__ __align__(1024) Scratch g_scr;
constexpr uint32_t sb = 1024;
constexpr uint32_t bar = sb + OFF_BAR;

struct Params {
  const __nv_bfloat16 *are, *aim, *bre, *bim, *cre, *cim, *logdt, *dskip, *x, *w1, *w2;
  __nv_bfloat16* out;
  Scratch* scr;
};

__device__ __forceinline__ void mbar_init(uint32_t a, int c) { asm volatile("mbarrier.init.shared::cta.b64 [%0], %1;" ::"r"(a), "r"(c)); }
__device__ __forceinline__ void mbar_expect(uint32_t a, int b) { asm volatile("mbarrier.arrive.expect_tx.shared::cta.b64 _, [%0], %1;" ::"r"(a), "r"(b) : "memory"); }
__device__ __forceinline__ void mbar_arrive(uint32_t a) { asm volatile("mbarrier.arrive.shared::cta.b64 _, [%0];" ::"r"(a) : "memory"); }
__device__ __forceinline__ void mbar_wait(uint32_t a, int ph) {
  asm volatile(
      "{\n.reg .pred p;\n.reg .u32 n;\n"
      "mbarrier.try_wait.parity.shared::cta.b64 p, [%0], %1;\n@p bra LD;\nmov.u32 n, 0;\n"
      "LW:\nmbarrier.try_wait.parity.shared::cta.b64 p, [%0], %1, 20000;\n@p bra LD;\n"
      "add.u32 n, n, 1;\nsetp.lt.u32 p, n, 100000;\n@p bra LW;\ntrap;\nLD:\n}\n" ::"r"(a), "r"(ph) : "memory");
}
__device__ __forceinline__ void poll_cnt(const unsigned* p, unsigned target) {
  asm volatile(
      "{\n.reg .pred p;\n.reg .u32 n;\n.reg .s32 v;\nmov.u32 n, 0;\n"
      "LW:\nld.relaxed.gpu.global.u32 v, [%0];\nsub.s32 v, v, %1;\nsetp.ge.s32 p, v, 0;\n@p bra LD;\n"
      "nanosleep.u32 64;\nadd.u32 n, n, 1;\nsetp.lt.u32 p, n, 4000000;\n@p bra LW;\ntrap;\n"
      "LD:\nfence.acquire.gpu;\nfence.proxy.async.global;\n}\n" ::"l"(p), "r"(target) : "memory");
}
__device__ __forceinline__ void publish(unsigned* p) {
  asm volatile("fence.proxy.async.global;\nfence.release.gpu;\nred.relaxed.gpu.global.add.u32 [%0], 1;" ::"l"(p) : "memory");
}
__device__ __forceinline__ uint32_t movm(uint32_t v) { uint32_t r; asm volatile("movmatrix.sync.aligned.m8n8.trans.b16 %0, %1;" : "=r"(r) : "r"(v)); return r; }
__device__ __forceinline__ void fence_async_smem() { asm volatile("fence.proxy.async.shared::cta;" ::: "memory"); }
__device__ __forceinline__ bool elect1() { uint32_t p; asm volatile("{\n.reg .pred P;\nelect.sync _|P, 0xffffffff;\nselp.u32 %0,1,0,P;\n}\n" : "=r"(p)); return p; }
__device__ __forceinline__ void bar_sync(int id, int n) { asm volatile("bar.sync %0, %1;" ::"r"(id), "r"(n) : "memory"); }
__device__ __forceinline__ void bar_arrive(int id, int n) { asm volatile("bar.arrive %0, %1;" ::"r"(id), "r"(n) : "memory"); }
__device__ __forceinline__ void bulk_g2s(uint32_t dst, const void* src, int bytes, uint32_t mb) {
  asm volatile("cp.async.bulk.shared::cluster.global.mbarrier::complete_tx::bytes [%0], [%1], %2, [%3];" ::"r"(dst), "l"(src), "r"(bytes), "r"(mb) : "memory");
}
__device__ __forceinline__ void bulk_prefetch(const void* src, int bytes) { asm volatile("cp.async.bulk.prefetch.L2.global [%0], %1;" ::"l"(src), "r"(bytes) : "memory"); }
__device__ __forceinline__ void tma2d(uint32_t dst, const CUtensorMap* m, int c0, int c1, uint32_t mb) {
  asm volatile("cp.async.bulk.tensor.2d.shared::cluster.global.mbarrier::complete_tx::bytes [%0], [%1, {%3, %4}], [%2];" ::"r"(dst), "l"(m), "r"(mb), "r"(c0), "r"(c1) : "memory");
}
__device__ __forceinline__ void tma3d(uint32_t dst, const CUtensorMap* m, int c0, int c1, int c2, uint32_t mb) {
  asm volatile("cp.async.bulk.tensor.3d.shared::cluster.global.mbarrier::complete_tx::bytes [%0], [%1, {%3, %4, %5}], [%2];" ::"r"(dst), "l"(m), "r"(mb), "r"(c0), "r"(c1), "r"(c2) : "memory");
}
__device__ __forceinline__ unsigned frag_col(unsigned l) { return (l & 0x61) | ((l & 6) << (2 - (l >> 6))) | ((l >> 2) & 6); }
__device__ __forceinline__ void tma5d(uint32_t dst, const CUtensorMap* m, int c0, int c4, uint32_t mb) {
  asm volatile("cp.async.bulk.tensor.5d.shared::cluster.global.mbarrier::complete_tx::bytes [%0], [%1, {%3, %5, %5, %5, %4}], [%2];" ::"r"(dst), "l"(m), "r"(mb), "r"(c0), "r"(c4), "r"(0) : "memory");
}
__device__ __forceinline__ uint64_t dsc(uint32_t lo, uint32_t hi) { return ((uint64_t)hi << 32) | lo; }
__device__ __forceinline__ void wg_fence() { asm volatile("wgmma.fence.sync.aligned;" ::: "memory"); }
__device__ __forceinline__ void wg_commit() { asm volatile("wgmma.commit_group.sync.aligned;" ::: "memory"); }
template <int N> __device__ __forceinline__ void wg_wait() { asm volatile("wgmma.wait_group.sync.aligned %0;" ::"n"(N) : "memory"); }
__device__ __forceinline__ void wgmma_n192(float (&d)[96], uint64_t da, uint64_t db, int scale_d) {
  asm volatile("{\n.reg .pred p;\nsetp.ne.b32 p, %98, 0;\n"
    "wgmma.mma_async.sync.aligned.m64n192k16.f32.bf16.bf16 "
    "{"
    "%0, %1, %2, %3, %4, %5, %6, %7, %8, %9, %10, %11, %12, %13, %14, %15, "
    "%16, %17, %18, %19, %20, %21, %22, %23, %24, %25, %26, %27, %28, %29, %30, %31, "
    "%32, %33, %34, %35, %36, %37, %38, %39, %40, %41, %42, %43, %44, %45, %46, %47, "
    "%48, %49, %50, %51, %52, %53, %54, %55, %56, %57, %58, %59, %60, %61, %62, %63, "
    "%64, %65, %66, %67, %68, %69, %70, %71, %72, %73, %74, %75, %76, %77, %78, %79, "
    "%80, %81, %82, %83, %84, %85, %86, %87, %88, %89, %90, %91, %92, %93, %94, %95"
    "}, "
    "%96, %97, p, 1, 1, 0, 1;\n}\n"
    : "+f"(d[0]), "+f"(d[1]), "+f"(d[2]), "+f"(d[3]), "+f"(d[4]), "+f"(d[5]), "+f"(d[6]), "+f"(d[7]),
      "+f"(d[8]), "+f"(d[9]), "+f"(d[10]), "+f"(d[11]), "+f"(d[12]), "+f"(d[13]), "+f"(d[14]), "+f"(d[15]),
      "+f"(d[16]), "+f"(d[17]), "+f"(d[18]), "+f"(d[19]), "+f"(d[20]), "+f"(d[21]), "+f"(d[22]), "+f"(d[23]),
      "+f"(d[24]), "+f"(d[25]), "+f"(d[26]), "+f"(d[27]), "+f"(d[28]), "+f"(d[29]), "+f"(d[30]), "+f"(d[31]),
      "+f"(d[32]), "+f"(d[33]), "+f"(d[34]), "+f"(d[35]), "+f"(d[36]), "+f"(d[37]), "+f"(d[38]), "+f"(d[39]),
      "+f"(d[40]), "+f"(d[41]), "+f"(d[42]), "+f"(d[43]), "+f"(d[44]), "+f"(d[45]), "+f"(d[46]), "+f"(d[47]),
      "+f"(d[48]), "+f"(d[49]), "+f"(d[50]), "+f"(d[51]), "+f"(d[52]), "+f"(d[53]), "+f"(d[54]), "+f"(d[55]),
      "+f"(d[56]), "+f"(d[57]), "+f"(d[58]), "+f"(d[59]), "+f"(d[60]), "+f"(d[61]), "+f"(d[62]), "+f"(d[63]),
      "+f"(d[64]), "+f"(d[65]), "+f"(d[66]), "+f"(d[67]), "+f"(d[68]), "+f"(d[69]), "+f"(d[70]), "+f"(d[71]),
      "+f"(d[72]), "+f"(d[73]), "+f"(d[74]), "+f"(d[75]), "+f"(d[76]), "+f"(d[77]), "+f"(d[78]), "+f"(d[79]),
      "+f"(d[80]), "+f"(d[81]), "+f"(d[82]), "+f"(d[83]), "+f"(d[84]), "+f"(d[85]), "+f"(d[86]), "+f"(d[87]),
      "+f"(d[88]), "+f"(d[89]), "+f"(d[90]), "+f"(d[91]), "+f"(d[92]), "+f"(d[93]), "+f"(d[94]), "+f"(d[95])
    : "l"(da), "l"(db), "r"(scale_d));
}

__device__ __forceinline__ void wgmma_n80(float (&d)[40], uint64_t da, uint64_t db, int scale_d) {
  asm volatile("{\n.reg .pred p;\nsetp.ne.b32 p, %42, 0;\n"
    "wgmma.mma_async.sync.aligned.m64n80k16.f32.bf16.bf16 "
    "{"
    "%0, %1, %2, %3, %4, %5, %6, %7, %8, %9, %10, %11, %12, %13, %14, %15, "
    "%16, %17, %18, %19, %20, %21, %22, %23, %24, %25, %26, %27, %28, %29, %30, %31, "
    "%32, %33, %34, %35, %36, %37, %38, %39"
    "}, "
    "%40, %41, p, 1, 1, 0, 1;\n}\n"
    : "+f"(d[0]), "+f"(d[1]), "+f"(d[2]), "+f"(d[3]), "+f"(d[4]), "+f"(d[5]), "+f"(d[6]), "+f"(d[7]),
      "+f"(d[8]), "+f"(d[9]), "+f"(d[10]), "+f"(d[11]), "+f"(d[12]), "+f"(d[13]), "+f"(d[14]), "+f"(d[15]),
      "+f"(d[16]), "+f"(d[17]), "+f"(d[18]), "+f"(d[19]), "+f"(d[20]), "+f"(d[21]), "+f"(d[22]), "+f"(d[23]),
      "+f"(d[24]), "+f"(d[25]), "+f"(d[26]), "+f"(d[27]), "+f"(d[28]), "+f"(d[29]), "+f"(d[30]), "+f"(d[31]),
      "+f"(d[32]), "+f"(d[33]), "+f"(d[34]), "+f"(d[35]), "+f"(d[36]), "+f"(d[37]), "+f"(d[38]), "+f"(d[39])
    : "l"(da), "l"(db), "r"(scale_d));
}

__device__ __forceinline__ void hmma(float* c, uint32_t a0, uint32_t a1, uint32_t a2, uint32_t a3, uint32_t b0, uint32_t b1) {
  asm volatile("mma.sync.aligned.m16n8k16.row.col.f32.f16.f16.f32 {%0,%1,%2,%3}, {%4,%5,%6,%7}, {%8,%9}, {%0,%1,%2,%3};"
      : "+f"(c[0]), "+f"(c[1]), "+f"(c[2]), "+f"(c[3]) : "r"(a0), "r"(a1), "r"(a2), "r"(a3), "r"(b0), "r"(b1));
}
__device__ __forceinline__ void ldsm4(uint32_t* r, uint32_t a) { asm volatile("ldmatrix.sync.aligned.m8n8.x4.shared.b16 {%0,%1,%2,%3}, [%4];" : "=r"(r[0]), "=r"(r[1]), "=r"(r[2]), "=r"(r[3]) : "r"(a) : "memory"); }
__device__ __forceinline__ void ldsm4t(uint32_t* r, uint32_t a) { asm volatile("ldmatrix.sync.aligned.m8n8.x4.trans.shared.b16 {%0,%1,%2,%3}, [%4];" : "=r"(r[0]), "=r"(r[1]), "=r"(r[2]), "=r"(r[3]) : "r"(a) : "memory"); }
__device__ __forceinline__ void stsm4(uint32_t a, uint32_t r0, uint32_t r1, uint32_t r2, uint32_t r3) { asm volatile("stmatrix.sync.aligned.m8n8.x4.shared.b16 [%0], {%1,%2,%3,%4};" ::"r"(a), "r"(r0), "r"(r1), "r"(r2), "r"(r3) : "memory"); }
__device__ __forceinline__ void stsm4t(uint32_t a, uint32_t r0, uint32_t r1, uint32_t r2, uint32_t r3) { asm volatile("stmatrix.sync.aligned.m8n8.x4.trans.shared.b16 [%0], {%1,%2,%3,%4};" ::"r"(a), "r"(r0), "r"(r1), "r"(r2), "r"(r3) : "memory"); }
__device__ __forceinline__ uint32_t lds32(uint32_t a) { uint32_t v; asm volatile("ld.shared.u32 %0, [%1];" : "=r"(v) : "r"(a) : "memory"); return v; }
__device__ __forceinline__ uint2 lds64(uint32_t a) { uint2 v; asm volatile("ld.shared.v2.u32 {%0,%1}, [%2];" : "=r"(v.x), "=r"(v.y) : "r"(a) : "memory"); return v; }
__device__ __forceinline__ uint4 lds128(uint32_t a) { uint4 v; asm volatile("ld.shared.v4.u32 {%0,%1,%2,%3}, [%4];" : "=r"(v.x), "=r"(v.y), "=r"(v.z), "=r"(v.w) : "r"(a) : "memory"); return v; }
__device__ __forceinline__ void sts16(uint32_t a, uint32_t v) { asm volatile("st.shared.u16 [%0], %1;" ::"r"(a), "h"((unsigned short)v) : "memory"); }
__device__ __forceinline__ void sts32(uint32_t a, uint32_t v) { asm volatile("st.shared.u32 [%0], %1;" ::"r"(a), "r"(v) : "memory"); }
__device__ __forceinline__ void sts64(uint32_t a, uint32_t x, uint32_t y) { asm volatile("st.shared.v2.u32 [%0], {%1,%2};" ::"r"(a), "r"(x), "r"(y) : "memory"); }
__device__ __forceinline__ void sts128(uint32_t a, uint32_t x, uint32_t y, uint32_t z, uint32_t w) { asm volatile("st.shared.v4.u32 [%0], {%1,%2,%3,%4};" ::"r"(a), "r"(x), "r"(y), "r"(z), "r"(w) : "memory"); }
__device__ __forceinline__ uint32_t ldg32(const void* a) { uint32_t v; asm volatile("ld.global.nc.u32 %0, [%1];" : "=r"(v) : "l"(a)); return v; }
__device__ __forceinline__ uint32_t ldg16(const void* a) { uint32_t v; asm volatile("ld.global.nc.u16 %0, [%1];" : "=r"(v) : "l"(a)); return v; }
__device__ __forceinline__ float bflo(uint32_t v) { return __uint_as_float(v << 16); }
__device__ __forceinline__ float bfhi(uint32_t v) { return __uint_as_float(v & 0xffff0000u); }
__device__ __forceinline__ uint32_t pack_bf(float lo, float hi) { uint32_t r; asm("cvt.rn.bf16x2.f32 %0, %1, %2;" : "=r"(r) : "f"(hi), "f"(lo)); return r; }
__device__ __forceinline__ uint32_t pack_h(float lo, float hi) { uint32_t r; asm("cvt.rn.f16x2.f32 %0, %1, %2;" : "=r"(r) : "f"(hi), "f"(lo)); return r; }
__device__ __forceinline__ float rnd_bf(float v) { return __bfloat162float(__float2bfloat16_rn(v)); }
__device__ __forceinline__ float ex2a(float v) { float r; asm("ex2.approx.ftz.f32 %0, %1;" : "=f"(r) : "f"(v)); return r; }
__device__ __forceinline__ float tanha(float v) { float r; asm("tanh.approx.f32 %0, %1;" : "=f"(r) : "f"(v)); return r; }
__device__ __forceinline__ uint32_t hadd(uint32_t a, uint32_t b) { uint32_t r; asm("add.rn.f16x2 %0, %1, %2;" : "=r"(r) : "r"(a), "r"(b)); return r; }
__device__ __forceinline__ uint32_t badd(uint32_t a, uint32_t b) { uint32_t r; asm("add.rn.bf16x2 %0, %1, %2;" : "=r"(r) : "r"(a), "r"(b)); return r; }
__device__ __forceinline__ uint32_t bmul(uint32_t a, uint32_t b) { uint32_t r; asm("mul.rn.bf16x2 %0, %1, %2;" : "=r"(r) : "r"(a), "r"(b)); return r; }
__device__ __forceinline__ uint32_t bfma(uint32_t a, uint32_t b, uint32_t c) { uint32_t r; asm("fma.rn.bf16x2 %0, %1, %2, %3;" : "=r"(r) : "r"(a), "r"(b), "r"(c)); return r; }
__device__ __forceinline__ float tanhv(float v) { float r; asm volatile("tanh.approx.f32 %0, %1;" : "=f"(r) : "f"(v)); return r; }
__device__ __forceinline__ uint32_t bsub(uint32_t a, uint32_t b) { uint32_t r; asm("sub.rn.bf16x2 %0, %1, %2;" : "=r"(r) : "r"(a), "r"(b)); return r; }
__device__ __forceinline__ uint32_t dup(uint32_t v, uint32_t nz) { uint32_t r; asm volatile("add.rn.f32 %0, %1, %2;" : "=r"(r) : "r"(v), "r"(nz)); return r; }
__device__ __forceinline__ void bmma(float* c, uint32_t a0, uint32_t a1, uint32_t a2, uint32_t a3, uint32_t b0, uint32_t b1) {
  asm("mma.sync.aligned.m16n8k16.row.col.f32.bf16.bf16.f32 {%0,%1,%2,%3}, {%4,%5,%6,%7}, {%8,%9}, {%0,%1,%2,%3};"
      : "+f"(c[0]), "+f"(c[1]), "+f"(c[2]), "+f"(c[3]) : "r"(a0), "r"(a1), "r"(a2), "r"(a3), "r"(b0), "r"(b1));
}
__device__ __forceinline__ uint32_t odd_pair(uint32_t a, uint32_t b) { return __byte_perm(a, b, 0x5432); }
__device__ __forceinline__ int upos(int c) { return c ^ ((c >> 5) & 7) ^ ((c >> 3) & 1); }
__device__ __forceinline__ int uoff(int pos) { return (pos >> 1) * 160 + (pos & 1) * 16; }

struct cf { float r, i; };
__device__ __forceinline__ cf cmul(cf a, cf b) { cf o; o.r = fmaf(a.r, b.r, -a.i * b.i); o.i = fmaf(a.r, b.i, a.i * b.r); return o; }
__device__ __forceinline__ cf cmulj(cf a, cf b) { cf o; o.r = fmaf(a.r, b.r, a.i * b.i); o.i = fmaf(a.i, b.r, -a.r * b.i); return o; }
__device__ __forceinline__ cf csq(cf a) { cf o; o.r = fmaf(a.r, a.r, -a.i * a.i); o.i = (a.r + a.r) * a.i; return o; }
struct hp { uint32_t r, i; };
__device__ __forceinline__ hp hpack(cf a, cf b) { hp o; o.r = pack_h(a.r, b.r); o.i = pack_h(a.i, b.i); return o; }
__device__ __forceinline__ hp hmulc(hp a, uint32_t c) {
  __half2 ar = *reinterpret_cast<__half2*>(&a.r), ai = *reinterpret_cast<__half2*>(&a.i), cc = *reinterpret_cast<__half2*>(&c);
  __half2 orr = __hfma2(ar, __low2half2(cc), __hneg2(__hmul2(ai, __high2half2(cc))));
  __half2 oi = __hfma2(ar, __high2half2(cc), __hmul2(ai, __low2half2(cc)));
  hp o; o.r = *reinterpret_cast<uint32_t*>(&orr); o.i = *reinterpret_cast<uint32_t*>(&oi); return o;
}
__device__ __forceinline__ hp hmulj(hp a, uint32_t c) {
  __half2 ar = *reinterpret_cast<__half2*>(&a.r), ai = *reinterpret_cast<__half2*>(&a.i), cc = *reinterpret_cast<__half2*>(&c);
  __half2 orr = __hfma2(ar, __low2half2(cc), __hmul2(ai, __high2half2(cc)));
  __half2 oi = __hfma2(ai, __low2half2(cc), __hneg2(__hmul2(ar, __high2half2(cc))));
  hp o; o.r = *reinterpret_cast<uint32_t*>(&orr); o.i = *reinterpret_cast<uint32_t*>(&oi); return o;
}
__device__ __forceinline__ void sts_tile(uint32_t a, const hp* t) {
  sts128(a, t[0].r, t[1].r, t[2].r, t[3].r);
  sts128(a + 512, t[0].i, t[1].i, t[2].i, t[3].i);
}
template <int STEP> __device__ __forceinline__ void put2(uint32_t a0, uint32_t a1, uint32_t h, uint32_t sel) {
  const uint32_t x = __byte_perm(h, h, sel), y = x >> 16;
  sts16(a0, x); sts16(a0 + STEP * 4 + 2, x);
  sts16(a1, y); sts16(a1 + STEP * 4 + 2, y);
}

__device__ __forceinline__ void spare_work(const Params& p, const CUtensorMap* tmW1, int k, int tid) {
  const int lane = tid & 31;
  unsigned ep = 0;
  if (tid >= 480) ep = p.scr->epoch[128 + k] + 1;
  if (tid == 480) {
    for (int i = 0; i < 8; i++) mbar_init(bar + 8 * i, i < 4 ? 1 : 12);
    asm volatile("fence.mbarrier_init.release.cluster;" ::: "memory");
    fence_async_smem();
  }
  __syncthreads();
  float a[2][4] = {{0.f, 0.f, 0.f, 0.f}, {0.f, 0.f, 0.f, 0.f}};
  if (tid >= 480) {
    if (elect1()) {
      if (SPARE_NS) __nanosleep(SPARE_NS);
#pragma unroll 1
      for (int s = 0; s < 10; s++) {
        mbar_wait(bar + 8 * (4 + (s & 3)), ((s >> 2) & 1) ^ 1);
        mbar_expect(bar + 8 * (s & 3), 49152);
#pragma unroll 1
        for (int b = 0; b < 2; b++) tma3d(sb + (s & 3) * 49152 + b * 24576, tmW1, 0, s * 64, k * 6 + b * 3, bar + 8 * (s & 3));
      }
    }
    __syncwarp();
  } else if (tid < 384) {
    const uint32_t idn = (lane >> 3) == (lane & 3) ? ((lane & 4) ? 0x3f800000u : 0x3f80u) : 0u;
#pragma unroll 1
    for (int s = 0; s < 10; s++) {
      mbar_wait(bar + 8 * (s & 3), (s >> 2) & 1);
      const uint32_t ad = sb + (s & 3) * 49152 + (tid >> 6) * 8192 + (tid & 63) * 16;
#pragma unroll
      for (int i = 0; i < 8; i += 2) {
        const uint4 v = lds128(ad + i * 1024), w = lds128(ad + i * 1024 + 1024);
        bmma(a[0], v.x, v.y, w.x, w.y, idn, idn);
        bmma(a[1], v.z, v.w, w.z, w.w, idn, idn);
      }
      __syncwarp();
      if (lane == 0) mbar_arrive(bar + 8 * (4 + (s & 3)));
    }
    const int rho = (tid >> 3) & 7;
    const uint32_t ad = sb + 196608 + rho * 1536 + ((tid >> 6) * 8 + ((tid & 7) ^ rho)) * 32;
    sts128(ad, __float_as_uint(a[0][0]), __float_as_uint(a[0][1]), __float_as_uint(a[0][2]), __float_as_uint(a[0][3]));
    sts128(ad + 16, __float_as_uint(a[1][0]), __float_as_uint(a[1][1]), __float_as_uint(a[1][2]), __float_as_uint(a[1][3]));
  }
  __syncthreads();
  if (tid < 384) {
    float s = 0.f;
#pragma unroll
    for (int r = 0; r < 8; r++) s += __uint_as_float(lds32(sb + 196608 + r * 1536 + tid * 4));
    p.scr->cs[k * 384 + tid] = s;
  }
  __syncthreads();
  if (tid == 480) {
    publish(p.scr->cnt + C_CS * 32);
    p.scr->epoch[128 + k] = ep;
    poll_cnt(p.scr->cnt + C_LN * 32, ep * 128);
  }
}

__device__ __forceinline__ void load1(int s, const CUtensorMap* tmX, const CUtensorMap* tmW1, int rg1, int j1) {
  const uint32_t d = sb + (s & 3) * SLOT1, mb = bar + 8 * (B_FULL1 + s);
  mbar_expect(mb, SLOT1);
  tma2d(d, tmX, s * 64, rg1 * 128, mb);
  tma3d(d + 16384, tmW1, 0, s * 64, j1 * 3, mb);
}
__device__ __forceinline__ void load_x(uint32_t (&xv)[2][10], const __nv_bfloat16* xc, int rstep, int q) {
#pragma unroll
  for (int r = 0; r < 2; r++) {
    const uint4 a = __ldg((const uint4*)(xc + r * rstep) + q), b = __ldg((const uint4*)(xc + r * rstep) + 4 + q);
    const uint2 c = __ldg((const uint2*)(xc + r * rstep + 64) + q);
    xv[r][0] = a.x; xv[r][1] = a.y; xv[r][2] = a.z; xv[r][3] = a.w; xv[r][4] = b.x; xv[r][5] = b.y; xv[r][6] = b.z; xv[r][7] = b.w;
    xv[r][8] = c.x; xv[r][9] = c.y;
  }
}

__device__ __forceinline__ uint32_t pin(uint32_t v, uint32_t z) { uint32_t r; asm volatile("add.u32 %0, %1, %2;" : "=r"(r) : "r"(v), "r"(z)); return r; }
struct Comb { uint32_t o[7]; };
__device__ __forceinline__ Comb comb_setup(int tid, uint32_t z) {
  Comb k;
  const int c = tid & 127, c1 = c < 112 ? c + 32 : c - 112, c2 = c < 112 ? c + 144 : c - 96;
  const uint32_t zr = ZA1 + (c & 7) * 16, a2 = ZA2 + ((c & ~15) - 32 + ((((c >> 1) & 7) + (c & 1) * 8) ^ ((c & 1) * 4))) * 16;
  k.o[0] = uoff(upos(c1)); k.o[1] = uoff(upos(c2));
  k.o[2] = c < 112 ? ZA1 + 512 + ((2 * c) ^ ((c >> 2) & 1)) * 16 : zr;
  k.o[3] = c1 >= 64 ? a2 : zr; k.o[4] = c < 112 ? a2 + 112 * 16 : zr;
  k.o[5] = ((c1 >> 4) * 1280 + (c & 15)) * 16; k.o[6] = ((c2 >> 4) * 1280 + (c & 15)) * 16;
#pragma unroll
  for (int i = 0; i < 7; i++) k.o[i] = pin(k.o[i], z);
  return k;
}
template <class F> __device__ __forceinline__ void combine(const Comb& k, int ch, int wid, uint4* sT, F&& after_reads) {
  const uint32_t ub = sb + OFF_U + ch * 32, zb = sb + OFF_Z + ch * ZSZ;
  const int row = (wid & 15) * 5 + ch;
  char* dst = (char*)(sT + ((wid >> 4) * 16 * 80 + row) * 16);
  mbar_wait(bar + 8 * (B_PART + ch), 0);
  const uint32_t sc = lds32(sb + OFF_CHC + ch * 8);
  const uint4 y0 = lds128(zb + k.o[2]), y1 = lds128(zb + (k.o[2] ^ 16));
  const uint4 v2 = lds128(zb + k.o[3]), u2 = lds128(zb + k.o[4]);
  const uint4 v0 = lds128(ub + k.o[0]), u0 = lds128(ub + k.o[1]);
  fence_async_smem();
  after_reads();
  *(uint4*)(dst + (k.o[5] ^ ((row & 7) * 16))) =
      make_uint4(bmul(badd(badd(y0.x, v2.x), v0.x), sc), bmul(badd(badd(y0.y, v2.y), v0.y), sc),
                 bmul(badd(badd(y1.x, v2.z), v0.z), sc), bmul(badd(badd(y1.y, v2.w), v0.w), sc));
  *(uint4*)(dst + (k.o[6] ^ ((row & 7) * 16))) =
      make_uint4(bmul(badd(badd(y0.z, u2.x), u0.x), sc), bmul(badd(badd(y0.w, u2.y), u0.y), sc),
                 bmul(badd(badd(y1.z, u2.z), u0.z), sc), bmul(badd(badd(y1.w, u2.w), u0.w), sc));
  __syncwarp();
  if (elect1()) mbar_arrive(bar + 8 * (B_FREE + ch));
}

__device__ __forceinline__ void load2(int s, uint32_t d, const uint4* srcA, const uint4* srcB) {
  const uint32_t mb = bar + 8 * (B_FULL2 + s);
  mbar_expect(mb, SLOT2);
  bulk_g2s(d, srcA, 16384, mb);
  bulk_g2s(d + 16384, srcB, 10240, mb);
}

template <bool USE_SMID>
__global__ void __launch_bounds__(512, 1)
fused_s4_ffn_kernel(const Params p, const __grid_constant__ CUtensorMap tmX, const __grid_constant__ CUtensorMap tmW1,
                    const __grid_constant__ CUtensorMap tmU, const __grid_constant__ CUtensorMap tmW2) {
  extern __shared__ __align__(1024) unsigned char smem_raw[];
  const int tid = threadIdx.x, lane = tid & 31;
  uint32_t sid;
  if (USE_SMID) asm("mov.u32 %0, %smid;" : "=r"(sid)); else sid = blockIdx.x;
  const int wid = sid < 120 ? sid : sid - 4;
  uint32_t pa[6], pld, pds;
  const unsigned pw = min(tid >> 5, 14), part = (pw * 13) >> 6;
  const unsigned ch = (wid >> 4) * 80 + frag_col(((wid & 15) - part) * 5 + pw);
  const unsigned o = (ch * 3 + part) * 32 + lane;
  {
    pld = ldg16(p.logdt + ch);
    pa[0] = ldg32((const uint32_t*)p.are + o); pa[1] = ldg32((const uint32_t*)p.aim + o);
    pds = ldg16(p.dskip + ch);
    if (!EARLY) {
      pa[2] = ldg32((const uint32_t*)p.bre + o); pa[3] = ldg32((const uint32_t*)p.bim + o);
      pa[4] = ldg32((const uint32_t*)p.cre + o); pa[5] = ldg32((const uint32_t*)p.cim + o);
    } else
    asm volatile("prefetch.global.L2 [%0];\nprefetch.global.L2 [%1];\nprefetch.global.L2 [%2];\nprefetch.global.L2 [%3];"
                 ::"l"((const uint32_t*)p.bre + o), "l"((const uint32_t*)p.bim + o), "l"((const uint32_t*)p.cre + o), "l"((const uint32_t*)p.cim + o));
  }
  const int warp = __shfl_sync(0xffffffffu, tid >> 5, 0);
  const int g = lane >> 2, q = lane & 3;
  if (sid - 120u < 4u) { spare_work(p, &tmW1, sid - 120, tid); return; }
  unsigned* const cnt = p.scr->cnt;

  float kacc[5][4];
  const int kch = warp - 10;
  float dt, k0;
  uint32_t xv[2][10], xs[2], mw;
  {
    unsigned ep0;
    if (warp == 15) {
      ep0 = p.scr->epoch[wid];
      if ((uint32_t)__cvta_generic_to_shared(smem_raw) != sb) __trap();
    }
    if (elect1()) {
      const int gi = (warp + 1) & 15;
#pragma unroll
      for (int i = 0; i < 6; i++) mbar_init(bar + 48 * gi + 8 * i, gi < 7 ? 1 : gi == 7 ? 2 : gi < 10 ? 4 : 8);
      asm volatile("fence.mbarrier_init.release.cluster;" ::: "memory");
    }
    bar_sync(14, 512);
    const __nv_bfloat16* const xr = p.x + (wid * 16 + ((g >> 1) << 2) + (g & 1)) * DM;
    if (warp == 15) {
      sts32(sb + OFF_ZERO + lane * 4, 0);
      int gpc, i;
      if (sid < 64) { gpc = (sid & 15) >> 1; i = sid >> 4; }
      else if (sid < 120) { const int t = sid - 64; i = t / 14; gpc = 1 + ((t - i * 14) >> 1); i += 4; }
      else { gpc = 0; i = 4 + ((sid - 124) >> 1); }
      const int qi = ((0x52741630 >> (4 * i)) & 7) * 2 + (sid & 1);
      const int rg = 4 * (gpc >> 1) + (qi >> 2), jc = 4 * (gpc & 1) + (qi & 3);
      sts64(sb + OFF_EP + 8, rg, jc);
      __syncwarp();
      if (elect1()) {
        asm volatile("prefetch.tensormap [%0];\nprefetch.tensormap [%1];\nprefetch.tensormap [%2];\nprefetch.tensormap [%3];" ::"l"(&tmW2), "l"(&tmX), "l"(&tmW1), "l"(&tmU) : "memory");
        if (DELAY_NS) __nanosleep(DELAY_NS);
        if (XPF) bulk_prefetch(p.x + wid * 16 * DM, 16 * DM * 2);
        mbar_expect(bar + 8 * B_W2, 96 * 176);
      }
      __syncwarp();
      load_x(xv, xr + 7 * 80, 2 * DM, q);
      xs[0] = __ldg((const uint32_t*)xr); xs[1] = __ldg((const uint32_t*)(xr + 2 * DM));
      bar_sync(5, 256);
      if (elect1()) {
        if (DELAY2_NS) __nanosleep(DELAY2_NS);
        tma5d(sb + OFF_W2S, &tmW2, (wid & 7) * 80, (wid >> 3) * 3, bar + 8 * B_W2);
        if (DELAY3_NS) __nanosleep(DELAY3_NS);
        bulk_prefetch(p.w1 + wid * 5 * FF, 5 * FF * 2);
        p.scr->epoch[wid] = ep0 + 1;
        sts32(sb + OFF_EP, ep0 + 1);
      }
      __syncwarp();
    }
#pragma unroll
    for (int j = 0; j < 5; j++) { kacc[j][0] = kacc[j][1] = kacc[j][2] = kacc[j][3] = 0.f; }
    float zr, th, zr1, th1;
    cf c, c1;
    const uint32_t ks = sb + OFF_KS + warp * 4096;
    dt = rnd_bf(expf(bflo(pld)));
    {
      const float dl2 = dt * 1.4426950408889634f;
      zr = bflo(pa[0]) * dl2; th = bflo(pa[1]) * dt; zr1 = bfhi(pa[0]) * dl2; th1 = bfhi(pa[1]) * dt;
    }
    if (EARLY && warp < 15) {
      const unsigned o2 = o + (pld & (sid >> 8));
      pa[2] = ldg32((const uint32_t*)p.bre + o2); pa[3] = ldg32((const uint32_t*)p.bim + o2);
      pa[4] = ldg32((const uint32_t*)p.cre + o2); pa[5] = ldg32((const uint32_t*)p.cim + o2);
    }
    auto csetup = [&] {
      c = cmul(cf{bflo(pa[4]), bflo(pa[5])}, cf{bflo(pa[2]), bflo(pa[3])});
      c1 = cmul(cf{bfhi(pa[4]), bfhi(pa[5])}, cf{bfhi(pa[2]), bfhi(pa[3])});
      mw = __reduce_max_sync(0xffffffffu, __float_as_uint(fmaxf(fmaxf(fabsf(c.r), fabsf(c.i)), fmaxf(fabsf(c1.r), fabsf(c1.i)))));
      mw = min(max(mw & 0x7f800000u, 20u << 23), 240u << 23);
      const float sc = __uint_as_float((259u << 23) - mw);
      k0 = c.r + c1.r;
      c.r *= sc; c.i *= -sc; c1.r *= sc; c1.i *= -sc;
      if (warp >= 8) {
        load_x(xv, xr + (warp - 8) * 80, 2 * DM, q);
        xs[0] = __ldg((const uint32_t*)xr); xs[1] = __ldg((const uint32_t*)(xr + 2 * DM));
        bar_arrive(5, 256);
      }
    };
    if (!EARLY && warp < 15) csetup();
    {
      const uint32_t ka = ks + (lane >> 3) * 512 + (lane & 7) * 16;
      const uint32_t kb = ks + ((lane >> 3) & 1) * 512 + ((lane >> 4) * 8 + (lane & 7)) * 16;
#pragma unroll 1
      for (int it = 0; it < 2; it++) {
        if (it == 1 && warp >= 8) {
          float sm[4] = {0.f, 0.f, 0.f, 0.f}, g0[4] = {0.f, 0.f, 0.f, 0.f}, g1[4] = {0.f, 0.f, 0.f, 0.f};
#pragma unroll
          for (int r = 0; r < 2; r++)
            xs[r] = fabsf(bflo(xs[r]) - bfhi(xs[r])) * 8.f < fabsf(bflo(xs[r])) ? __byte_perm(xs[r], 0, 0x1010) : 0u;
#pragma unroll
          for (int i = 0; i < 10; i += 2) {
            const uint32_t a0 = bsub(xv[0][i], xs[0]), a1 = bsub(xv[1][i], xs[1]), a2 = bsub(xv[0][i + 1], xs[0]), a3 = bsub(xv[1][i + 1], xs[1]);
            bmma(sm, a0, a1, a2, a3, 0x3f803f80u, 0x3f803f80u);
            bmma(g0, a0, a1, a2, a3, xv[0][i], xv[0][i + 1]);
            bmma(g1, a0, a1, a2, a3, xv[1][i], xv[1][i + 1]);
          }
          if (q == (g >> 1))
            sts128(sb + OFF_LNP + (warp - 8) * 128 + g * 16, __float_as_uint(sm[0]), __float_as_uint((g & 1) ? g0[1] : g0[0]),
                   __float_as_uint(sm[2]), __float_as_uint((g & 1) ? g1[3] : g1[2]));
          if (warp == 15) sts64(sb + OFF_MISC + 256 + g * 8, xs[0], xs[1]);
          bar_arrive(1, 288);
        }
        if (warp == 15) continue;
        float m = ex2a(zr);
        const cf w1 = cf{m * __cosf(th), m * __sinf(th)};
        m = ex2a(zr * 8.f);
        const cf w8 = cf{m * __cosf(th * 8.f), m * __sinf(th * 8.f)};
        const cf w16 = csq(w8), w32 = csq(w16), w64 = csq(w32), w128 = csq(w64), w256 = csq(w128), w512 = csq(w256), w1024 = csq(w512);
        hp lo[8];
        lo[0] = hpack(cf{1.f, 0.f}, w8);
        lo[1] = hmulc(lo[0], pack_h(w16.r, w16.i));
        { const uint32_t k = pack_h(w32.r, w32.i); lo[2] = hmulc(lo[0], k); lo[3] = hmulc(lo[1], k); }
        { const uint32_t k = pack_h(w64.r, w64.i);
#pragma unroll
          for (int i = 0; i < 4; i++) lo[4 + i] = hmulc(lo[i], k); }
        const uint32_t st = ks + lane * 16;
        sts128(st + 512, lo[4].r, lo[5].r, lo[6].r, lo[7].r);
        sts128(st + 1536, lo[4].i, lo[5].i, lo[6].i, lo[7].i);
        sts128(st, lo[0].r, lo[1].r, lo[2].r, lo[3].r);
        sts128(st + 1024, lo[0].i, lo[1].i, lo[2].i, lo[3].i);
        const uint32_t k128 = pack_h(w128.r, w128.i), k256 = pack_h(w256.r, w256.i), k512 = pack_h(w512.r, w512.i);
        if (EARLY && it == 0) csetup();
        const cf t8 = cmulj(c, w8);
        hp T0[4], T1[4], T2[4], T3[4], T4[4];
        { const cf u0 = cmulj(t8, w1024), u1 = cmulj(u0, w128);
          T4[0] = hpack(u0, u1); T4[1] = hmulj(T4[0], k256); T4[2] = hmulj(T4[0], k512); T4[3] = hmulj(T4[1], k512); }
        sts_tile(st + 2048, T4);
        __syncwarp();
        uint32_t af[4][4];
#pragma unroll
        for (int mg = 0; mg < 4; mg++) ldsm4t(af[mg], ka + mg * 128);
#pragma unroll
        for (int mg = 0; mg < 4; mg += 2) {
          uint32_t b[4];
          ldsm4t(b, kb + 2048 + mg * 128);
          hmma(kacc[4], af[mg][0], af[mg][1], af[mg][2], af[mg][3], b[0], b[1]);
          hmma(kacc[4], af[mg + 1][0], af[mg + 1][1], af[mg + 1][2], af[mg + 1][3], b[2], b[3]);
        }
        const cf t1 = cmulj(c, w1), t2 = cmulj(t1, w1), t3 = cmulj(t2, w1), t4 = cmulj(t3, w1);
        const cf t5 = cmulj(t4, w1), t6 = cmulj(t5, w1), t7 = cmulj(t6, w1);
        T0[0] = hpack(t4, t8); T0[1] = hpack(t2, t6); T0[2] = hpack(t1, t5); T0[3] = hpack(t3, t7);
#pragma unroll
        for (int i = 0; i < 4; i++) T1[i] = hmulj(T0[i], k128);
        T2[0] = hmulj(T0[0], k256); T2[1] = hmulj(T0[1], k256); T2[2] = hmulj(T1[0], k256); T2[3] = hmulj(T1[1], k256);
        T3[0] = hmulj(T0[0], k512); T3[1] = hmulj(T1[0], k512); T3[2] = hmulj(T2[0], k512); T3[3] = hmulj(T2[2], k512);
        __syncwarp();
        sts_tile(st + 3072, T3);
        sts_tile(st + 2048, T2);
        sts_tile(st + 1024, T1);
        sts_tile(st, T0);
        __syncwarp();
#pragma unroll
        for (int mg = 0; mg < 4; mg += 2)
#pragma unroll
          for (int j = 3; j >= 0; j--) {
            uint32_t b[4];
            ldsm4t(b, kb + j * 1024 + mg * 128);
            hmma(kacc[j], af[mg][0], af[mg][1], af[mg][2], af[mg][3], b[0], b[1]);
            hmma(kacc[j], af[mg + 1][0], af[mg + 1][1], af[mg + 1][2], af[mg + 1][3], b[2], b[3]);
          }
        __syncwarp();
        zr = zr1; th = th1; c = c1;
      }
    }
    if (warp < 10) {
#pragma unroll
      for (int j = 0; j < 5; j++)
        sts128(ks + j * 512 + lane * 16, __float_as_uint(kacc[j][0]), __float_as_uint(kacc[j][1]), __float_as_uint(kacc[j][2]), __float_as_uint(kacc[j][3]));
      sts64(ks + 2560 + lane * 8, __float_as_uint(k0), mw);
    }
    if (warp == 3) {
      bar_sync(1, 288);
      float s1 = 0.f, s2 = 0.f;
#pragma unroll
      for (int w = 0; w < 8; w++) {
        const uint2 v = lds64(sb + OFF_LNP + w * 128 + g * 16 + (q & 1) * 8);
        s1 += __uint_as_float(v.x); s2 += __uint_as_float(v.y);
      }
      const float md = s1 * (1.f / DM), mean = bflo(lds32(sb + OFF_MISC + 256 + g * 8 + (q & 1) * 4)) + md;
      const float var = fmaxf(fmaf(-md, mean, s2 * (1.f / DM)), 0.f);
      const float m = rnd_bf(mean);
      float sd, ri;
      asm("sqrt.approx.f32 %0, %1;" : "=f"(sd) : "f"(rnd_bf(rnd_bf(var) + 1e-5f)));
      asm("rcp.approx.f32 %0, %1;" : "=f"(ri) : "f"(rnd_bf(sd)));
      if (q < 2) {
        p.scr->stats[wid * 16 + ((g >> 1) << 2) + (g & 1) + 2 * q] = make_float2(-m, 0.5f * ri);
        sts64(sb + OFF_STAT + g * 16 + q * 8, __float_as_uint(-m * ri), __float_as_uint(ri));
      }
      __syncwarp();
    }
    if (warp == 15) {
      const uint2 rj = lds64(sb + OFF_EP + 8);
      mbar_wait(bar + 8 * B_W2, 0);
#pragma unroll 1
      for (int uu = 0; uu < 3; uu++) {
        if (elect1()) load1(uu, &tmX, &tmW1, rj.x, rj.y);
        const uint32_t a = sb + OFF_W2S + (uu * 32 + lane) * 176;
        const int rem = ((wid >> 3) & 1) * 3 + uu;
        uint4* dst = p.scr->w2p + ((wid & 7) * 24 + 8 * (rem >> 1) + (wid >> 4)) * 640 + ((rem & 1) * 4 + (lane >> 3)) * 80 + (lane & 7);
        uint4 v[10];
#pragma unroll
        for (int i = 0; i < 10; i++) v[i] = lds128(a + i * 16);
#pragma unroll
        for (int i = 0; i < 8; i++)
          dst[8 * i] = make_uint4(bmul((&v[i & 4].x)[i & 3], 0x3f003f00u), bmul((&v[(i & 4) + 1].x)[i & 3], 0x3f003f00u),
                                  bmul((&v[(i & 4) + 2].x)[i & 3], 0x3f003f00u), bmul((&v[(i & 4) + 3].x)[i & 3], 0x3f003f00u));
        dst[64] = make_uint4(bmul(v[8].x, 0x3f003f00u), bmul(v[8].z, 0x3f003f00u), bmul(v[9].x, 0x3f003f00u), bmul(v[9].z, 0x3f003f00u));
        dst[72] = make_uint4(bmul(v[8].y, 0x3f003f00u), bmul(v[8].w, 0x3f003f00u), bmul(v[9].y, 0x3f003f00u), bmul(v[9].w, 0x3f003f00u));
      }
      fence_async_smem();
      __syncwarp();
      if (elect1()) load1(3, &tmX, &tmW1, rj.x, rj.y);
      __syncwarp();
    }
  }

  if (warp < 8) {
    float acc[96];
    const uint32_t alo = ((sb >> 4) | (1 << 16)) + (warp >> 2) * 512;
    bar_sync(0, 512);
#pragma unroll 1
    for (int s = 0; s < 10; s++) {
      const uint32_t so = (s & 3) * (SLOT1 >> 4);
      mbar_wait(bar + 8 * (B_FULL1 + s), 0);
      wg_fence();
#pragma unroll
      for (int kk = 0; kk < 4; kk++)
        wgmma_n192(acc, dsc(alo + so + kk * 2, 0x40000040u), dsc((((sb + 16384) >> 4) | (512 << 16)) + so + kk * 128, 0x40000040u), (s | kk) != 0);
      wg_commit();
      wg_wait<1>();
      if (lane == 0) mbar_arrive(bar + 8 * (B_REL1 + s));
    }
    wg_wait<0>();
    bar_arrive(14, 384);
    bar_arrive(7, 384);
    mbar_wait(bar + 8 * B_EPI, 0);
    const uint2 s0 = lds64(sb + OFF_STAT + (warp * 16 + g) * 8), s1 = lds64(sb + OFF_STAT + (warp * 16 + g + 8) * 8);
    const float nm0 = __uint_as_float(s0.x), r0 = __uint_as_float(s0.y), nm1 = __uint_as_float(s1.x), r1 = __uint_as_float(s1.y);
    const uint4 erj = lds128(sb + OFF_EP);
    const unsigned ep = erj.x;
    const int rg1 = erj.z, j1 = erj.w;
    uint4* hd = p.scr->h + (rg1 * 24 + j1) * 1024 + warp * 128 + q * 8 + g;
#pragma unroll
    for (int grp = 0; grp < 6; grp++) {
      uint32_t o0[4], o1[4];
#pragma unroll
      for (int tl = 0; tl < 4; tl++) {
        const int nt = grp * 4 + tl;
        const uint2 cs = lds64(sb + OFF_CS + (nt * 8 + 2 * q) * 4);
        const float ca = __uint_as_float(cs.x), cb = __uint_as_float(cs.y);
        const float a = fmaf(nm0, ca, acc[4 * nt]) * r0, b = fmaf(nm0, cb, acc[4 * nt + 1]) * r0;
        const float c = fmaf(nm1, ca, acc[4 * nt + 2]) * r1, d = fmaf(nm1, cb, acc[4 * nt + 3]) * r1;
        o0[tl] = pack_bf(fmaf(a, tanha(a), a), fmaf(b, tanha(b), b));
        o1[tl] = pack_bf(fmaf(c, tanha(c), c), fmaf(d, tanha(d), d));
      }
      uint4* dst = hd + (grp >> 1) * 8192 + (grp & 1) * 32;
      dst[0] = make_uint4(o0[0], o0[1], o0[2], o0[3]);
      dst[64] = make_uint4(o1[0], o1[1], o1[2], o1[3]);
      if (PACE_NS) __nanosleep(PACE_NS);
      if (grp == 1) {
        if (warp == 7) { bar_sync(2, 256); if (lane == 0) publish(cnt + (C_H0 + rg1) * 32); __syncwarp(); }
        else bar_arrive(2, 256);
      }
    }
    if (warp == 6) { bar_sync(11, 256); if (lane == 0) publish(cnt + (C_H1 + rg1) * 32); __syncwarp(); }
    else bar_arrive(11, 256);
    const int go = (rg1 * 128 + warp * 16 + g) * DM + j1 * 80;
    load_x(xv, p.x + go, 8 * DM, q);
    if (warp < 4) {
      const Comb cmb = comb_setup(tid, 0);
#pragma unroll 1
      for (int ch = 0; ch < 3; ch++) {
        combine(cmb, ch, wid, p.scr->sT, [] {});
      }
    } else if (warp == 4) {
      if (elect1()) {
        poll_cnt(cnt + (C_H0 + rg1) * 32, ep * 8);
#pragma unroll 1
        for (int s = 0; s < NS2 - 2; s++) {
          if (s == 4) poll_cnt(cnt + (C_H1 + rg1) * 32, ep * 8);
          if (s == 3) mbar_wait(bar + 8 * B_FREE, 0);
          if (s >= 3) mbar_wait(bar + 8 * (B_FREE + s - 2), 0);
          load2(s, sb + s * SLOT2, p.scr->h + (rg1 * 24 + s) * 1024, p.scr->w2p + (j1 * 24 + s) * 640);
        }
      }
      __syncwarp();
    }
    float acc2[40];
    bar_sync(8, 512);
    {
      const uint32_t al2 = ((sb >> 4) | (8 << 16)) + (warp >> 2) * 512;
      uint32_t so = 0;
#pragma unroll 1
      for (int s = 0; s < 24; s++) {
        mbar_wait(bar + 8 * (B_FULL2 + s), 0);
        wg_fence();
#pragma unroll
        for (int kk = 0; kk < 4; kk++)
          wgmma_n80(acc2, dsc(al2 + so + kk * 16, 64), dsc((((sb + 16384) >> 4) | (80 << 16)) + so + kk * 160, 8), (s | kk) != 0);
        wg_commit();
        so = so == (NS2 - 1) * (SLOT2 >> 4) ? 0 : so + (SLOT2 >> 4);
        wg_wait<1>();
        if (lane == 0) mbar_arrive(bar + 8 * (B_REL2 + s));
      }
    }
    mbar_wait(bar + 8 * B_SFULL, 0);
    uint32_t sv[5][4];
    {
      const int i = lane & 7, mi = lane >> 3;
      const uint32_t a = sb + OFF_U + ((mi >> 1) * 8 + i) * 256 + (((2 * warp + (mi & 1)) ^ i) << 4);
#pragma unroll
      for (int k = 0; k < 5; k++) ldsm4t(sv[k], a + k * 4096);
    }
    wg_wait<0>();
#pragma unroll
    for (int hh = 0; hh < 2; hh++) {
      uint32_t o[10];
      __nv_bfloat16* op = p.out + go + hh * 8 * DM;
#pragma unroll
      for (int tl = 0; tl < 10; tl++) {
        const float a = acc2[4 * tl + 2 * hh], b = acc2[4 * tl + 2 * hh + 1];
        o[tl] = bfma(sv[tl >> 1][(tl & 1) * 2 + hh], pack_bf(fmaf(a, tanhv(a), a), fmaf(b, tanhv(b), b)), xv[hh][tl]);
        if ((tl & 3) == 3)
          asm volatile("st.global.v4.u32 [%0], {%1, %2, %3, %4};" ::"l"((uint4*)op + (tl >> 2) * 4 + q), "r"(o[tl - 3]), "r"(o[tl - 2]), "r"(o[tl - 1]), "r"(o[tl]) : "memory");
      }
      asm volatile("st.global.v2.u32 [%0], {%1, %2};" ::"l"((uint2*)(op + 64) + q), "r"(o[8]), "r"(o[9]) : "memory");
    }
  } else {
    const int cw = warp - 8;
    bar_sync(0, 512);
    const uint4 erj = lds128(sb + OFF_EP);
    const unsigned ep = erj.x;
    const int rg1 = erj.z, j1 = erj.w;
    {
      const uint4 st = lds128(sb + OFF_STAT + g * 16);
      const float n0 = __uint_as_float(st.x), r0 = __uint_as_float(st.y), n1 = __uint_as_float(st.z), r1 = __uint_as_float(st.w);
      const int up = upos(2 * wid);
      uint2* dst = (uint2*)p.scr->uT + ((up >> 1) * DM + cw * 80) * 4 + (lane ^ ((up & 1) << 1));
#pragma unroll
      for (int i = 0; i < 10; i++) {
        const uint32_t a = movm(pack_h(fmaf(bflo(xv[0][i]), r0, n0), fmaf(bfhi(xv[0][i]), r0, n0)));
        const uint32_t b = movm(pack_h(fmaf(bflo(xv[1][i]), r1, n1), fmaf(bfhi(xv[1][i]), r1, n1)));
        dst[i * 32] = make_uint2(a, b);
      }
    }
    if (warp == 8) {
      bar_sync(12, 256);
      if (lane == 0) publish(cnt + C_LN * 32);
      __syncwarp();
    } else bar_arrive(12, 256);
    if (warp == 15) {
      if (elect1()) {
#pragma unroll 1
        for (int s = 4; s < 10; s++) {
          mbar_wait(bar + 8 * (B_REL1 + s - 3), 0);
          load1(s, &tmX, &tmW1, rg1, j1);
        }
        poll_cnt(cnt + C_CS * 32, ep * 4);
        bulk_g2s(sb + OFF_CS, p.scr->cs + j1 * 192, 768, bar + 8 * B_EPI);
      }
      __syncwarp();
    }
    if (warp >= 10 && warp < 15) {
      const uint32_t pb = sb + OFF_P + kch * 3072, pk = sb + OFF_KS + kch * 4096;
      const uint2 e0 = lds64(pk + 2560 + lane * 8), e1 = lds64(pk + 5 * 4096 + 2560 + lane * 8);
      const float dsk = bflo(pds);
      uint32_t kex = __float_as_uint(fmaxf(__uint_as_float(max(max(e0.y, e1.y), mw)) * dt, fabsf(dsk) * (1.f / 256.f))) >> 23;
      kex = min(max(kex, 20u), 240u);
      const float s2 = __uint_as_float((258 - kex) << 23), sd = s2 * dt * (1.f / 32.f);
      const float f0 = __uint_as_float(e0.y) * sd, f1 = __uint_as_float(e1.y) * sd, f2 = __uint_as_float(mw) * sd;
      k0 += __uint_as_float(e0.x) + __uint_as_float(e1.x);
#pragma unroll
      for (int o = 16; o; o >>= 1) k0 += __shfl_xor_sync(0xffffffffu, k0, o);
      const float k0n = fmaf(k0, dt, dsk) * s2;
      uint32_t h[5][2];
#pragma unroll
      for (int j = 0; j < 5; j++) {
        const uint4 a = lds128(pk + j * 512 + lane * 16), b = lds128(pk + 5 * 4096 + j * 512 + lane * 16);
#pragma unroll
        for (int e = 0; e < 4; e++) kacc[j][e] = fmaf(__uint_as_float((&a.x)[e]), f0, fmaf(__uint_as_float((&b.x)[e]), f1, kacc[j][e] * f2));
        if (j == 1) {
          const float k256 = __shfl_sync(0xffffffffu, kacc[1][3], 28);
          if (lane == 31) kacc[1][3] -= k256;
        }
        if (j == 2 || j == 3) { h[j][0] = pack_h(kacc[j][0], kacc[j][2]); h[j][1] = pack_h(kacc[j][1], kacc[j][3]); }
        else { h[j][0] = pack_h(kacc[j][0], kacc[j][1]); h[j][1] = pack_h(kacc[j][2], kacc[j][3]); }
      }
      fence_async_smem();
      bar_arrive(13, 192);
#pragma unroll
      for (int i = 0; i < 6; i++) sts128(pb + i * 512 + lane * 16, 0, 0, 0, 0);
      __syncwarp();
      {
        const int sw = g >> 2;
        const uint32_t sel = sw ? 0x1032 : 0x3210;
        const uint32_t a = pb + (P0 + 8 * g + ((0x3124 >> (4 * q)) & 7)) * 4, a0 = a + sw * 16, a1 = a + 16 - sw * 16;
        put2<1>(a0, a1, h[0][0], sel);
        put2<1>(a0 + 256, a1 + 256, h[0][1], sel);
        put2<1>(a0 + 512, a1 + 512, h[1][0], sel);
        put2<1>(lane == 28 ? pb + PB1 * 4 : a0 + 768, a1 + 768, h[1][1], sel);
      }
      {
        const int sw = q >> 1;
        const uint32_t sel = sw ? 0x1032 : 0x3210;
        uint32_t a = pb + (((q & 1) ? PA1 : PB1 + 1) + 32 * sw + 2 * g) * 4;
        put2<1>(a + sw * 64, a + 64 - sw * 64, h[2][0], sel);
        put2<1>(a + 4 + sw * 64, a + 68 - sw * 64, h[2][1], sel);
        a = pb + (PA2 + g + 16 * q) * 4;
        put2<2>(a + sw * 32, a + 32 - sw * 32, h[3][0], sel);
        put2<2>(a + (PB2 - PA2) * 4 + sw * 32, a + (PB2 - PA2) * 4 + 32 - sw * 32, h[3][1], sel);
        a = pb + (((g & 1) ? PB3 : PA3) + (g >> 1) + 16 * q) * 4;
        const uint32_t hx = sw ? h[4][1] : h[4][0], hy = sw ? h[4][0] : h[4][1];
        put2<1>(a + sw * 16, a + 32 + sw * 16, hx, 0x3210);
        put2<1>(a + 16 - sw * 16, a + 48 - sw * 16, hy, 0x3210);
      }
      if (lane == 30) put2<1>(pb + P0 * 4, pb + (PA1 + 64) * 4, pack_h(k0n, kacc[2][3]), 0x3210);
      if (lane == 31) sts64(sb + OFF_CHC + kch * 8, (kex - 4) * 0x00800080u, __byte_perm(h[3][1], 0, 0x3232));
    }
    if (warp == 8) {
      bar_sync(13, 192);
      if (elect1()) {
        mbar_expect(bar + 8 * B_UFULL, 144 * 160);
        mbar_expect(bar + 8 * B_EPI, 1024 + 768);
        poll_cnt(cnt + C_LN * 32, ep * 128);
        tma2d(sb + OFF_U - 16 * 160, &tmU, wid * 80, -16, bar + 8 * B_UFULL);
        bulk_g2s(sb + OFF_STAT, p.scr->stats + rg1 * 128, 1024, bar + 8 * B_EPI);
      }
      __syncwarp();
    }
    const int wg = warp >> 2, role = (warp + 2 * wg) & 3;
    uint32_t co[6], cpa = (g - 2 * q) * 4;
    if (role < 2) {
#pragma unroll
      for (int gm = 0; gm < 3; gm++) {
        const int hb = 2 * (lane & 7) + role - 2 + gm, l3 = ((lane >> 3) ^ (hb >> 1)) & 7;
        co[2 * gm] = hb * 1280 + uoff(l3); co[2 * gm + 1] = hb * 1280 + uoff(l3 ^ 4);
      }
    } else {
      const int mi = lane >> 3, hf = (lane >> 2) & 1;
      co[0] = hf * 1792 + (mi ^ hf) * 64 + ((q ^ (mi >> 1) ^ (hf * 2)) << 4);
      co[1] = co[0] ^ 96;
      co[2] = (lane ^ (role == 2 ? (mi & 1) : ((lane >> 1) & 4))) << 4;
      co[3] = lane * 16;
      co[4] = (g >> 1) == q ? ((g & 1) ? 0xffff0000u : 0xffffu) : 0u;
      co[5] = 2 * cpa;
    }
    const uint32_t zero = lds32(sb + OFF_ZERO), nz = zero | 0x80000000u;
#pragma unroll
    for (int i = 0; i < 6; i++) co[i] = pin(co[i], zero);
    cpa = pin(cpa, zero);
    const Comb cmb = comb_setup(tid, zero);
    if (warp >= 10 && warp < 15) bar_sync(15, 160);
    mbar_wait(bar + 8 * B_UFULL, 0);
#pragma unroll 1
    for (unsigned seq = (cw >> 2) ? 0xb9ac : 0x8; seq; seq >>= 4) {
      const int ch = seq & 7;
      if (ch == 1) bar_arrive(0, 256);
      if (ch < 4) mbar_wait(bar + 8 * (B_REL1 + (ch ? 8 : 7)), 0);
      const int qt = (cw + ch) & 3, j = qt * 32 + lane;
      const uint32_t ub = sb + OFF_U + ch * 32, zb = sb + OFF_Z + ch * ZSZ;
      uint32_t w_[20], o_[20], d_[20], b3_[20];
      uint32_t *w = w_ + 8, *o = o_ + 8, *d = d_ + 8, *b3 = b3_ + 8;
      {
        const uint32_t am = ub + uoff(upos(2 * j - 2)), a0 = ub + uoff(upos(2 * j));
        const uint2 a = lds64(am + 8);
        const uint4 b = lds128(am ^ 16), c = lds128(a0), e = lds128(a0 ^ 16);
        w[8] = lds32(ub + uoff(upos((2 * j + 2) & 255)));
        w[-6] = a.x; w[-5] = a.y; w[-4] = b.x; w[-3] = b.y; w[-2] = b.z; w[-1] = b.w;
        w[0] = c.x; w[1] = c.y; w[2] = c.z; w[3] = c.w; w[4] = e.x; w[5] = e.y; w[6] = e.z; w[7] = e.w;
      }
#pragma unroll
      for (int i = -1; i <= 7; i++) o[i] = odd_pair(w[i], w[i + 1]);
#pragma unroll
      for (int i = 0; i <= 7; i++) { d[i] = hadd(w[i], o[i]); b3[i] = hadd(d[i], o[i - 1]); }
      if (j < 112) {
        const int gr = j >> 1;
        const uint32_t a1 = zb + ZA1 + 512 + (gr ^ ((gr >> 2) & 1)) * 64 + ((gr >> 1) & 3) * 16 + (j & 1) * 8;
#pragma unroll
        for (int pp = 0; pp < 4; pp++) {
          const uint32_t sel = (pp & 1) ? 0x7632 : 0x5410;
          const int k = pp >> 1;
          sts64(a1 ^ (pp * 16), __byte_perm(w[k - 1], w[k + 1], sel), __byte_perm(w[k + 3], w[k + 5], sel));
          sts64((a1 ^ (pp * 16)) + (ZB1 - ZA1), __byte_perm(b3[k], b3[k + 2], sel), __byte_perm(b3[k + 4], b3[k + 6], sel));
        }
      } else {
        const uint32_t a1 = zb + ZA1 + ((lane ^ 7) & 15) * 16;
        sts128(a1, 0, 0, 0, 0); sts128(a1 + 256, 0, 0, 0, 0); sts128(a1 + ZB1 - ZA1, 0, 0, 0, 0);
        sts128(a1 + ZB1 - ZA1 + 256, 0, 0, 0, j == 127 ? w[8] << 16 : 0u);
      }
      if (qt < 3) {
        uint32_t e_[20], b5_[20];
        uint32_t *e = e_ + 8, *b5 = b5_ + 8;
#pragma unroll
        for (int i = -6; i <= -2; i++) o[i] = odd_pair(w[i], w[i + 1]);
#pragma unroll
        for (int i = -6; i <= -1; i++) d[i] = hadd(w[i], o[i]);
#pragma unroll
        for (int i = -5; i <= -1; i++) b3[i] = hadd(d[i], o[i - 1]);
#pragma unroll
        for (int i = -5; i <= 4; i++) e[i] = hadd(d[i - 1], d[i]);
#pragma unroll
        for (int i = -4; i <= 4; i++) b5[i] = hadd(e[i], w[i + 1]);
        const uint32_t a2 = zb + ((j >> 3) * 16 + (j & 7)) * 16;
        sts128(a2 + ZA2, b3[-2], b3[-1], b3[0], b3[1]);
        sts128(a2 + ZA2 + 128, b3[2], b3[3], b3[4], b3[5]);
        sts128(a2 + ZB2, b5[-4], b5[-3], b5[-2], b5[-1]);
        sts128(a2 + ZB2 + 128, b5[0], b5[1], b5[2], b5[3]);
        if (qt < 2) {
          sts128(a2 + ZS, d[-2], d[-1], d[0], d[1]);
          sts128(a2 + ZS + 128, d[2], d[3], d[4], d[5]);
          uint32_t b7[8], b9[8];
#pragma unroll
          for (int i = -4; i <= 3; i++) { b7[i + 4] = hadd(b3[i - 1], e[i + 1]); b9[i + 4] = hadd(e[i - 1], b5[i + 1]); }
          const uint32_t a3 = zb + ((j >> 4) * 32 + (j & 15)) * 16;
          sts128(a3 + ZA3, b7[0], b7[1], b7[2], b7[3]);
          sts128(a3 + ZA3 + 256, b7[4], b7[5], b7[6], b7[7]);
          sts128(a3 + ZB3 + 256, b9[0], b9[1], b9[2], b9[3]);
          if (j < 63) sts128(a3 + ZB3 + ((j & 15) == 15 ? 272 : 16), b9[4], b9[5], b9[6], b9[7]);
          else sts128(zb + ZB3, 0, 0, 0, 0);
        }
      }
    }
    bar_sync(wg == 2 ? 14 : 7, 384);
#pragma unroll 1
    for (int ch = wg - 2; ch < 5; ch += 2) {
      const uint32_t ub = sb + OFF_U + ch * 32, zb = sb + OFF_Z + ch * ZSZ, pb = sb + OFF_P + ch * 3072;
      if (ch == 2) bar_sync(0, 256);
      const uint32_t pa = pb + cpa;
      if (role < 2) {
        float acc[8][4];
#pragma unroll
        for (int r = 0; r < 8; r++) { acc[r][0] = acc[r][1] = acc[r][2] = acc[r][3] = 0.f; }
        float fix = 0.f;
        if (role == 1 && lane == 28) {
          const uint32_t k = lds32(pb + PB1 * 4), u0 = lds32(ub);
          fix = __low2float(*reinterpret_cast<const __half2*>(&k)) * __low2float(*reinterpret_cast<const __half2*>(&u0));
        }
        uint32_t b[12][4], A[17][4];
#pragma unroll
        for (int i = 11; i >= 8; i--) ldsm4(b[i], ub + (co[4 + (i & 1)] ^ (((i >> 1) & 1) * 16)) + ((i >> 1) & 1) * 640);
        A[0][0] = lds32(pa + P0 * 4); A[0][1] = lds32(pa + P0 * 4 + 32); A[0][2] = lds32(sb + OFF_ZERO + 4);
#pragma unroll
        for (int m = 0; m <= 16; m++) {
          if (m < 16) {
            A[m + 1][0] = lds32(pa + P0 * 4 + (2 * m + 2) * 32);
            A[m + 1][1] = m < 15 ? lds32(pa + P0 * 4 + (2 * m + 3) * 32) : lds32(sb + OFF_ZERO + 8);
          }
          if ((m & 1) == 0 && m < 16) {
            const int i = 7 - (m >> 1);
            ldsm4(b[i], ub + (co[2 * (i >> 2) + (i & 1)] ^ (((i >> 1) & 1) * 16)) + ((i >> 1) & 1) * 640);
          }
          if (m == 9 && elect1()) mbar_arrive(bar + 8 * (B_PAIR + ch));
          A[m][3] = dup(A[m][0], nz);
          if (m < 16) A[m + 1][2] = dup(A[m][1], nz);
#pragma unroll
          for (int r = 7; r >= 0; r--) {
            const int f = 16 + r - m;
            hmma(acc[r], A[m][0], A[m][1], A[m][2], A[m][3], b[f >> 1][(f & 1) * 2], b[f >> 1][(f & 1) * 2 + 1]);
          }
        }
        acc[7][2] += fix;
        mbar_wait(bar + 8 * (B_PAIR + ch), 0);
#pragma unroll
        for (int i = 3; i >= 0; i--)
          stsm4t(ub + (co[4 + (i & 1)] ^ (((i >> 1) & 1) * 16)) + ((i >> 1) & 1) * 640, pack_bf(acc[2 * i][0], acc[2 * i][1]), pack_bf(acc[2 * i][2], acc[2 * i][3]),
                 pack_bf(acc[2 * i + 1][0], acc[2 * i + 1][1]), pack_bf(acc[2 * i + 1][2], acc[2 * i + 1][3]));
      } else if (role == 2) {
        float acc[14][4];
#pragma unroll
        for (int r = 0; r < 14; r++) { acc[r][0] = acc[r][1] = acc[r][2] = acc[r][3] = 0.f; }
#pragma unroll
        for (int arr = 0; arr < 2; arr++) {
          uint32_t A[5][4];
#pragma unroll
          for (int m = 0; m < 5; m++) {
            A[m][0] = lds32(pa + (arr ? PB1 : PA1) * 4 + m * 64);
            A[m][1] = m < 4 ? lds32(pa + (arr ? PB1 : PA1) * 4 + m * 64 + 32) : lds32(sb + OFF_ZERO + 4 + arr * 8);
          }
#pragma unroll
          for (int m = 4; m >= 1; m--) { A[m][2] = dup(A[m - 1][1], nz); A[m][3] = dup(A[m][0], nz); }
          A[0][2] = lds32(sb + OFF_ZERO + 8 + arr * 8); A[0][3] = dup(A[0][0], nz);
#pragma unroll
          for (int ip = 0; ip < 9; ip++) {
            uint32_t b[4];
            ldsm4(b, zb + co[ip & 1] + (arr ? ZB1 : ZA1) + ip * 256);
#pragma unroll
            for (int hh = 0; hh < 2; hh++)
#pragma unroll
              for (int m = 0; m < 5; m++) {
                const int i = 2 * ip + hh - 4 + m;
                if (i >= 0 && i < 14) hmma(acc[i], A[m][0], A[m][1], A[m][2], A[m][3], b[2 * hh], b[2 * hh + 1]);
              }
          }
        }
        const uint32_t a = zb + ZA1 + 512 + co[2];
#pragma unroll
        for (int i = 0; i < 7; i++)
          stsm4(a + i * 512, pack_bf(acc[2 * i][0], acc[2 * i][1]), pack_bf(acc[2 * i][2], acc[2 * i][3]),
                pack_bf(acc[2 * i + 1][0], acc[2 * i + 1][1]), pack_bf(acc[2 * i + 1][2], acc[2 * i + 1][3]));
      } else {
        float acc[12][4];
        const uint32_t za = zb + co[3];
        {
          float d[4][2][4];
#pragma unroll
          for (int r = 0; r < 8; r++) { d[r >> 1][r & 1][0] = d[r >> 1][r & 1][1] = d[r >> 1][r & 1][2] = d[r >> 1][r & 1][3] = 0.f; }
#pragma unroll
          for (int arr = 0; arr < 2; arr++) {
            uint32_t A[4][4];
#pragma unroll
            for (int m = 0; m < 4; m++) { A[m][0] = lds32(pa + (arr ? PB3 : PA3) * 4 + m * 64); A[m][1] = lds32(pa + (arr ? PB3 : PA3) * 4 + m * 64 + 32); }
#pragma unroll
            for (int m = 0; m < 4; m++) { A[m][2] = m ? dup(A[m - 1][1], nz) : lds32(sb + OFF_ZERO + 4 + arr * 4); A[m][3] = dup(A[m][0], nz); }
#pragma unroll
            for (int io = 0; io < 4; io++) {
              uint32_t b[4];
              ldsm4t(b, za + (arr ? ZB3 : ZA3) + io * 512);
#pragma unroll
              for (int m = 0; m + io < 4; m++) {
                hmma(d[io + m][0], A[m][0], A[m][1], A[m][2], A[m][3], b[0], b[1]);
                hmma(d[io + m][1], A[m][0], A[m][1], A[m][2], A[m][3], b[2], b[3]);
              }
            }
          }
#pragma unroll
          for (int r = 0; r < 4; r++) {
            acc[r][0] = acc[r][1] = acc[r][2] = acc[r][3] = 0.f;
            acc[4 + 2 * r][0] = d[r][0][0]; acc[4 + 2 * r][1] = d[r][0][1]; acc[4 + 2 * r][2] = d[r][1][0]; acc[4 + 2 * r][3] = d[r][1][1];
            acc[5 + 2 * r][0] = d[r][0][2]; acc[5 + 2 * r][1] = d[r][0][3]; acc[5 + 2 * r][2] = d[r][1][2]; acc[5 + 2 * r][3] = d[r][1][3];
          }
        }
        {
          const uint32_t k0 = lds32(sb + OFF_CHC + ch * 8 + 4) & co[4];
          const uint32_t k1 = lds32(sb + OFF_ZERO + 12), k2 = lds32(sb + OFF_ZERO + 16), k3 = dup(k0, nz);
#pragma unroll
          for (int ip = 0; ip < 4; ip++) {
            uint32_t b[4];
            ldsm4t(b, za + ZS + ip * 512);
            hmma(acc[4 + 2 * ip], k0, k1, k2, k3, b[0], b[1]);
            hmma(acc[5 + 2 * ip], k0, k1, k2, k3, b[2], b[3]);
          }
        }
        const uint32_t pa2 = pb + co[5];
#pragma unroll
        for (int arr = 0; arr < 2; arr++) {
          uint32_t A[5][4];
#pragma unroll
          for (int m = 0; m < 5; m++) {
            const uint2 v = lds64(pa2 + (arr ? PB2 : PA2) * 4 + m * 64);
            A[m][0] = v.x; A[m][1] = v.y; A[m][2] = lds32(pa2 + (arr ? PB2 : PA2) * 4 + m * 64 - 4);
          }
#pragma unroll
          for (int m = 0; m < 5; m++) A[m][3] = dup(A[m][0], nz);
#pragma unroll
          for (int ip = 0; ip < 6; ip++) {
            uint32_t b[4];
            ldsm4t(b, za + (arr ? ZB2 : ZA2) + ip * 512);
#pragma unroll
            for (int hh = 0; hh < 2; hh++)
#pragma unroll
              for (int m = 0; m < 5; m++) {
                const int i = 2 * ip + hh + m;
                if (i < 12) hmma(acc[i], A[m][0], A[m][1], A[m][2], A[m][3], b[2 * hh], b[2 * hh + 1]);
              }
          }
        }
        const uint32_t a = zb + ZA2 + co[2];
#pragma unroll
        for (int i = 0; i < 6; i++)
          stsm4(a + i * 512, pack_bf(acc[2 * i][0], acc[2 * i][1]), pack_bf(acc[2 * i][2], acc[2 * i][3]),
                pack_bf(acc[2 * i + 1][0], acc[2 * i + 1][1]), pack_bf(acc[2 * i + 1][2], acc[2 * i + 1][3]));
      }
      __syncwarp();
      if (elect1()) mbar_arrive(bar + 8 * (B_PART + ch));
    }
    const uint4* srcA = p.scr->h + (rg1 * 24 + NS2 - 2) * 1024;
    const uint4* srcB = p.scr->w2p + (j1 * 24 + NS2 - 2) * 640;
    combine(cmb, 6 - wg, wid, p.scr->sT, [&] {
      if (warp == 12) {
        bar_sync(8, 512);
        if (elect1()) {
          asm volatile("fence.proxy.async.global;" ::: "memory");
          load2(NS2 - 2, sb + (NS2 - 2) * SLOT2, srcA, srcB);
          load2(NS2 - 1, sb + (NS2 - 1) * SLOT2, srcA + 1024, srcB + 640);
        }
        __syncwarp();
      } else bar_arrive(8, 512);
    });
    if (warp == 12) {
      if (elect1()) {
        uint32_t d = sb;
#pragma unroll 1
        for (int s = NS2; s < 24; s++) {
          mbar_wait(bar + 8 * (B_REL2 + s - NS2 + 1), 0);
          load2(s, d, srcA + 2048, srcB + 1280);
          srcA += 1024; srcB += 640;
          d = d == sb + (NS2 - 1) * SLOT2 ? sb : d + SLOT2;
        }
      }
      __syncwarp();
    } else if (warp == 13) {
      if (elect1()) {
#pragma unroll 1
        for (int c = 2; c < 5; c++) mbar_wait(bar + 8 * (B_FREE + c), 0);
        publish(cnt + (C_S + (wid >> 4)) * 32);
        mbar_expect(bar + 8 * B_SFULL, 20480);
        poll_cnt(cnt + (C_S + j1) * 32, ep * 16);
        mbar_wait(bar + 8 * (B_REL2 + 24 - NS2), 0);
        bulk_g2s(sb + OFF_U, p.scr->sT + (j1 * 16 + rg1) * 1280, 20480, bar + 8 * B_SFULL);
      }
      __syncwarp();
    }
  }
}

typedef CUresult (*EncodeFn)(CUtensorMap*, CUtensorMapDataType, cuuint32_t, void*, const cuuint64_t*, const cuuint64_t*,
                             const cuuint32_t*, const cuuint32_t*, CUtensorMapInterleave, CUtensorMapSwizzle,
                             CUtensorMapL2promotion, CUtensorMapFloatOOBfill);

}

extern "C" void kernel_launch(void* const* d_in, const int* in_sizes, int n_in, void* d_out, int out_size) {
  static EncodeFn enc = nullptr;
  static int nsm = 0;
  static void* scr = nullptr;
  if (!enc) {
    void* fn = nullptr;
    cudaDriverEntryPointQueryResult qr;
    cudaGetDriverEntryPoint("cuTensorMapEncodeTiled", &fn, cudaEnableDefault, &qr);
    enc = (EncodeFn)fn;
    int dev = 0;
    cudaGetDevice(&dev);
    cudaDeviceGetAttribute(&nsm, cudaDevAttrMultiProcessorCount, dev);
    cudaFuncSetAttribute(fused_s4_ffn_kernel<true>, cudaFuncAttributeMaxDynamicSharedMemorySize, SMEM_BYTES);
    cudaFuncSetAttribute(fused_s4_ffn_kernel<false>, cudaFuncAttributeMaxDynamicSharedMemorySize, SMEM_BYTES);
    cudaGetSymbolAddress(&scr, g_scr);
  }
  Params p;
  p.x = (const __nv_bfloat16*)d_in[0];
  p.are = (const __nv_bfloat16*)d_in[1]; p.aim = (const __nv_bfloat16*)d_in[2];
  p.bre = (const __nv_bfloat16*)d_in[3]; p.bim = (const __nv_bfloat16*)d_in[4];
  p.cre = (const __nv_bfloat16*)d_in[5]; p.cim = (const __nv_bfloat16*)d_in[6];
  p.logdt = (const __nv_bfloat16*)d_in[7]; p.dskip = (const __nv_bfloat16*)d_in[8];
  p.w1 = (const __nv_bfloat16*)d_in[10]; p.w2 = (const __nv_bfloat16*)d_in[11];
  p.out = (__nv_bfloat16*)d_out;
  p.scr = (Scratch*)scr;
  CUtensorMap tmX, tmW1, tmU, tmW2;
  const cuuint32_t es[5] = {1, 1, 1, 1, 1};
  {
    const cuuint64_t gd[5] = {DM, 2, 4, 4, FF / 32}, gs[4] = {DM * 2, DM * 16, DM * 4, DM * 64};
    const cuuint32_t bx[5] = {88, 2, 4, 4, 3};
    enc(&tmW2, CU_TENSOR_MAP_DATA_TYPE_BFLOAT16, 5, d_in[11], gd, gs, bx, es, CU_TENSOR_MAP_INTERLEAVE_NONE,
        CU_TENSOR_MAP_SWIZZLE_NONE, CU_TENSOR_MAP_L2_PROMOTION_NONE, CU_TENSOR_MAP_FLOAT_OOB_FILL_NONE);
  }
  {
    const cuuint64_t gd[2] = {16 * DM, 128}, gs[1] = {DM * 32};
    const cuuint32_t bx[2] = {80, 144};
    enc(&tmU, CU_TENSOR_MAP_DATA_TYPE_FLOAT16, 2, p.scr->uT, gd, gs, bx, es, CU_TENSOR_MAP_INTERLEAVE_NONE,
        CU_TENSOR_MAP_SWIZZLE_NONE, CU_TENSOR_MAP_L2_PROMOTION_NONE, CU_TENSOR_MAP_FLOAT_OOB_FILL_NONE);
  }
  {
    const cuuint64_t gd[2] = {DM, SEQ}, gs[1] = {DM * 2};
    const cuuint32_t bx[2] = {64, 128};
    enc(&tmX, CU_TENSOR_MAP_DATA_TYPE_BFLOAT16, 2, d_in[0], gd, gs, bx, es, CU_TENSOR_MAP_INTERLEAVE_NONE,
        CU_TENSOR_MAP_SWIZZLE_128B, CU_TENSOR_MAP_L2_PROMOTION_L2_128B, CU_TENSOR_MAP_FLOAT_OOB_FILL_NONE);
  }
  {
    const cuuint64_t gd[3] = {64, DM, FF / 64}, gs[2] = {FF * 2, 128};
    const cuuint32_t bx[3] = {64, 64, 3};
    enc(&tmW1, CU_TENSOR_MAP_DATA_TYPE_BFLOAT16, 3, d_in[10], gd, gs, bx, es, CU_TENSOR_MAP_INTERLEAVE_NONE,
        CU_TENSOR_MAP_SWIZZLE_128B, CU_TENSOR_MAP_L2_PROMOTION_L2_128B, CU_TENSOR_MAP_FLOAT_OOB_FILL_NONE);
  }
  if (nsm == 132) fused_s4_ffn_kernel<true><<<132, 512, SMEM_BYTES>>>(p, tmX, tmW1, tmU, tmW2);
  else fused_s4_ffn_kernel<false><<<132, 512, SMEM_BYTES>>>(p, tmX, tmW1, tmU, tmW2);
}
```

```cpp
#include <cuda_runtime.h>
#include <cuda_bf16.h>
#include <cuda_fp16.h>
#include <cuda.h>
#include <stdint.h>

namespace {

constexpr int SEQ = 2048, DM = 640, FF = 1536;

constexpr int SLOT1 = 40960;
constexpr int SLOT2 = 26624;
constexpr int NS2 = 7;
#define DELAY2_NS 0
#define DELAY3_NS 300
#define DTE 0
#define XPF 1
#define XWAIT 1
#define W1PF 2
#define SKW 1
#define SK2 21
#define CSW 5
#define SW 17
#define STAG 0x2020
#define STAGN 1
#define FINW 11
#define W2H 0
#define LDQ 0
#define SQ 1
#define GATE 0
#define SPARE_NS 300
#define DELAY_NS 100
#define PACE_NS 60
constexpr int OFF_Z = 85504, ZSZ = 20480;
constexpr int ZA3 = 0, ZB3 = 2048, ZS = 4096, ZA2 = 6144, ZB2 = 9216, ZA1 = 12288, ZB1 = 16384;
constexpr int OFF_W2S = 3 * SLOT1;
constexpr int OFF_U = 190464;
constexpr int OFF_P = 210944;
constexpr int OFF_KS = 163840;
constexpr int OFF_LNP = 225280;
constexpr int OFF_MISC = 226304;
constexpr int OFF_CHC = OFF_MISC + 16;
constexpr int OFF_EP = OFF_MISC + 64;
constexpr int OFF_ZERO = OFF_MISC + 128;
constexpr int OFF_STAT = OFF_MISC + 1024;
constexpr int OFF_CS = OFF_MISC + 2048;
constexpr int OFF_BAR = OFF_MISC + 2816;
constexpr int SMEM_BYTES = OFF_MISC + 6144;
constexpr int P0 = 8, PA1 = 280, PB1 = 360, PA2 = 448, PB2 = 544, PA3 = 632, PB3 = 704;
enum { B_FULL1 = 0, B_FULL2 = 10, B_UFULL = 34, B_EPI = 35, B_SFULL = 36, B_W2 = 37,
       B_PAIR = 42,
       B_FREE = 48, B_PART = 54,
       B_REL1 = 60, B_REL2 = 70 };
enum { C_LN = 0, C_CS = 1, C_H0 = 2, C_H1 = 18, C_S = 34, C_W2 = 42, C_NUM = 43 };

struct Scratch {
  unsigned cnt[64 * 32];
  unsigned epoch[256];
  float2 stats[SEQ];
  float cs[FF];
  uint4 uT[DM * 256];
  uint4 w2p[8 * 24 * 640];
  uint4 sT[8 * 16 * 1280];
  uint4 h[16 * 24 * 1024];
};
__device__ __align__(1024) Scratch g_scr;
constexpr uint32_t sb = 1024;
constexpr uint32_t bar = sb + OFF_BAR;

struct Params {
  const __nv_bfloat16 *are, *aim, *bre, *bim, *cre, *cim, *logdt, *dskip, *x, *w1, *w2;
  __nv_bfloat16* out;
  Scratch* scr;
};

__device__ __forceinline__ void mbar_init(uint32_t a, int c) { asm volatile("mbarrier.init.shared::cta.b64 [%0], %1;" ::"r"(a), "r"(c)); }
__device__ __forceinline__ void mbar_expect(uint32_t a, int b) { asm volatile("mbarrier.arrive.expect_tx.shared::cta.b64 _, [%0], %1;" ::"r"(a), "r"(b) : "memory"); }
__device__ __forceinline__ void mbar_arrive(uint32_t a) { asm volatile("mbarrier.arrive.shared::cta.b64 _, [%0];" ::"r"(a) : "memory"); }
__device__ __forceinline__ void mbar_wait(uint32_t a, int ph) {
  asm volatile(
      "{\n.reg .pred p;\n.reg .u32 n;\n"
      "mbarrier.try_wait.parity.shared::cta.b64 p, [%0], %1;\n@p bra LD;\nmov.u32 n, 0;\n"
      "LW:\nmbarrier.try_wait.parity.shared::cta.b64 p, [%0], %1, 20000;\n@p bra LD;\n"
      "add.u32 n, n, 1;\nsetp.lt.u32 p, n, 100000;\n@p bra LW;\ntrap;\nLD:\n}\n" ::"r"(a), "r"(ph) : "memory");
}
__device__ __forceinline__ void poll_cnt(const unsigned* p, unsigned target) {
  asm volatile(
      "{\n.reg .pred p;\n.reg .u32 n;\n.reg .s32 v;\nmov.u32 n, 0;\n"
      "LW:\nld.relaxed.gpu.global.u32 v, [%0];\nsub.s32 v, v, %1;\nsetp.ge.s32 p, v, 0;\n@p bra LD;\n"
      "nanosleep.u32 64;\nadd.u32 n, n, 1;\nsetp.lt.u32 p, n, 4000000;\n@p bra LW;\ntrap;\n"
      "LD:\nfence.acquire.gpu;\nfence.proxy.async.global;\n}\n" ::"l"(p), "r"(target) : "memory");
}
__device__ __forceinline__ void publish(unsigned* p) {
  asm volatile("fence.proxy.async.global;\nfence.release.gpu;\nred.relaxed.gpu.global.add.u32 [%0], 1;" ::"l"(p) : "memory");
}
__device__ __forceinline__ uint32_t movm(uint32_t v) { uint32_t r; asm volatile("movmatrix.sync.aligned.m8n8.trans.b16 %0, %1;" : "=r"(r) : "r"(v)); return r; }
__device__ __forceinline__ void fence_async_smem() { asm volatile("fence.proxy.async.shared::cta;" ::: "memory"); }
__device__ __forceinline__ bool elect1() { uint32_t p; asm volatile("{\n.reg .pred P;\nelect.sync _|P, 0xffffffff;\nselp.u32 %0,1,0,P;\n}\n" : "=r"(p)); return p; }
__device__ __forceinline__ void bar_sync(int id, int n) { asm volatile("bar.sync %0, %1;" ::"r"(id), "r"(n) : "memory"); }
__device__ __forceinline__ void bar_arrive(int id, int n) { asm volatile("bar.arrive %0, %1;" ::"r"(id), "r"(n) : "memory"); }
__device__ __forceinline__ void bulk_g2s(uint32_t dst, const void* src, int bytes, uint32_t mb) {
  asm volatile("cp.async.bulk.shared::cluster.global.mbarrier::complete_tx::bytes [%0], [%1], %2, [%3];" ::"r"(dst), "l"(src), "r"(bytes), "r"(mb) : "memory");
}
__device__ __forceinline__ void bulk_prefetch(const void* src, int bytes) { asm volatile("cp.async.bulk.prefetch.L2.global [%0], %1;" ::"l"(src), "r"(bytes) : "memory"); }
__device__ __forceinline__ void tma2d(uint32_t dst, const CUtensorMap* m, int c0, int c1, uint32_t mb) {
  asm volatile("cp.async.bulk.tensor.2d.shared::cluster.global.mbarrier::complete_tx::bytes [%0], [%1, {%3, %4}], [%2];" ::"r"(dst), "l"(m), "r"(mb), "r"(c0), "r"(c1) : "memory");
}
__device__ __forceinline__ void tma3d(uint32_t dst, const CUtensorMap* m, int c0, int c1, int c2, uint32_t mb) {
  asm volatile("cp.async.bulk.tensor.3d.shared::cluster.global.mbarrier::complete_tx::bytes [%0], [%1, {%3, %4, %5}], [%2];" ::"r"(dst), "l"(m), "r"(mb), "r"(c0), "r"(c1), "r"(c2) : "memory");
}
__device__ __forceinline__ unsigned frag_col(unsigned l) { return (l & 0x61) | ((l & 6) << (2 - (l >> 6))) | ((l >> 2) & 6); }
__device__ __forceinline__ void tma5d(uint32_t dst, const CUtensorMap* m, int c0, int c4, uint32_t mb) {
  asm volatile("cp.async.bulk.tensor.5d.shared::cluster.global.mbarrier::complete_tx::bytes [%0], [%1, {%3, %5, %5, %5, %4}], [%2];" ::"r"(dst), "l"(m), "r"(mb), "r"(c0), "r"(c4), "r"(0) : "memory");
}
__device__ __forceinline__ uint64_t dsc(uint32_t lo, uint32_t hi) { return ((uint64_t)hi << 32) | lo; }
__device__ __forceinline__ void wg_fence() { asm volatile("wgmma.fence.sync.aligned;" ::: "memory"); }
__device__ __forceinline__ void wg_commit() { asm volatile("wgmma.commit_group.sync.aligned;" ::: "memory"); }
template <int N> __device__ __forceinline__ void wg_wait() { asm volatile("wgmma.wait_group.sync.aligned %0;" ::"n"(N) : "memory"); }
__device__ __forceinline__ void wgmma_n192(float (&d)[96], uint64_t da, uint64_t db, int scale_d) {
  asm volatile("{\n.reg .pred p;\nsetp.ne.b32 p, %98, 0;\n"
    "wgmma.mma_async.sync.aligned.m64n192k16.f32.bf16.bf16 "
    "{"
    "%0, %1, %2, %3, %4, %5, %6, %7, %8, %9, %10, %11, %12, %13, %14, %15, "
    "%16, %17, %18, %19, %20, %21, %22, %23, %24, %25, %26, %27, %28, %29, %30, %31, "
    "%32, %33, %34, %35, %36, %37, %38, %39, %40, %41, %42, %43, %44, %45, %46, %47, "
    "%48, %49, %50, %51, %52, %53, %54, %55, %56, %57, %58, %59, %60, %61, %62, %63, "
    "%64, %65, %66, %67, %68, %69, %70, %71, %72, %73, %74, %75, %76, %77, %78, %79, "
    "%80, %81, %82, %83, %84, %85, %86, %87, %88, %89, %90, %91, %92, %93, %94, %95"
    "}, "
    "%96, %97, p, 1, 1, 0, 1;\n}\n"
    : "+f"(d[0]), "+f"(d[1]), "+f"(d[2]), "+f"(d[3]), "+f"(d[4]), "+f"(d[5]), "+f"(d[6]), "+f"(d[7]),
      "+f"(d[8]), "+f"(d[9]), "+f"(d[10]), "+f"(d[11]), "+f"(d[12]), "+f"(d[13]), "+f"(d[14]), "+f"(d[15]),
      "+f"(d[16]), "+f"(d[17]), "+f"(d[18]), "+f"(d[19]), "+f"(d[20]), "+f"(d[21]), "+f"(d[22]), "+f"(d[23]),
      "+f"(d[24]), "+f"(d[25]), "+f"(d[26]), "+f"(d[27]), "+f"(d[28]), "+f"(d[29]), "+f"(d[30]), "+f"(d[31]),
      "+f"(d[32]), "+f"(d[33]), "+f"(d[34]), "+f"(d[35]), "+f"(d[36]), "+f"(d[37]), "+f"(d[38]), "+f"(d[39]),
      "+f"(d[40]), "+f"(d[41]), "+f"(d[42]), "+f"(d[43]), "+f"(d[44]), "+f"(d[45]), "+f"(d[46]), "+f"(d[47]),
      "+f"(d[48]), "+f"(d[49]), "+f"(d[50]), "+f"(d[51]), "+f"(d[52]), "+f"(d[53]), "+f"(d[54]), "+f"(d[55]),
      "+f"(d[56]), "+f"(d[57]), "+f"(d[58]), "+f"(d[59]), "+f"(d[60]), "+f"(d[61]), "+f"(d[62]), "+f"(d[63]),
      "+f"(d[64]), "+f"(d[65]), "+f"(d[66]), "+f"(d[67]), "+f"(d[68]), "+f"(d[69]), "+f"(d[70]), "+f"(d[71]),
      "+f"(d[72]), "+f"(d[73]), "+f"(d[74]), "+f"(d[75]), "+f"(d[76]), "+f"(d[77]), "+f"(d[78]), "+f"(d[79]),
      "+f"(d[80]), "+f"(d[81]), "+f"(d[82]), "+f"(d[83]), "+f"(d[84]), "+f"(d[85]), "+f"(d[86]), "+f"(d[87]),
      "+f"(d[88]), "+f"(d[89]), "+f"(d[90]), "+f"(d[91]), "+f"(d[92]), "+f"(d[93]), "+f"(d[94]), "+f"(d[95])
    : "l"(da), "l"(db), "r"(scale_d));
}

__device__ __forceinline__ void wgmma_n80(float (&d)[40], uint64_t da, uint64_t db, int scale_d) {
  asm volatile("{\n.reg .pred p;\nsetp.ne.b32 p, %42, 0;\n"
    "wgmma.mma_async.sync.aligned.m64n80k16.f32.bf16.bf16 "
    "{"
    "%0, %1, %2, %3, %4, %5, %6, %7, %8, %9, %10, %11, %12, %13, %14, %15, "
    "%16, %17, %18, %19, %20, %21, %22, %23, %24, %25, %26, %27, %28, %29, %30, %31, "
    "%32, %33, %34, %35, %36, %37, %38, %39"
    "}, "
    "%40, %41, p, 1, 1, 0, 1;\n}\n"
    : "+f"(d[0]), "+f"(d[1]), "+f"(d[2]), "+f"(d[3]), "+f"(d[4]), "+f"(d[5]), "+f"(d[6]), "+f"(d[7]),
      "+f"(d[8]), "+f"(d[9]), "+f"(d[10]), "+f"(d[11]), "+f"(d[12]), "+f"(d[13]), "+f"(d[14]), "+f"(d[15]),
      "+f"(d[16]), "+f"(d[17]), "+f"(d[18]), "+f"(d[19]), "+f"(d[20]), "+f"(d[21]), "+f"(d[22]), "+f"(d[23]),
      "+f"(d[24]), "+f"(d[25]), "+f"(d[26]), "+f"(d[27]), "+f"(d[28]), "+f"(d[29]), "+f"(d[30]), "+f"(d[31]),
      "+f"(d[32]), "+f"(d[33]), "+f"(d[34]), "+f"(d[35]), "+f"(d[36]), "+f"(d[37]), "+f"(d[38]), "+f"(d[39])
    : "l"(da), "l"(db), "r"(scale_d));
}

__device__ __forceinline__ void hmma(float* c, uint32_t a0, uint32_t a1, uint32_t a2, uint32_t a3, uint32_t b0, uint32_t b1) {
  asm volatile("mma.sync.aligned.m16n8k16.row.col.f32.f16.f16.f32 {%0,%1,%2,%3}, {%4,%5,%6,%7}, {%8,%9}, {%0,%1,%2,%3};"
      : "+f"(c[0]), "+f"(c[1]), "+f"(c[2]), "+f"(c[3]) : "r"(a0), "r"(a1), "r"(a2), "r"(a3), "r"(b0), "r"(b1));
}
__device__ __forceinline__ void ldsm4(uint32_t* r, uint32_t a) { asm volatile("ldmatrix.sync.aligned.m8n8.x4.shared.b16 {%0,%1,%2,%3}, [%4];" : "=r"(r[0]), "=r"(r[1]), "=r"(r[2]), "=r"(r[3]) : "r"(a) : "memory"); }
__device__ __forceinline__ void ldsm4t(uint32_t* r, uint32_t a) { asm volatile("ldmatrix.sync.aligned.m8n8.x4.trans.shared.b16 {%0,%1,%2,%3}, [%4];" : "=r"(r[0]), "=r"(r[1]), "=r"(r[2]), "=r"(r[3]) : "r"(a) : "memory"); }
__device__ __forceinline__ void stsm4(uint32_t a, uint32_t r0, uint32_t r1, uint32_t r2, uint32_t r3) { asm volatile("stmatrix.sync.aligned.m8n8.x4.shared.b16 [%0], {%1,%2,%3,%4};" ::"r"(a), "r"(r0), "r"(r1), "r"(r2), "r"(r3) : "memory"); }
__device__ __forceinline__ void stsm4t(uint32_t a, uint32_t r0, uint32_t r1, uint32_t r2, uint32_t r3) { asm volatile("stmatrix.sync.aligned.m8n8.x4.trans.shared.b16 [%0], {%1,%2,%3,%4};" ::"r"(a), "r"(r0), "r"(r1), "r"(r2), "r"(r3) : "memory"); }
__device__ __forceinline__ uint32_t lds32(uint32_t a) { uint32_t v; asm volatile("ld.shared.u32 %0, [%1];" : "=r"(v) : "r"(a) : "memory"); return v; }
__device__ __forceinline__ uint2 lds64(uint32_t a) { uint2 v; asm volatile("ld.shared.v2.u32 {%0,%1}, [%2];" : "=r"(v.x), "=r"(v.y) : "r"(a) : "memory"); return v; }
__device__ __forceinline__ uint4 lds128(uint32_t a) { uint4 v; asm volatile("ld.shared.v4.u32 {%0,%1,%2,%3}, [%4];" : "=r"(v.x), "=r"(v.y), "=r"(v.z), "=r"(v.w) : "r"(a) : "memory"); return v; }
__device__ __forceinline__ void sts16(uint32_t a, uint32_t v) { asm volatile("st.shared.u16 [%0], %1;" ::"r"(a), "h"((unsigned short)v) : "memory"); }
__device__ __forceinline__ void sts32(uint32_t a, uint32_t v) { asm volatile("st.shared.u32 [%0], %1;" ::"r"(a), "r"(v) : "memory"); }
__device__ __forceinline__ void sts64(uint32_t a, uint32_t x, uint32_t y) { asm volatile("st.shared.v2.u32 [%0], {%1,%2};" ::"r"(a), "r"(x), "r"(y) : "memory"); }
__device__ __forceinline__ void sts128(uint32_t a, uint32_t x, uint32_t y, uint32_t z, uint32_t w) { asm volatile("st.shared.v4.u32 [%0], {%1,%2,%3,%4};" ::"r"(a), "r"(x), "r"(y), "r"(z), "r"(w) : "memory"); }
__device__ __forceinline__ uint32_t ldg32(const void* a) { uint32_t v; asm volatile("ld.global.nc.u32 %0, [%1];" : "=r"(v) : "l"(a)); return v; }
__device__ __forceinline__ uint32_t ldg16(const void* a) { uint32_t v; asm volatile("ld.global.nc.u16 %0, [%1];" : "=r"(v) : "l"(a)); return v; }
__device__ __forceinline__ float bflo(uint32_t v) { return __uint_as_float(v << 16); }
__device__ __forceinline__ float bfhi(uint32_t v) { return __uint_as_float(v & 0xffff0000u); }
__device__ __forceinline__ uint32_t pack_bf(float lo, float hi) { uint32_t r; asm("cvt.rn.bf16x2.f32 %0, %1, %2;" : "=r"(r) : "f"(hi), "f"(lo)); return r; }
__device__ __forceinline__ uint32_t pack_h(float lo, float hi) { uint32_t r; asm("cvt.rn.f16x2.f32 %0, %1, %2;" : "=r"(r) : "f"(hi), "f"(lo)); return r; }
__device__ __forceinline__ float rnd_bf(float v) { return __bfloat162float(__float2bfloat16_rn(v)); }
__device__ __forceinline__ float ex2a(float v) { float r; asm("ex2.approx.ftz.f32 %0, %1;" : "=f"(r) : "f"(v)); return r; }
__device__ __forceinline__ float tanha(float v) { float r; asm("tanh.approx.f32 %0, %1;" : "=f"(r) : "f"(v)); return r; }
__device__ __forceinline__ uint32_t hadd(uint32_t a, uint32_t b) { uint32_t r; asm("add.rn.f16x2 %0, %1, %2;" : "=r"(r) : "r"(a), "r"(b)); return r; }
__device__ __forceinline__ uint32_t badd(uint32_t a, uint32_t b) { uint32_t r; asm("add.rn.bf16x2 %0, %1, %2;" : "=r"(r) : "r"(a), "r"(b)); return r; }
__device__ __forceinline__ uint32_t bmul(uint32_t a, uint32_t b) { uint32_t r; asm("mul.rn.bf16x2 %0, %1, %2;" : "=r"(r) : "r"(a), "r"(b)); return r; }
__device__ __forceinline__ uint32_t bfma(uint32_t a, uint32_t b, uint32_t c) { uint32_t r; asm("fma.rn.bf16x2 %0, %1, %2, %3;" : "=r"(r) : "r"(a), "r"(b), "r"(c)); return r; }
__device__ __forceinline__ float tanhv(float v) { float r; asm volatile("tanh.approx.f32 %0, %1;" : "=f"(r) : "f"(v)); return r; }
__device__ __forceinline__ uint32_t bsub(uint32_t a, uint32_t b) { uint32_t r; asm("sub.rn.bf16x2 %0, %1, %2;" : "=r"(r) : "r"(a), "r"(b)); return r; }
__device__ __forceinline__ uint32_t dup(uint32_t v, uint32_t nz) { uint32_t r; asm volatile("add.rn.f32 %0, %1, %2;" : "=r"(r) : "r"(v), "r"(nz)); return r; }
__device__ __forceinline__ void bmma(float* c, uint32_t a0, uint32_t a1, uint32_t a2, uint32_t a3, uint32_t b0, uint32_t b1) {
  asm("mma.sync.aligned.m16n8k16.row.col.f32.bf16.bf16.f32 {%0,%1,%2,%3}, {%4,%5,%6,%7}, {%8,%9}, {%0,%1,%2,%3};"
      : "+f"(c[0]), "+f"(c[1]), "+f"(c[2]), "+f"(c[3]) : "r"(a0), "r"(a1), "r"(a2), "r"(a3), "r"(b0), "r"(b1));
}
__device__ __forceinline__ uint32_t odd_pair(uint32_t a, uint32_t b) { return __byte_perm(a, b, 0x5432); }
__device__ __forceinline__ int upos(int c) { return c ^ ((c >> 5) & 7) ^ ((c >> 3) & 1); }
__device__ __forceinline__ int uoff(int pos) { return (pos >> 1) * 160 + (pos & 1) * 16; }

struct cf { float r, i; };
__device__ __forceinline__ cf cmul(cf a, cf b) { cf o; o.r = fmaf(a.r, b.r, -a.i * b.i); o.i = fmaf(a.r, b.i, a.i * b.r); return o; }
__device__ __forceinline__ cf cmulj(cf a, cf b) { cf o; o.r = fmaf(a.r, b.r, a.i * b.i); o.i = fmaf(a.i, b.r, -a.r * b.i); return o; }
__device__ __forceinline__ cf csq(cf a) { cf o; o.r = fmaf(a.r, a.r, -a.i * a.i); o.i = (a.r + a.r) * a.i; return o; }
struct hp { uint32_t r, i; };
__device__ __forceinline__ hp hpack(cf a, cf b) { hp o; o.r = pack_h(a.r, b.r); o.i = pack_h(a.i, b.i); return o; }
__device__ __forceinline__ hp hmulc(hp a, uint32_t c) {
  __half2 ar = *reinterpret_cast<__half2*>(&a.r), ai = *reinterpret_cast<__half2*>(&a.i), cc = *reinterpret_cast<__half2*>(&c);
  __half2 orr = __hfma2(ar, __low2half2(cc), __hneg2(__hmul2(ai, __high2half2(cc))));
  __half2 oi = __hfma2(ar, __high2half2(cc), __hmul2(ai, __low2half2(cc)));
  hp o; o.r = *reinterpret_cast<uint32_t*>(&orr); o.i = *reinterpret_cast<uint32_t*>(&oi); return o;
}
__device__ __forceinline__ hp hmulj(hp a, uint32_t c) {
  __half2 ar = *reinterpret_cast<__half2*>(&a.r), ai = *reinterpret_cast<__half2*>(&a.i), cc = *reinterpret_cast<__half2*>(&c);
  __half2 orr = __hfma2(ar, __low2half2(cc), __hmul2(ai, __high2half2(cc)));
  __half2 oi = __hfma2(ai, __low2half2(cc), __hneg2(__hmul2(ar, __high2half2(cc))));
  hp o; o.r = *reinterpret_cast<uint32_t*>(&orr); o.i = *reinterpret_cast<uint32_t*>(&oi); return o;
}
__device__ __forceinline__ hp hmule(hp a, hp b) {
  __half2 ar = *reinterpret_cast<__half2*>(&a.r), ai = *reinterpret_cast<__half2*>(&a.i);
  __half2 br = *reinterpret_cast<__half2*>(&b.r), bi = *reinterpret_cast<__half2*>(&b.i);
  __half2 orr = __hfma2(ar, br, __hneg2(__hmul2(ai, bi))), oi = __hfma2(ar, bi, __hmul2(ai, br));
  hp o; o.r = *reinterpret_cast<uint32_t*>(&orr); o.i = *reinterpret_cast<uint32_t*>(&oi); return o;
}
__device__ __forceinline__ void sts_tile(uint32_t a, const hp* t) {
  sts128(a, t[0].r, t[1].r, t[2].r, t[3].r);
  sts128(a + 512, t[0].i, t[1].i, t[2].i, t[3].i);
}
template <int STEP> __device__ __forceinline__ void put2(uint32_t a0, uint32_t a1, uint32_t h, uint32_t sel) {
  const uint32_t x = __byte_perm(h, h, sel), y = x >> 16;
  sts16(a0, x); sts16(a0 + STEP * 4 + 2, x);
  sts16(a1, y); sts16(a1 + STEP * 4 + 2, y);
}

__device__ __forceinline__ void spare_work(const Params& p, const CUtensorMap* tmW1, int k, int tid) {
  const int lane = tid & 31;
  unsigned ep = 0;
  if (tid >= 480) ep = p.scr->epoch[128 + k] + 1;
  if (tid == 480) {
    for (int i = 0; i < 8; i++) mbar_init(bar + 8 * i, i < 4 ? 1 : 12);
    asm volatile("fence.mbarrier_init.release.cluster;" ::: "memory");
    fence_async_smem();
  }
  __syncthreads();
  float a[2][4] = {{0.f, 0.f, 0.f, 0.f}, {0.f, 0.f, 0.f, 0.f}};
  if (tid >= 480) {
    if (elect1()) {
      if (SPARE_NS) __nanosleep(SPARE_NS);
#pragma unroll 1
      for (int s = 0; s < 10; s++) {
        mbar_wait(bar + 8 * (4 + (s & 3)), ((s >> 2) & 1) ^ 1);
        mbar_expect(bar + 8 * (s & 3), 49152);
#pragma unroll 1
        for (int b = 0; b < 2; b++) tma3d(sb + (s & 3) * 49152 + b * 24576, tmW1, 0, s * 64, k * 6 + b * 3, bar + 8 * (s & 3));
      }
    }
    __syncwarp();
  } else if (tid < 384) {
    const uint32_t idn = (lane >> 3) == (lane & 3) ? ((lane & 4) ? 0x3f800000u : 0x3f80u) : 0u;
#pragma unroll 1
    for (int s = 0; s < 10; s++) {
      mbar_wait(bar + 8 * (s & 3), (s >> 2) & 1);
      const uint32_t ad = sb + (s & 3) * 49152 + (tid >> 6) * 8192 + (tid & 63) * 16;
#pragma unroll
      for (int i = 0; i < 8; i += 2) {
        const uint4 v = lds128(ad + i * 1024), w = lds128(ad + i * 1024 + 1024);
        bmma(a[0], v.x, v.y, w.x, w.y, idn, idn);
        bmma(a[1], v.z, v.w, w.z, w.w, idn, idn);
      }
      __syncwarp();
      if (lane == 0) mbar_arrive(bar + 8 * (4 + (s & 3)));
    }
    const int rho = (tid >> 3) & 7;
    const uint32_t ad = sb + 196608 + rho * 1536 + ((tid >> 6) * 8 + ((tid & 7) ^ rho)) * 32;
    sts128(ad, __float_as_uint(a[0][0]), __float_as_uint(a[0][1]), __float_as_uint(a[0][2]), __float_as_uint(a[0][3]));
    sts128(ad + 16, __float_as_uint(a[1][0]), __float_as_uint(a[1][1]), __float_as_uint(a[1][2]), __float_as_uint(a[1][3]));
  }
  __syncthreads();
  if (tid < 384) {
    float s = 0.f;
#pragma unroll
    for (int r = 0; r < 8; r++) s += __uint_as_float(lds32(sb + 196608 + r * 1536 + tid * 4));
    p.scr->cs[k * 384 + (tid & ~30) + ((tid & 6) << 2) + ((tid >> 2) & 6)] = s;
  }
  __syncthreads();
  if (tid == 480) {
    publish(p.scr->cnt + C_CS * 32);
    p.scr->epoch[128 + k] = ep;
    poll_cnt(p.scr->cnt + C_LN * 32, ep * 128);
  }
}

__device__ __forceinline__ void load1(int s, const CUtensorMap* tmX, const CUtensorMap* tmW1, int rg1, int j1) {
  const uint32_t d = sb + (s & 3) * SLOT1, mb = bar + 8 * (B_FULL1 + s);
  mbar_expect(mb, SLOT1);
  tma2d(d, tmX, s * 64, rg1 * 128, mb);
  tma3d(d + 16384, tmW1, 0, s * 64, j1 * 3, mb);
}
__device__ __forceinline__ void load_x(uint32_t (&xv)[2][10], const __nv_bfloat16* xa, const __nv_bfloat16* xb, int rstep) {
#pragma unroll
  for (int r = 0; r < 2; r++) {
    const uint4 a = __ldg((const uint4*)(xa + r * rstep)), b = __ldg((const uint4*)(xa + r * rstep + 32));
    const uint2 c = __ldg((const uint2*)(xb + r * rstep + 64));
    xv[r][0] = a.x; xv[r][1] = a.y; xv[r][2] = a.z; xv[r][3] = a.w; xv[r][4] = b.x; xv[r][5] = b.y; xv[r][6] = b.z; xv[r][7] = b.w;
    xv[r][8] = c.x; xv[r][9] = c.y;
  }
}

__device__ __forceinline__ uint32_t pin(uint32_t v, uint32_t z) { uint32_t r; asm volatile("add.u32 %0, %1, %2;" : "=r"(r) : "r"(v), "r"(z)); return r; }
struct Comb { uint32_t o[7]; };
__device__ __forceinline__ Comb comb_setup(int tid, uint32_t z) {
  Comb k;
  const int c = tid & 127, c1 = c < 112 ? c + 32 : c - 112, c2 = c < 112 ? c + 144 : c - 96;
  const uint32_t zr = ZA1 + (c & 7) * 16, a2 = ZA2 + ((c & ~15) - 32 + ((((c >> 1) & 7) + (c & 1) * 8) ^ ((c & 1) * 4))) * 16;
  k.o[0] = uoff(upos(c1)); k.o[1] = uoff(upos(c2));
  k.o[2] = c < 112 ? ZA1 + 512 + ((2 * c) ^ ((c >> 2) & 1)) * 16 : zr;
  k.o[3] = c1 >= 64 ? a2 : zr; k.o[4] = c < 112 ? a2 + 112 * 16 : zr;
  k.o[5] = ((c1 >> 4) * 1280 + (c & 15)) * 16; k.o[6] = ((c2 >> 4) * 1280 + (c & 15)) * 16;
#pragma unroll
  for (int i = 0; i < 7; i++) k.o[i] = pin(k.o[i], z);
  return k;
}
template <class F> __device__ __forceinline__ void combine(const Comb& k, int ch, int wid, uint4* sT, F&& after_reads) {
  const uint32_t ub = sb + OFF_U + ch * 32, zb = sb + OFF_Z + ch * ZSZ;
  const int row = (wid & 15) * 5 + ch;
  char* dst = (char*)(sT + ((wid >> 4) * 16 * 80 + row) * 16);
  mbar_wait(bar + 8 * (B_PART + ch), 0);
  const uint32_t sc = lds32(sb + OFF_CHC + ch * 8);
  const uint4 y0 = lds128(zb + k.o[2]), y1 = lds128(zb + (k.o[2] ^ 16));
  const uint4 v2 = lds128(zb + k.o[3]), u2 = lds128(zb + k.o[4]);
  const uint4 v0 = lds128(ub + k.o[0]), u0 = lds128(ub + k.o[1]);
  fence_async_smem();
  after_reads();
  *(uint4*)(dst + (k.o[5] ^ ((row & 7) * 16))) =
      make_uint4(bmul(badd(badd(y0.x, v2.x), v0.x), sc), bmul(badd(badd(y0.y, v2.y), v0.y), sc),
                 bmul(badd(badd(y1.x, v2.z), v0.z), sc), bmul(badd(badd(y1.y, v2.w), v0.w), sc));
  *(uint4*)(dst + (k.o[6] ^ ((row & 7) * 16))) =
      make_uint4(bmul(badd(badd(y0.z, u2.x), u0.x), sc), bmul(badd(badd(y0.w, u2.y), u0.y), sc),
                 bmul(badd(badd(y1.z, u2.z), u0.z), sc), bmul(badd(badd(y1.w, u2.w), u0.w), sc));
  __syncwarp();
  if (elect1()) mbar_arrive(bar + 8 * (B_FREE + ch));
}

__device__ __forceinline__ void load2(int s, uint32_t d, const uint4* srcA, const uint4* srcB) {
  const uint32_t mb = bar + 8 * (B_FULL2 + s);
  mbar_expect(mb, SLOT2);
  bulk_g2s(d, srcA, 16384, mb);
  bulk_g2s(d + 16384, srcB, 10240, mb);
}

template <bool USE_SMID>
__global__ void __launch_bounds__(512, 1)
fused_s4_ffn_kernel(const Params p, const __grid_constant__ CUtensorMap tmX, const __grid_constant__ CUtensorMap tmW1,
                    const __grid_constant__ CUtensorMap tmU, const __grid_constant__ CUtensorMap tmW2) {
  extern __shared__ __align__(1024) unsigned char smem_raw[];
  const int tid = threadIdx.x, lane = tid & 31;
  uint32_t sid;
  if (USE_SMID) asm("mov.u32 %0, %smid;" : "=r"(sid)); else sid = blockIdx.x;
  const int wid = sid < 120 ? sid : sid - 4;
  uint32_t pa[6], pld, pds;
  const unsigned pw = min(tid >> 5, 14), part = (pw * 13) >> 6;
  const unsigned ch = (wid >> 4) * 80 + frag_col(((wid & 15) - part) * 5 + pw);
  const unsigned o = (ch * 3 + part) * 32 + lane;
  {
    pld = ldg16(p.logdt + ch);
    pa[0] = ldg32((const uint32_t*)p.are + o); pa[1] = ldg32((const uint32_t*)p.aim + o);
    pds = ldg16(p.dskip + ch);
    pa[2] = ldg32((const uint32_t*)p.bre + o); pa[3] = ldg32((const uint32_t*)p.bim + o);
    pa[4] = ldg32((const uint32_t*)p.cre + o); pa[5] = ldg32((const uint32_t*)p.cim + o);
  }
  const int warp = __shfl_sync(0xffffffffu, tid >> 5, 0);
  const int g = lane >> 2, q = lane & 3;
  float dt;
  if (DTE) dt = __uint_as_float(pin(__float_as_uint(rnd_bf(expf(bflo(pld)))), sid >> 8));
  if (sid - 120u < 4u) { spare_work(p, &tmW1, sid - 120, tid); return; }
  unsigned* const cnt = p.scr->cnt;

  float kacc[6][4];
  const int kch = warp - 10;
  float k0;
  uint32_t xv[2][10], xs[2], mw;
  {
    unsigned ep0;
    if (warp == 15) {
      ep0 = p.scr->epoch[wid];
      if ((uint32_t)__cvta_generic_to_shared(smem_raw) != sb) __trap();
    }
    if (elect1()) {
      const int gi = (warp + 1) & 15;
#pragma unroll
      for (int i = 0; i < 6; i++) mbar_init(bar + 48 * gi + 8 * i, gi < 7 ? 1 : gi == 7 ? 2 : gi < 10 ? 4 : 8);
      asm volatile("fence.mbarrier_init.release.cluster;" ::: "memory");
    }
    const uint32_t z0 = sid >> 8;
#pragma unroll
    for (int j = 0; j < 24; j++) kacc[j >> 2][j & 3] = __uint_as_float(pin(z0, z0));
    const uint32_t ks = sb + OFF_KS + warp * 4096;
    const uint32_t st = pin(ks + lane * 16, z0);
    const uint32_t kw = pin(ks + 3584 + (lane >> 1) * (SQ ? 8 : 16) + (lane & 1) * 2, z0), kr = pin(ks + 3584 + q * (SQ ? 8 : 16), z0);
    const uint32_t kb = pin(ks + ((lane >> 3) & 1) * 512 + ((lane >> 4) * 8 + (lane & 7)) * 16, z0);
    const __nv_bfloat16* xr = p.x + (wid * 16 + ((g >> 1) << 2) + (g & 1)) * DM;
    const __nv_bfloat16 *xa = xr + (warp & 7) * 80 + q * 8, *xb = xr + (warp & 7) * 80 + q * 4;
    asm volatile("add.u64 %0, %0, %3;\nadd.u64 %1, %1, %3;\nadd.u64 %2, %2, %3;" : "+l"(xr), "+l"(xa), "+l"(xb) : "l"((uint64_t)z0));
    bar_sync(14, 512);
    if (warp == 15) {
      sts32(sb + OFF_ZERO + lane * 4, 0);
      int gpc, i;
      if (sid < 64) { gpc = (sid & 15) >> 1; i = sid >> 4; }
      else if (sid < 120) { const int t = sid - 64; i = t / 14; gpc = 1 + ((t - i * 14) >> 1); i += 4; }
      else { gpc = 0; i = 4 + ((sid - 124) >> 1); }
      const int qi = ((0x52741630 >> (4 * i)) & 7) * 2 + (sid & 1);
      const int rg = 4 * (gpc >> 1) + (qi >> 2), jc = 4 * (gpc & 1) + (qi & 3);
      sts64(sb + OFF_EP + 8, rg, jc);
      __syncwarp();
      if (elect1()) {
        asm volatile("prefetch.tensormap [%0];\nprefetch.tensormap [%1];\nprefetch.tensormap [%2];\nprefetch.tensormap [%3];" ::"l"(&tmW2), "l"(&tmX), "l"(&tmW1), "l"(&tmU) : "memory");
        if (DELAY_NS) __nanosleep(DELAY_NS);
        if (XPF) bulk_prefetch(p.x + wid * 16 * DM, 16 * DM * 2);
        mbar_expect(bar + 8 * B_W2, 96 * 176);
      }
      __syncwarp();
      load_x(xv, xa, xb, 2 * DM);
      xs[0] = __ldg((const uint32_t*)xr); xs[1] = __ldg((const uint32_t*)(xr + 2 * DM));
      bar_sync(5, 256);
      if (XWAIT) sts32(sb + OFF_EP + 4, xv[1][9]);
      if (elect1()) {
        if (DELAY2_NS) __nanosleep(DELAY2_NS);
        tma5d(sb + OFF_W2S, &tmW2, (wid & 7) * 80, (wid >> 3) * 3, bar + 8 * B_W2);
        p.scr->epoch[wid] = ep0 + 1;
        sts32(sb + OFF_EP, ep0 + 1);
      }
      __syncwarp();
    }
    float zr, th, zr1, th1;
    cf c, c1;
    if (!DTE) dt = rnd_bf(expf(bflo(pld)));
    {
      const float dl2 = dt * 1.4426950408889634f;
      zr = bflo(pa[0]) * dl2; th = bflo(pa[1]) * dt; zr1 = bfhi(pa[0]) * dl2; th1 = bfhi(pa[1]) * dt;
    }
    if (warp < 15) {
      c = cmul(cf{bflo(pa[4]), bflo(pa[5])}, cf{bflo(pa[2]), bflo(pa[3])});
      c1 = cmul(cf{bfhi(pa[4]), bfhi(pa[5])}, cf{bfhi(pa[2]), bfhi(pa[3])});
      mw = __reduce_max_sync(0xffffffffu, __float_as_uint(fmaxf(fmaxf(fabsf(c.r), fabsf(c.i)), fmaxf(fabsf(c1.r), fabsf(c1.i)))));
      mw = min(max(mw & 0x7f800000u, 20u << 23), 240u << 23);
      const float sc = __uint_as_float((259u << 23) - mw);
      k0 = c.r + c1.r;
      c.r *= sc; c.i *= -sc; c1.r *= sc; c1.i *= -sc;
      if (warp >= 8) {
        load_x(xv, xa, xb, 2 * DM);
        xs[0] = __ldg((const uint32_t*)xr); xs[1] = __ldg((const uint32_t*)(xr + 2 * DM));
        bar_arrive(5, 256);
      }
    }
    if (STAG && ((STAG >> (8 * (warp >> 2))) & 255)) {
      const unsigned t0 = clock(), dl = ((STAG >> (8 * (warp >> 2))) & 255) * 16;
      if (STAGN) __nanosleep(dl * 4 / 7); else while (clock() - t0 < dl) {}
    }
    {
#pragma unroll 1
      for (int it = 0; it < 2; it++) {
        if (it == 1 && warp >= 8) {
          float sm[4] = {0.f, 0.f, 0.f, 0.f}, g0[4] = {0.f, 0.f, 0.f, 0.f}, g1[4] = {0.f, 0.f, 0.f, 0.f};
#pragma unroll
          for (int r = 0; r < 2; r++)
            xs[r] = fabsf(bflo(xs[r]) - bfhi(xs[r])) * 8.f < fabsf(bflo(xs[r])) ? __byte_perm(xs[r], 0, 0x1010) : 0u;
#pragma unroll
          for (int i = 0; i < 10; i += 2) {
            const uint32_t a0 = bsub(xv[0][i], xs[0]), a1 = bsub(xv[1][i], xs[1]), a2 = bsub(xv[0][i + 1], xs[0]), a3 = bsub(xv[1][i + 1], xs[1]);
            bmma(sm, a0, a1, a2, a3, 0x3f803f80u, 0x3f803f80u);
            bmma(g0, a0, a1, a2, a3, xv[0][i], xv[0][i + 1]);
            bmma(g1, a0, a1, a2, a3, xv[1][i], xv[1][i + 1]);
          }
          if (q == (g >> 1))
            sts128(sb + OFF_LNP + (warp - 8) * 128 + g * 16, __float_as_uint(sm[0]), __float_as_uint((g & 1) ? g0[1] : g0[0]),
                   __float_as_uint(sm[2]), __float_as_uint((g & 1) ? g1[3] : g1[2]));
          if (warp != FINW) bar_arrive(1, 256);
        }
        if (warp == 15) continue;
        if (LDQ && it == 1 && (warp & 3) == 3) {
          if (elect1()) { const uint2 rj = lds64(sb + OFF_EP + 8); load1(warp == 11 ? 0 : (warp >> 2) + 1, &tmX, &tmW1, rj.x, rj.y); }
          __syncwarp();
        }
        float m = ex2a(zr);
        const cf w1 = cf{m * __cosf(th), m * __sinf(th)};
        m = ex2a(zr * 8.f);
        const cf w8 = cf{m * __cosf(th * 8.f), m * __sinf(th * 8.f)};
        const cf w16 = csq(w8), w32 = csq(w16), w64 = csq(w32), w128 = csq(w64), w256 = csq(w128), w512 = csq(w256), w1024 = csq(w512);
        hp lo[4];
        lo[0] = hpack(cf{1.f, 0.f}, w8);
        lo[1] = hmulc(lo[0], pack_h(w16.r, w16.i));
        { const uint32_t k = pack_h(w32.r, w32.i); lo[2] = hmulc(lo[0], k); lo[3] = hmulc(lo[1], k); }
        sts_tile(st, lo);
        { const uint32_t k = pack_h(w64.r, w64.i); sts16(kw, k); sts16(kw + 4, k >> 16); }
        if (!SQ) { const uint32_t k = pack_h(w128.r, w128.i); sts16(kw + 8, k); sts16(kw + 12, k >> 16); }
        const uint32_t k256 = pack_h(w256.r, w256.i), k512 = pack_h(w512.r, w512.i);
        const cf t8 = cmulj(c, w8);
        { const cf u0 = cmulj(t8, w1024), u1 = cmulj(u0, w256);
          const hp a = hpack(u0, u1), b = hmulj(a, k512);
          sts128(st + 3072, a.r, b.r, a.i, b.i); }
        const cf t1 = cmulj(c, w1), t2 = cmulj(t1, w1), t3 = cmulj(t2, w1), t4 = cmulj(t3, w1);
        const cf t5 = cmulj(t4, w1), t6 = cmulj(t5, w1), t7 = cmulj(t6, w1);
        hp T0[4], T1[4];
        T0[0] = hpack(t4, t8); T0[1] = hpack(t2, t6); T0[2] = hpack(t1, t5); T0[3] = hpack(t3, t7);
        T1[0] = hmulj(T0[0], k256); T1[1] = hmulj(T0[1], k256); T1[2] = hmulj(T0[0], k512); T1[3] = hmulj(T1[0], k512);
        sts_tile(st + 2048, T1);
        sts_tile(st + 1024, T0);
        __syncwarp();
        uint32_t bc[4];
        ldsm4t(bc, st + 3072);
#pragma unroll
        for (int m2 = 0; m2 < 4; m2 += 2) {
          uint32_t l0[4], b0[4], b1[4];
          ldsm4t(l0, kb + m2 * 128);
          ldsm4t(b0, kb + 1024 + m2 * 128);
          ldsm4t(b1, kb + 2048 + m2 * 128);
#pragma unroll
          for (int i = 0; i < 2; i++) {
            hp k64, k128;
            if (SQ) { const uint2 v = lds64(kr + (m2 + i) * 32); k64.r = v.x; k64.i = v.y; k128 = hmule(k64, k64); }
            else { const uint4 v = lds128(kr + (m2 + i) * 64); k64.r = v.x; k64.i = v.y; k128.r = v.z; k128.i = v.w; }
            hp L0, L1, L2, L3;
            L0.r = l0[2 * i]; L0.i = l0[2 * i + 1];
            L1 = hmule(L0, k64); L2 = hmule(L0, k128); L3 = hmule(L1, k128);
            const uint32_t c0 = lane < 16 ? bc[m2 + i] : 0u, c1b = lane < 16 ? 0u : bc[m2 + i];
            const uint32_t a0 = pin(L0.r, z0), a2 = pin(L0.i, z0);
            hmma(kacc[0], a0, L1.r, a2, L1.i, b0[2 * i], b0[2 * i + 1]);
            hmma(kacc[2], a0, L1.r, a2, L1.i, b1[2 * i], b1[2 * i + 1]);
            hmma(kacc[4], a0, L1.r, a2, L1.i, c0, c1b);
            hmma(kacc[1], L2.r, L3.r, L2.i, L3.i, b0[2 * i], b0[2 * i + 1]);
            hmma(kacc[3], L2.r, L3.r, L2.i, L3.i, b1[2 * i], b1[2 * i + 1]);
            hmma(kacc[5], L2.r, L3.r, L2.i, L3.i, c0, c1b);
          }
        }
        __syncwarp();
        zr = zr1; th = th1; c = c1;
      }
    }
    if (warp >= 8) bar_arrive(6, 512);
    if (warp < 10) {
#pragma unroll
      for (int j = 0; j < 6; j++)
        sts128(st + j * 512, __float_as_uint(kacc[j][0]), __float_as_uint(kacc[j][1]), __float_as_uint(kacc[j][2]), __float_as_uint(kacc[j][3]));
      sts64(ks + 3072 + lane * 8, __float_as_uint(k0), mw);
    }
    if (warp == FINW) {
      bar_sync(1, 256);
      float s1 = 0.f, s2 = 0.f;
#pragma unroll
      for (int w = 0; w < 8; w++) {
        const uint2 v = lds64(sb + OFF_LNP + w * 128 + g * 16 + (q & 1) * 8);
        s1 += __uint_as_float(v.x); s2 += __uint_as_float(v.y);
      }
      const float md = s1 * (1.f / DM), mean = bflo((q & 1) ? xs[1] : xs[0]) + md;
      const float var = fmaxf(fmaf(-md, mean, s2 * (1.f / DM)), 0.f);
      const float m = rnd_bf(mean);
      float sd, ri;
      asm("sqrt.approx.f32 %0, %1;" : "=f"(sd) : "f"(rnd_bf(rnd_bf(var) + 1e-5f)));
      asm("rcp.approx.f32 %0, %1;" : "=f"(ri) : "f"(rnd_bf(sd)));
      if (q < 2) {
        p.scr->stats[wid * 16 + ((g >> 1) << 2) + (g & 1) + 2 * q] = make_float2(-m, 0.5f * ri);
        sts64(sb + OFF_STAT + g * 16 + q * 8, __float_as_uint(-m * ri), __float_as_uint(ri));
      }
      __syncwarp();
    }
    if (warp == 15 || (W2H && warp == 11)) {
      const uint2 rj = lds64(sb + OFF_EP + 8);
      mbar_wait(bar + 8 * B_W2, 0);
#pragma unroll 1
      for (int uu = warp == 15 ? 0 : 2; uu < 3; uu++) {
        if (warp == 15 && elect1()) {
          if (!LDQ) load1(uu, &tmX, &tmW1, rj.x, rj.y);
          if (uu == W1PF) bulk_prefetch(p.w1 + wid * 5 * FF, 5 * FF * 2);
        }
        if (W2H && warp == 15 && uu == 2) break;
        const uint32_t a = sb + OFF_W2S + (uu * 32 + lane) * 176;
        const int rem = ((wid >> 3) & 1) * 3 + uu;
        uint4* dst = p.scr->w2p + ((wid & 7) * 24 + 8 * (rem >> 1) + (wid >> 4)) * 640 + ((rem & 1) * 4 + (lane >> 3)) * 80 + (lane & 7);
        uint4 v[10];
#pragma unroll
        for (int i = 0; i < 10; i++) v[i] = lds128(a + i * 16);
        if (W2H && warp == 11) { fence_async_smem(); bar_arrive(4, 64); }
#pragma unroll
        for (int i = 0; i < 8; i++)
          dst[8 * i] = make_uint4(bmul((&v[i & 4].x)[i & 3], 0x3f003f00u), bmul((&v[(i & 4) + 1].x)[i & 3], 0x3f003f00u),
                                  bmul((&v[(i & 4) + 2].x)[i & 3], 0x3f003f00u), bmul((&v[(i & 4) + 3].x)[i & 3], 0x3f003f00u));
        dst[64] = make_uint4(bmul(v[8].x, 0x3f003f00u), bmul(v[8].z, 0x3f003f00u), bmul(v[9].x, 0x3f003f00u), bmul(v[9].z, 0x3f003f00u));
        dst[72] = make_uint4(bmul(v[8].y, 0x3f003f00u), bmul(v[8].w, 0x3f003f00u), bmul(v[9].y, 0x3f003f00u), bmul(v[9].w, 0x3f003f00u));
      }
      if (warp == 15) {
        fence_async_smem();
        if (W2H) bar_sync(4, 64); else __syncwarp();
        if (elect1()) load1(3, &tmX, &tmW1, rj.x, rj.y);
        __syncwarp();
      }
    }
  }

  if (warp < 8) {
    float acc[96];
    const uint32_t alo = ((sb >> 4) | (1 << 16)) + (warp >> 2) * 512;
    bar_arrive(0, 512);
#pragma unroll 1
    for (int s = 0; s < 10; s++) {
      const uint32_t so = (s & 3) * (SLOT1 >> 4);
      mbar_wait(bar + 8 * (B_FULL1 + s), 0);
      if (s == 0) bar_sync(6, 512);
      wg_fence();
#pragma unroll
      for (int kk = 0; kk < 4; kk++)
        wgmma_n192(acc, dsc(alo + so + kk * 2, 0x40000040u), dsc((((sb + 16384) >> 4) | (512 << 16)) + so + kk * 128, 0x40000040u), (s | kk) != 0);
      wg_commit();
      wg_wait<1>();
      if (lane == 0) mbar_arrive(bar + 8 * (B_REL1 + s));
    }
    wg_wait<0>();
    bar_arrive(14, 384);
    bar_arrive(7, 384);
    mbar_wait(bar + 8 * B_EPI, 0);
    const uint2 s0 = lds64(sb + OFF_STAT + (warp * 16 + g) * 8), s1 = lds64(sb + OFF_STAT + (warp * 16 + g + 8) * 8);
    const float nm0 = __uint_as_float(s0.x), r0 = __uint_as_float(s0.y), nm1 = __uint_as_float(s1.x), r1 = __uint_as_float(s1.y);
    const uint4 erj = lds128(sb + OFF_EP);
    const unsigned ep = erj.x;
    const int rg1 = erj.z, j1 = erj.w;
    uint4* hd = p.scr->h + (rg1 * 24 + j1) * 1024 + warp * 128 + q * 8 + g;
#pragma unroll
    for (int grp = 0; grp < 6; grp++) {
      uint32_t o0[4], o1[4];
      const uint4 cs[2] = {lds128(sb + OFF_CS + grp * 128 + q * 32), lds128(sb + OFF_CS + grp * 128 + q * 32 + 16)};
#pragma unroll
      for (int tl = 0; tl < 4; tl++) {
        const int nt = grp * 4 + tl;
        const float ca = __uint_as_float((&cs[tl >> 1].x)[(tl & 1) * 2]), cb = __uint_as_float((&cs[tl >> 1].x)[(tl & 1) * 2 + 1]);
        const float a = fmaf(nm0, ca, acc[4 * nt]) * r0, b = fmaf(nm0, cb, acc[4 * nt + 1]) * r0;
        const float c = fmaf(nm1, ca, acc[4 * nt + 2]) * r1, d = fmaf(nm1, cb, acc[4 * nt + 3]) * r1;
        o0[tl] = pack_bf(fmaf(a, tanha(a), a), fmaf(b, tanha(b), b));
        o1[tl] = pack_bf(fmaf(c, tanha(c), c), fmaf(d, tanha(d), d));
      }
      uint4* dst = hd + (grp >> 1) * 8192 + (grp & 1) * 32;
      dst[0] = make_uint4(o0[0], o0[1], o0[2], o0[3]);
      dst[64] = make_uint4(o1[0], o1[1], o1[2], o1[3]);
      if (PACE_NS) __nanosleep(PACE_NS);
      if (grp == 1) {
        if (warp == 7) { bar_sync(2, 256); if (lane == 0) publish(cnt + (C_H0 + rg1) * 32); __syncwarp(); }
        else bar_arrive(2, 256);
      }
    }
    if (warp == 6) { bar_sync(11, 256); if (lane == 0) publish(cnt + (C_H1 + rg1) * 32); __syncwarp(); }
    else bar_arrive(11, 256);
    const int go = (rg1 * 128 + warp * 16 + g) * DM + j1 * 80;
    load_x(xv, p.x + go + q * 8, p.x + go + q * 4, 8 * DM);
    if (warp < 4) {
      const Comb cmb = comb_setup(tid, 0);
#pragma unroll 1
      for (int ch = 0; ch < 3; ch++) {
        combine(cmb, ch, wid, p.scr->sT, [] {});
      }
    } else if (warp == 4) {
      if (elect1()) {
        poll_cnt(cnt + (C_H0 + rg1) * 32, ep * 8);
#pragma unroll 1
        for (int s = 0; s < NS2 - 2; s++) {
          if (s == 4) poll_cnt(cnt + (C_H1 + rg1) * 32, ep * 8);
          if (s == 3) mbar_wait(bar + 8 * B_FREE, 0);
          if (s >= 3) mbar_wait(bar + 8 * (B_FREE + s - 2), 0);
          load2(s, sb + s * SLOT2, p.scr->h + (rg1 * 24 + s) * 1024, p.scr->w2p + (j1 * 24 + s) * 640);
        }
      }
      __syncwarp();
    }
    float acc2[40];
    bar_sync(8, 512);
    {
      const uint32_t al2 = ((sb >> 4) | (8 << 16)) + (warp >> 2) * 512;
      uint32_t so = 0;
#pragma unroll 1
      for (int s = 0; s < 24; s++) {
        mbar_wait(bar + 8 * (B_FULL2 + s), 0);
        if (SK2 && s == SK2 && warp < 4) bar_sync(4, 256);
        wg_fence();
#pragma unroll
        for (int kk = 0; kk < 4; kk++)
          wgmma_n80(acc2, dsc(al2 + so + kk * 16, 64), dsc((((sb + 16384) >> 4) | (80 << 16)) + so + kk * 160, 8), (s | kk) != 0);
        wg_commit();
        so = so == (NS2 - 1) * (SLOT2 >> 4) ? 0 : so + (SLOT2 >> 4);
        if (!SK2 || s < SK2 - 1) {
          wg_wait<1>();
          if (lane == 0) mbar_arrive(bar + 8 * (B_REL2 + s));
        }
      }
      if (SK2 && warp >= 4) { wg_wait<SKW>(); bar_arrive(4, 256); }
    }
    mbar_wait(bar + 8 * B_SFULL, 0);
    uint32_t sv[5][4];
    {
      const int i = lane & 7, mi = lane >> 3;
      const uint32_t a = sb + OFF_U + ((mi >> 1) * 8 + i) * 256 + (((2 * warp + (mi & 1)) ^ i) << 4);
#pragma unroll
      for (int k = 0; k < 5; k++) ldsm4t(sv[k], a + k * 4096);
    }
    wg_wait<0>();
#pragma unroll
    for (int hh = 0; hh < 2; hh++) {
      uint32_t o[10];
      __nv_bfloat16* op = p.out + go + hh * 8 * DM;
#pragma unroll
      for (int tl = 0; tl < 10; tl++) {
        const float a = acc2[4 * tl + 2 * hh], b = acc2[4 * tl + 2 * hh + 1];
        o[tl] = bfma(sv[tl >> 1][(tl & 1) * 2 + hh], pack_bf(fmaf(a, tanhv(a), a), fmaf(b, tanhv(b), b)), xv[hh][tl]);
        if ((tl & 3) == 3)
          asm volatile("st.global.v4.u32 [%0], {%1, %2, %3, %4};" ::"l"((uint4*)op + (tl >> 2) * 4 + q), "r"(o[tl - 3]), "r"(o[tl - 2]), "r"(o[tl - 1]), "r"(o[tl]) : "memory");
      }
      asm volatile("st.global.v2.u32 [%0], {%1, %2};" ::"l"((uint2*)(op + 64) + q), "r"(o[8]), "r"(o[9]) : "memory");
    }
  } else {
    const int cw = warp - 8;
    bar_sync(0, 512);
    const uint4 erj = lds128(sb + OFF_EP);
    const unsigned ep = erj.x;
    const int rg1 = erj.z, j1 = erj.w;
    {
      const uint4 st = lds128(sb + OFF_STAT + g * 16);
      const float n0 = __uint_as_float(st.x), r0 = __uint_as_float(st.y), n1 = __uint_as_float(st.z), r1 = __uint_as_float(st.w);
      const int up = upos(2 * wid);
      uint2* dst = (uint2*)p.scr->uT + ((up >> 1) * DM + cw * 80) * 4 + (lane ^ ((up & 1) << 1));
#pragma unroll
      for (int i = 0; i < 10; i++) {
        const uint32_t a = movm(pack_h(fmaf(bflo(xv[0][i]), r0, n0), fmaf(bfhi(xv[0][i]), r0, n0)));
        const uint32_t b = movm(pack_h(fmaf(bflo(xv[1][i]), r1, n1), fmaf(bfhi(xv[1][i]), r1, n1)));
        dst[i * 32] = make_uint2(a, b);
      }
    }
    if (warp == 8) {
      bar_sync(12, 256);
      if (lane == 0) publish(cnt + C_LN * 32);
      __syncwarp();
    } else bar_arrive(12, 256);
    if (warp == 15) {
      if (elect1()) {
#pragma unroll 1
        for (int s = 4; s < 10; s++) {
          mbar_wait(bar + 8 * (B_REL1 + s - 3), 0);
          load1(s, &tmX, &tmW1, rg1, j1);
        }
        poll_cnt(cnt + C_CS * 32, ep * 4);
        bulk_g2s(sb + OFF_CS, p.scr->cs + j1 * 192, 768, bar + 8 * B_EPI);
      }
      __syncwarp();
    }
    if (warp >= 10 && warp < 15) {
      const uint32_t pb = sb + OFF_P + kch * 3072, pk = sb + OFF_KS + kch * 4096;
      const uint2 e0 = lds64(pk + 3072 + lane * 8), e1 = lds64(pk + 5 * 4096 + 3072 + lane * 8);
      const float dsk = bflo(pds);
      uint32_t kex = __float_as_uint(fmaxf(__uint_as_float(max(max(e0.y, e1.y), mw)) * dt, fabsf(dsk) * (1.f / 256.f))) >> 23;
      kex = min(max(kex, 20u), 240u);
      const float s2 = __uint_as_float((258 - kex) << 23), sd = s2 * dt * (1.f / 32.f);
      const float f0 = __uint_as_float(e0.y) * sd, f1 = __uint_as_float(e1.y) * sd, f2 = __uint_as_float(mw) * sd;
      k0 += __uint_as_float(e0.x) + __uint_as_float(e1.x);
#pragma unroll
      for (int o = 16; o; o >>= 1) k0 += __shfl_xor_sync(0xffffffffu, k0, o);
      const float k0n = fmaf(k0, dt, dsk) * s2;
      uint32_t h[5][2];
#pragma unroll
      for (int j = 0; j < 6; j++) {
        const uint4 a = lds128(pk + j * 512 + lane * 16), b = lds128(pk + 5 * 4096 + j * 512 + lane * 16);
#pragma unroll
        for (int e = 0; e < 4; e++) kacc[j][e] = fmaf(__uint_as_float((&a.x)[e]), f0, fmaf(__uint_as_float((&b.x)[e]), f1, kacc[j][e] * f2));
        if (j == 1) {
          const float k256 = __shfl_sync(0xffffffffu, kacc[1][3], 28);
          if (lane == 31) kacc[1][3] -= k256;
        }
        if (j == 2 || j == 3) { h[j][0] = pack_h(kacc[j][0], kacc[j][2]); h[j][1] = pack_h(kacc[j][1], kacc[j][3]); }
        else if (j < 2) { h[j][0] = pack_h(kacc[j][0], kacc[j][1]); h[j][1] = pack_h(kacc[j][2], kacc[j][3]); }
      }
      {
        const bool sw = q >> 1;
        float v[4];
#pragma unroll
        for (int e = 0; e < 4; e++) v[e] = (sw ? kacc[5][e] : kacc[4][e]) + __shfl_xor_sync(0xffffffffu, sw ? kacc[4][e] : kacc[5][e], 2);
        h[4][0] = pack_h(v[0], v[1]); h[4][1] = pack_h(v[2], v[3]);
#pragma unroll
        for (int e = 0; e < 2; e++) {
          const uint32_t r = __shfl_xor_sync(0xffffffffu, sw ? h[2][e] : h[3][e], 2);
          if (sw) h[2][e] = r; else h[3][e] = r;
        }
      }
      fence_async_smem();
      bar_arrive(13, 192);
#pragma unroll
      for (int i = 0; i < 6; i++) sts128(pb + i * 512 + lane * 16, 0, 0, 0, 0);
      __syncwarp();
      {
        const int sw = g >> 2;
        const uint32_t sel = sw ? 0x1032 : 0x3210;
        const uint32_t a = pb + (P0 + 8 * g + ((0x3124 >> (4 * q)) & 7)) * 4, a0 = a + sw * 16, a1 = a + 16 - sw * 16;
        put2<1>(a0, a1, h[0][0], sel);
        put2<1>(a0 + 256, a1 + 256, h[0][1], sel);
        put2<1>(a0 + 512, a1 + 512, h[1][0], sel);
        put2<1>(lane == 28 ? pb + PB1 * 4 : a0 + 768, a1 + 768, h[1][1], sel);
      }
      {
        const int sw = q >> 1;
        const uint32_t sel = sw ? 0x1032 : 0x3210;
        uint32_t a = pb + (((q & 1) ? PA1 : PB1 + 1) + 32 * sw + 2 * g) * 4;
        put2<1>(a + sw * 64, a + 64 - sw * 64, h[2][0], sel);
        put2<1>(a + 4 + sw * 64, a + 68 - sw * 64, h[2][1], sel);
        const int s1 = q & 1;
        const uint32_t sel1 = s1 ? 0x1032 : 0x3210;
        a = pb + (PA2 + g + 16 * sw + 32 * s1) * 4;
        put2<2>(a + s1 * 32, a + 32 - s1 * 32, h[3][0], sel1);
        put2<2>(a + (PB2 - PA2) * 4 + s1 * 32, a + (PB2 - PA2) * 4 + 32 - s1 * 32, h[3][1], sel1);
        a = pb + (((g & 1) ? PB3 : PA3) + (g >> 1) + 8 * sw + 32 * s1) * 4;
        const uint32_t hx = s1 ? h[4][1] : h[4][0], hy = s1 ? h[4][0] : h[4][1];
        put2<1>(a + s1 * 16, a + 64 + s1 * 16, hx, 0x3210);
        put2<1>(a + 16 - s1 * 16, a + 80 - s1 * 16, hy, 0x3210);
      }
      if (lane == 30) put2<1>(pb + P0 * 4, pb + (PA1 + 64) * 4, __byte_perm(pack_h(k0n, 0.f), h[2][1], 0x7610), 0x3210);
      if (lane == 31) sts64(sb + OFF_CHC + kch * 8, (kex - 4) * 0x00800080u, __byte_perm(h[3][1], 0, 0x3232));
    }
    if (warp == 8) {
      bar_sync(13, 192);
      if (elect1()) {
        mbar_expect(bar + 8 * B_UFULL, 144 * 160);
        mbar_expect(bar + 8 * B_EPI, 1024 + 768);
        poll_cnt(cnt + C_LN * 32, ep * 128);
        tma2d(sb + OFF_U - 16 * 160, &tmU, wid * 80, -16, bar + 8 * B_UFULL);
        bulk_g2s(sb + OFF_STAT, p.scr->stats + rg1 * 128, 1024, bar + 8 * B_EPI);
      }
      __syncwarp();
    }
    const int wg = warp >> 2, role = (warp + 2 * wg) & 3;
    uint32_t co[6], cpa = (g - 2 * q) * 4;
    if (role < 2) {
#pragma unroll
      for (int gm = 0; gm < 3; gm++) {
        const int hb = 2 * (lane & 7) + role - 2 + gm, l3 = ((lane >> 3) ^ (hb >> 1)) & 7;
        co[2 * gm] = hb * 1280 + uoff(l3); co[2 * gm + 1] = hb * 1280 + uoff(l3 ^ 4);
      }
    } else {
      const int mi = lane >> 3, hf = (lane >> 2) & 1;
      co[0] = hf * 1792 + (mi ^ hf) * 64 + ((q ^ (mi >> 1) ^ (hf * 2)) << 4);
      co[1] = co[0] ^ 96;
      co[2] = (lane ^ (role == 2 ? (mi & 1) : ((lane >> 1) & 4))) << 4;
      co[3] = lane * 16;
      co[4] = (g >> 1) == q ? ((g & 1) ? 0xffff0000u : 0xffffu) : 0u;
      co[5] = 2 * cpa;
    }
    const uint32_t zero = lds32(sb + OFF_ZERO), nz = zero | 0x80000000u;
#pragma unroll
    for (int i = 0; i < 6; i++) co[i] = pin(co[i], zero);
    cpa = pin(cpa, zero);
    const Comb cmb = comb_setup(tid, zero);
    if (warp >= 10 && warp < 15) bar_sync(15, 160);
    const int qt = ((cw & 1) << 1) | ((cw >> 1) & 1), jz = qt * 32 + lane;
    uint32_t zo[12];
    {
      const int j = jz < 112 ? jz : jz - 128, gr = j >> 1;
      zo[0] = uoff(upos(max(2 * j - 2, -32))); zo[1] = zo[0] ^ 16; zo[2] = uoff(upos(2 * j)); zo[3] = zo[2] ^ 16; zo[4] = uoff(upos(2 * j + 2));
#pragma unroll
      for (int pp = 0; pp < 4; pp++) zo[5 + pp] = ZA1 + 512 + (gr ^ ((gr >> 2) & 1)) * 64 + ((((gr >> 1) & 3) ^ pp) << 4) + (j & 1) * 8;
      zo[9] = ((j >> 3) * 16 + (j & 7)) * 16;
      zo[10] = ((j >> 4) * 32 + (j & 15)) * 16;
      zo[11] = zo[10] + ((j & 15) == 15 ? 272 : 16);
#pragma unroll
      for (int i = 0; i < 12; i++) zo[i] = pin(zo[i], zero);
    }
    mbar_wait(bar + 8 * B_UFULL, 0);
#pragma unroll 1
    for (unsigned seq = (cw >> 2) ? 0xb9ac : 0x8; seq; seq >>= 4) {
      const int ch = seq & 7;
      if (ch == 1) bar_arrive(0, 256);
      if (ch < 4) mbar_wait(bar + 8 * (B_REL1 + (ch ? 8 : 7)), 0);
      const uint32_t ub = sb + OFF_U + ch * 32, zb = sb + OFF_Z + ch * ZSZ;
      uint32_t w_[20], o_[20], d_[20], b3_[20];
      uint32_t *w = w_ + 8, *o = o_ + 8, *d = d_ + 8, *b3 = b3_ + 8;
      {
        const uint4 c = lds128(ub + zo[2]), e = lds128(ub + zo[3]), b = lds128(ub + zo[1]);
        w[8] = lds32(ub + zo[4]);
        const uint2 a = lds64(ub + zo[0] + 8);
        w[-6] = a.x; w[-5] = a.y; w[-4] = b.x; w[-3] = b.y; w[-2] = b.z; w[-1] = b.w;
        w[0] = c.x; w[1] = c.y; w[2] = c.z; w[3] = c.w; w[4] = e.x; w[5] = e.y; w[6] = e.z; w[7] = e.w;
      }
#pragma unroll
      for (int i = -1; i <= 7; i++) o[i] = odd_pair(w[i], w[i + 1]);
#pragma unroll
      for (int i = 0; i <= 7; i++) { d[i] = hadd(w[i], o[i]); b3[i] = hadd(d[i], o[i - 1]); }
#pragma unroll
      for (int pp = 0; pp < 4; pp++) {
        const uint32_t sel = (pp & 1) ? 0x7632 : 0x5410;
        const int k = pp >> 1;
        sts64(zb + zo[5 + pp], __byte_perm(w[k - 1], w[k + 1], sel), __byte_perm(w[k + 3], w[k + 5], sel));
        sts64(zb + zo[5 + pp] + (ZB1 - ZA1), __byte_perm(b3[k], b3[k + 2], sel), __byte_perm(b3[k + 4], b3[k + 6], sel));
      }
      if (qt < 3) {
        uint32_t e_[20], b5_[20];
        uint32_t *e = e_ + 8, *b5 = b5_ + 8;
#pragma unroll
        for (int i = -6; i <= -2; i++) o[i] = odd_pair(w[i], w[i + 1]);
#pragma unroll
        for (int i = -6; i <= -1; i++) d[i] = hadd(w[i], o[i]);
#pragma unroll
        for (int i = -5; i <= -1; i++) b3[i] = hadd(d[i], o[i - 1]);
#pragma unroll
        for (int i = -5; i <= 4; i++) e[i] = hadd(d[i - 1], d[i]);
#pragma unroll
        for (int i = -4; i <= 4; i++) b5[i] = hadd(e[i], w[i + 1]);
        const uint32_t a2 = zb + zo[9];
        sts128(a2 + ZA2, b3[-2], b3[-1], b3[0], b3[1]);
        sts128(a2 + ZA2 + 128, b3[2], b3[3], b3[4], b3[5]);
        sts128(a2 + ZB2, b5[-4], b5[-3], b5[-2], b5[-1]);
        sts128(a2 + ZB2 + 128, b5[0], b5[1], b5[2], b5[3]);
        if (qt < 2) {
          sts128(a2 + ZS, d[-2], d[-1], d[0], d[1]);
          sts128(a2 + ZS + 128, d[2], d[3], d[4], d[5]);
          uint32_t b7[8], b9[8];
#pragma unroll
          for (int i = -4; i <= 3; i++) { b7[i + 4] = hadd(b3[i - 1], e[i + 1]); b9[i + 4] = hadd(e[i - 1], b5[i + 1]); }
          const uint32_t a3 = zb + zo[10];
          sts128(a3 + ZA3, b7[0], b7[1], b7[2], b7[3]);
          sts128(a3 + ZA3 + 256, b7[4], b7[5], b7[6], b7[7]);
          sts128(a3 + ZB3 + 256, b9[0], b9[1], b9[2], b9[3]);
          if (jz < 63) sts128(zb + zo[11] + ZB3, b9[4], b9[5], b9[6], b9[7]);
          else sts128(zb + ZB3, 0, 0, 0, 0);
        }
      }
    }
    bar_sync(wg == 2 ? 14 : 7, 384);
#pragma unroll 1
    for (int ch = wg - 2; ch < 5; ch += 2) {
      const uint32_t ub = sb + OFF_U + ch * 32, zb = sb + OFF_Z + ch * ZSZ, pb = sb + OFF_P + ch * 3072;
      if (ch == 2) bar_sync(0, 256);
      const uint32_t pa = pb + cpa;
      if (role < 2) {
        float acc[8][4];
#pragma unroll
        for (int r = 0; r < 8; r++) { acc[r][0] = acc[r][1] = acc[r][2] = acc[r][3] = 0.f; }
        float fix = 0.f;
        if (role == 1 && lane == 28) {
          const uint32_t k = lds32(pb + PB1 * 4), u0 = lds32(ub);
          fix = __low2float(*reinterpret_cast<const __half2*>(&k)) * __low2float(*reinterpret_cast<const __half2*>(&u0));
        }
        uint32_t b[12][4], A[17][4];
#pragma unroll
        for (int i = 11; i >= 8; i--) ldsm4(b[i], ub + (co[4 + (i & 1)] ^ (((i >> 1) & 1) * 16)) + ((i >> 1) & 1) * 640);
        A[0][0] = lds32(pa + P0 * 4); A[0][1] = lds32(pa + P0 * 4 + 32); A[0][2] = lds32(sb + OFF_ZERO + 4);
#pragma unroll
        for (int m = 0; m <= 16; m++) {
          if (m < 16) {
            A[m + 1][0] = lds32(pa + P0 * 4 + (2 * m + 2) * 32);
            A[m + 1][1] = m < 15 ? lds32(pa + P0 * 4 + (2 * m + 3) * 32) : lds32(sb + OFF_ZERO + 8);
          }
          if ((m & 1) == 0 && m < 16) {
            const int i = 7 - (m >> 1);
            ldsm4(b[i], ub + (co[2 * (i >> 2) + (i & 1)] ^ (((i >> 1) & 1) * 16)) + ((i >> 1) & 1) * 640);
          }
          if (m == 9 && elect1()) mbar_arrive(bar + 8 * (B_PAIR + ch));
          A[m][3] = dup(A[m][0], nz);
          if (m < 16) A[m + 1][2] = dup(A[m][1], nz);
#pragma unroll
          for (int r = 7; r >= 0; r--) {
            const int f = 16 + r - m;
            hmma(acc[r], A[m][0], A[m][1], A[m][2], A[m][3], b[f >> 1][(f & 1) * 2], b[f >> 1][(f & 1) * 2 + 1]);
          }
        }
        acc[7][2] += fix;
        mbar_wait(bar + 8 * (B_PAIR + ch), 0);
#pragma unroll
        for (int i = 3; i >= 0; i--)
          stsm4t(ub + (co[4 + (i & 1)] ^ (((i >> 1) & 1) * 16)) + ((i >> 1) & 1) * 640, pack_bf(acc[2 * i][0], acc[2 * i][1]), pack_bf(acc[2 * i][2], acc[2 * i][3]),
                 pack_bf(acc[2 * i + 1][0], acc[2 * i + 1][1]), pack_bf(acc[2 * i + 1][2], acc[2 * i + 1][3]));
      } else if (role == 2) {
        float acc[14][4];
#pragma unroll
        for (int r = 0; r < 14; r++) { acc[r][0] = acc[r][1] = acc[r][2] = acc[r][3] = 0.f; }
#pragma unroll
        for (int arr = 0; arr < 2; arr++) {
          uint32_t A[5][4];
#pragma unroll
          for (int m = 0; m < 5; m++) {
            A[m][0] = lds32(pa + (arr ? PB1 : PA1) * 4 + m * 64);
            A[m][1] = m < 4 ? lds32(pa + (arr ? PB1 : PA1) * 4 + m * 64 + 32) : lds32(sb + OFF_ZERO + 4 + arr * 8);
          }
#pragma unroll
          for (int m = 4; m >= 1; m--) { A[m][2] = dup(A[m - 1][1], nz); A[m][3] = dup(A[m][0], nz); }
          A[0][2] = lds32(sb + OFF_ZERO + 8 + arr * 8); A[0][3] = dup(A[0][0], nz);
#pragma unroll
          for (int ip = 0; ip < 9; ip++) {
            uint32_t b[4];
            ldsm4(b, zb + co[ip & 1] + (arr ? ZB1 : ZA1) + ip * 256);
#pragma unroll
            for (int hh = 0; hh < 2; hh++)
#pragma unroll
              for (int m = 0; m < 5; m++) {
                const int i = 2 * ip + hh - 4 + m;
                if (i >= 0 && i < 14) hmma(acc[i], A[m][0], A[m][1], A[m][2], A[m][3], b[2 * hh], b[2 * hh + 1]);
              }
          }
        }
        const uint32_t a = zb + ZA1 + 512 + co[2];
#pragma unroll
        for (int i = 0; i < 7; i++)
          stsm4(a + i * 512, pack_bf(acc[2 * i][0], acc[2 * i][1]), pack_bf(acc[2 * i][2], acc[2 * i][3]),
                pack_bf(acc[2 * i + 1][0], acc[2 * i + 1][1]), pack_bf(acc[2 * i + 1][2], acc[2 * i + 1][3]));
      } else {
        float acc[12][4];
        const uint32_t za = zb + co[3];
        {
          float d[4][2][4];
#pragma unroll
          for (int r = 0; r < 8; r++) { d[r >> 1][r & 1][0] = d[r >> 1][r & 1][1] = d[r >> 1][r & 1][2] = d[r >> 1][r & 1][3] = 0.f; }
#pragma unroll
          for (int arr = 0; arr < 2; arr++) {
            uint32_t A[4][4];
#pragma unroll
            for (int m = 0; m < 4; m++) { A[m][0] = lds32(pa + (arr ? PB3 : PA3) * 4 + m * 64); A[m][1] = lds32(pa + (arr ? PB3 : PA3) * 4 + m * 64 + 32); }
#pragma unroll
            for (int m = 0; m < 4; m++) { A[m][2] = m ? dup(A[m - 1][1], nz) : lds32(sb + OFF_ZERO + 4 + arr * 4); A[m][3] = dup(A[m][0], nz); }
#pragma unroll
            for (int io = 0; io < 4; io++) {
              uint32_t b[4];
              ldsm4t(b, za + (arr ? ZB3 : ZA3) + io * 512);
#pragma unroll
              for (int m = 0; m + io < 4; m++) {
                hmma(d[io + m][0], A[m][0], A[m][1], A[m][2], A[m][3], b[0], b[1]);
                hmma(d[io + m][1], A[m][0], A[m][1], A[m][2], A[m][3], b[2], b[3]);
              }
            }
          }
#pragma unroll
          for (int r = 0; r < 4; r++) {
            acc[r][0] = acc[r][1] = acc[r][2] = acc[r][3] = 0.f;
            acc[4 + 2 * r][0] = d[r][0][0]; acc[4 + 2 * r][1] = d[r][0][1]; acc[4 + 2 * r][2] = d[r][1][0]; acc[4 + 2 * r][3] = d[r][1][1];
            acc[5 + 2 * r][0] = d[r][0][2]; acc[5 + 2 * r][1] = d[r][0][3]; acc[5 + 2 * r][2] = d[r][1][2]; acc[5 + 2 * r][3] = d[r][1][3];
          }
        }
        {
          const uint32_t k0 = lds32(sb + OFF_CHC + ch * 8 + 4) & co[4];
          const uint32_t k1 = lds32(sb + OFF_ZERO + 12), k2 = lds32(sb + OFF_ZERO + 16), k3 = dup(k0, nz);
#pragma unroll
          for (int ip = 0; ip < 4; ip++) {
            uint32_t b[4];
            ldsm4t(b, za + ZS + ip * 512);
            hmma(acc[4 + 2 * ip], k0, k1, k2, k3, b[0], b[1]);
            hmma(acc[5 + 2 * ip], k0, k1, k2, k3, b[2], b[3]);
          }
        }
        const uint32_t pa2 = pb + co[5];
#pragma unroll
        for (int arr = 0; arr < 2; arr++) {
          uint32_t A[5][4];
#pragma unroll
          for (int m = 0; m < 5; m++) {
            const uint2 v = lds64(pa2 + (arr ? PB2 : PA2) * 4 + m * 64);
            A[m][0] = v.x; A[m][1] = v.y; A[m][2] = lds32(pa2 + (arr ? PB2 : PA2) * 4 + m * 64 - 4);
          }
#pragma unroll
          for (int m = 0; m < 5; m++) A[m][3] = dup(A[m][0], nz);
#pragma unroll
          for (int ip = 0; ip < 6; ip++) {
            uint32_t b[4];
            ldsm4t(b, za + (arr ? ZB2 : ZA2) + ip * 512);
#pragma unroll
            for (int hh = 0; hh < 2; hh++)
#pragma unroll
              for (int m = 0; m < 5; m++) {
                const int i = 2 * ip + hh + m;
                if (i < 12) hmma(acc[i], A[m][0], A[m][1], A[m][2], A[m][3], b[2 * hh], b[2 * hh + 1]);
              }
          }
        }
        const uint32_t a = zb + ZA2 + co[2];
#pragma unroll
        for (int i = 0; i < 6; i++)
          stsm4(a + i * 512, pack_bf(acc[2 * i][0], acc[2 * i][1]), pack_bf(acc[2 * i][2], acc[2 * i][3]),
                pack_bf(acc[2 * i + 1][0], acc[2 * i + 1][1]), pack_bf(acc[2 * i + 1][2], acc[2 * i + 1][3]));
      }
      __syncwarp();
      if (elect1()) mbar_arrive(bar + 8 * (B_PART + ch));
    }
    const uint4* srcA = p.scr->h + (rg1 * 24 + NS2 - 2) * 1024;
    const uint4* srcB = p.scr->w2p + (j1 * 24 + NS2 - 2) * 640;
    combine(cmb, 6 - wg, wid, p.scr->sT, [&] {
      if (warp == 12) {
        bar_sync(8, 512);
        if (elect1()) {
          asm volatile("fence.proxy.async.global;" ::: "memory");
          load2(NS2 - 2, sb + (NS2 - 2) * SLOT2, srcA, srcB);
          load2(NS2 - 1, sb + (NS2 - 1) * SLOT2, srcA + 1024, srcB + 640);
        }
        __syncwarp();
      } else bar_arrive(8, 512);
    });
    if (warp == 12) {
      if (elect1()) {
        uint32_t d = sb;
#pragma unroll 1
        for (int s = NS2; s < 24; s++) {
          mbar_wait(bar + 8 * (B_REL2 + s - NS2 + 1), 0);
          load2(s, d, srcA + 2048, srcB + 1280);
          srcA += 1024; srcB += 640;
          d = d == sb + (NS2 - 1) * SLOT2 ? sb : d + SLOT2;
        }
      }
      __syncwarp();
    } else if (warp == 13) {
      if (elect1()) {
#pragma unroll 1
        for (int c = 2; c < 5; c++) mbar_wait(bar + 8 * (B_FREE + c), 0);
        publish(cnt + (C_S + (wid >> 4)) * 32);
        mbar_expect(bar + 8 * B_SFULL, 20480);
        poll_cnt(cnt + (C_S + j1) * 32, ep * 16);
        mbar_wait(bar + 8 * (B_REL2 + SW), 0);
        bulk_g2s(sb + OFF_U, p.scr->sT + (j1 * 16 + rg1) * 1280, 20480, bar + 8 * B_SFULL);
      }
      __syncwarp();
    }
  }
}

typedef CUresult (*EncodeFn)(CUtensorMap*, CUtensorMapDataType, cuuint32_t, void*, const cuuint64_t*, const cuuint64_t*,
                             const cuuint32_t*, const cuuint32_t*, CUtensorMapInterleave, CUtensorMapSwizzle,
                             CUtensorMapL2promotion, CUtensorMapFloatOOBfill);

}

extern "C" void kernel_launch(void* const* d_in, const int* in_sizes, int n_in, void* d_out, int out_size) {
  static EncodeFn enc = nullptr;
  static int nsm = 0;
  static void* scr = nullptr;
  if (!enc) {
    void* fn = nullptr;
    cudaDriverEntryPointQueryResult qr;
    cudaGetDriverEntryPoint("cuTensorMapEncodeTiled", &fn, cudaEnableDefault, &qr);
    enc = (EncodeFn)fn;
    int dev = 0;
    cudaGetDevice(&dev);
    cudaDeviceGetAttribute(&nsm, cudaDevAttrMultiProcessorCount, dev);
    cudaFuncSetAttribute(fused_s4_ffn_kernel<true>, cudaFuncAttributeMaxDynamicSharedMemorySize, SMEM_BYTES);
    cudaFuncSetAttribute(fused_s4_ffn_kernel<false>, cudaFuncAttributeMaxDynamicSharedMemorySize, SMEM_BYTES);
    cudaGetSymbolAddress(&scr, g_scr);
  }
  Params p;
  p.x = (const __nv_bfloat16*)d_in[0];
  p.are = (const __nv_bfloat16*)d_in[1]; p.aim = (const __nv_bfloat16*)d_in[2];
  p.bre = (const __nv_bfloat16*)d_in[3]; p.bim = (const __nv_bfloat16*)d_in[4];
  p.cre = (const __nv_bfloat16*)d_in[5]; p.cim = (const __nv_bfloat16*)d_in[6];
  p.logdt = (const __nv_bfloat16*)d_in[7]; p.dskip = (const __nv_bfloat16*)d_in[8];
  p.w1 = (const __nv_bfloat16*)d_in[10]; p.w2 = (const __nv_bfloat16*)d_in[11];
  p.out = (__nv_bfloat16*)d_out;
  p.scr = (Scratch*)scr;
  CUtensorMap tmX, tmW1, tmU, tmW2;
  const cuuint32_t es[5] = {1, 1, 1, 1, 1};
  {
    const cuuint64_t gd[5] = {DM, 2, 4, 4, FF / 32}, gs[4] = {DM * 2, DM * 16, DM * 4, DM * 64};
    const cuuint32_t bx[5] = {88, 2, 4, 4, 3};
    enc(&tmW2, CU_TENSOR_MAP_DATA_TYPE_BFLOAT16, 5, d_in[11], gd, gs, bx, es, CU_TENSOR_MAP_INTERLEAVE_NONE,
        CU_TENSOR_MAP_SWIZZLE_NONE, CU_TENSOR_MAP_L2_PROMOTION_NONE, CU_TENSOR_MAP_FLOAT_OOB_FILL_NONE);
  }
  {
    const cuuint64_t gd[2] = {16 * DM, 128}, gs[1] = {DM * 32};
    const cuuint32_t bx[2] = {80, 144};
    enc(&tmU, CU_TENSOR_MAP_DATA_TYPE_FLOAT16, 2, p.scr->uT, gd, gs, bx, es, CU_TENSOR_MAP_INTERLEAVE_NONE,
        CU_TENSOR_MAP_SWIZZLE_NONE, CU_TENSOR_MAP_L2_PROMOTION_NONE, CU_TENSOR_MAP_FLOAT_OOB_FILL_NONE);
  }
  {
    const cuuint64_t gd[2] = {DM, SEQ}, gs[1] = {DM * 2};
    const cuuint32_t bx[2] = {64, 128};
    enc(&tmX, CU_TENSOR_MAP_DATA_TYPE_BFLOAT16, 2, d_in[0], gd, gs, bx, es, CU_TENSOR_MAP_INTERLEAVE_NONE,
        CU_TENSOR_MAP_SWIZZLE_128B, CU_TENSOR_MAP_L2_PROMOTION_L2_128B, CU_TENSOR_MAP_FLOAT_OOB_FILL_NONE);
  }
  {
    const cuuint64_t gd[3] = {64, DM, FF / 64}, gs[2] = {FF * 2, 128};
    const cuuint32_t bx[3] = {64, 64, 3};
    enc(&tmW1, CU_TENSOR_MAP_DATA_TYPE_BFLOAT16, 3, d_in[10], gd, gs, bx, es, CU_TENSOR_MAP_INTERLEAVE_NONE,
        CU_TENSOR_MAP_SWIZZLE_128B, CU_TENSOR_MAP_L2_PROMOTION_L2_128B, CU_TENSOR_MAP_FLOAT_OOB_FILL_NONE);
  }
  if (nsm == 132) fused_s4_ffn_kernel<true><<<132, 512, SMEM_BYTES>>>(p, tmX, tmW1, tmU, tmW2);
  else fused_s4_ffn_kernel<false><<<132, 512, SMEM_BYTES>>>(p, tmX, tmW1, tmU, tmW2);
}
```

```cpp
#include <cuda_runtime.h>
#include <cuda_bf16.h>
#include <cuda_fp16.h>
#include <cuda.h>
#include <stdint.h>

namespace {

constexpr int SEQ = 2048, DM = 640, FF = 1536;

constexpr int SLOT1 = 40960;
constexpr int SLOT2 = 26624;
constexpr int NS2 = 7;
#define LDLY 150
#define DELAY_NS 100
#define PACE_NS 60
#define SK2 21
constexpr int OFF_Z = 85504, ZSZ = 20480;
constexpr int ZA3 = 0, ZB3 = 2048, ZS = 4096, ZA2 = 6144, ZB2 = 9216, ZA1 = 12288, ZB1 = 16384;
constexpr int OFF_CMB = 2 * SLOT1;
constexpr int OFF_W2S = 3 * SLOT1;
constexpr int OFF_U = 190464;
constexpr int OFF_P = 210944;
constexpr int OFF_KS = 163840;
constexpr int OFF_LNP = 225280;
constexpr int OFF_MISC = 226304;
constexpr int OFF_CHC = OFF_MISC + 16;
constexpr int OFF_EP = OFF_MISC + 64;
constexpr int OFF_ZERO = OFF_MISC + 128;
constexpr int OFF_STAT = OFF_MISC + 1024;
constexpr int OFF_CS = OFF_MISC + 2048;
constexpr int OFF_BAR = OFF_MISC + 2816;
constexpr int SMEM_BYTES = OFF_MISC + 6144;
constexpr int P0 = 8, PA1 = 280, PB1 = 360, PA2 = 448, PB2 = 544, PA3 = 632, PB3 = 704;
enum { B_W2 = 0, B_FULL1 = 1, B_FULL2 = 11, B_UFULL = 35, B_EPI = 36, B_SFULL = 37,
       B_PAIR = 42,
       B_FREE = 48, B_PART = 54,
       B_REL1 = 60, B_REL2 = 70 };
enum { C_LN = 0, C_H0 = 2, C_H1 = 18, C_S = 34, C_CS = 42, C_NUM = 46 };

struct Scratch {
  unsigned cnt[64 * 32];
  unsigned epoch[256];
  float2 stats[SEQ];
  float cs[FF];
  uint4 uT[DM * 256];
  uint4 w2p[8 * 24 * 640];
  uint4 sT[8 * 16 * 1280];
  uint4 h[16 * 24 * 1024];
};
__device__ __align__(1024) Scratch g_scr;
constexpr uint32_t sb = 1024;
constexpr uint32_t bar = sb + OFF_BAR;

struct Params {
  const __nv_bfloat16 *are, *aim, *bre, *bim, *cre, *cim, *logdt, *dskip, *x, *w1, *w2;
  __nv_bfloat16* out;
  Scratch* scr;
};

__device__ __forceinline__ void mbar_init(uint32_t a, int c) { asm volatile("mbarrier.init.shared::cta.b64 [%0], %1;" ::"r"(a), "r"(c)); }
__device__ __forceinline__ void mbar_expect(uint32_t a, int b) { asm volatile("mbarrier.arrive.expect_tx.shared::cta.b64 _, [%0], %1;" ::"r"(a), "r"(b) : "memory"); }
__device__ __forceinline__ void mbar_arrive(uint32_t a) { asm volatile("mbarrier.arrive.shared::cta.b64 _, [%0];" ::"r"(a) : "memory"); }
__device__ __forceinline__ void mbar_wait(uint32_t a, int ph) {
  asm volatile(
      "{\n.reg .pred p;\n.reg .u32 n;\n"
      "mbarrier.try_wait.parity.shared::cta.b64 p, [%0], %1;\n@p bra LD;\nmov.u32 n, 0;\n"
      "LW:\nmbarrier.try_wait.parity.shared::cta.b64 p, [%0], %1, 20000;\n@p bra LD;\n"
      "add.u32 n, n, 1;\nsetp.lt.u32 p, n, 100000;\n@p bra LW;\ntrap;\nLD:\n}\n" ::"r"(a), "r"(ph) : "memory");
}
__device__ __forceinline__ void poll_cnt(const unsigned* p, unsigned target) {
  asm volatile(
      "{\n.reg .pred p;\n.reg .u32 n;\n.reg .s32 v;\nmov.u32 n, 0;\n"
      "LW:\nld.relaxed.gpu.global.u32 v, [%0];\nsub.s32 v, v, %1;\nsetp.ge.s32 p, v, 0;\n@p bra LD;\n"
      "nanosleep.u32 64;\nadd.u32 n, n, 1;\nsetp.lt.u32 p, n, 4000000;\n@p bra LW;\ntrap;\n"
      "LD:\nfence.acquire.gpu;\nfence.proxy.async.global;\n}\n" ::"l"(p), "r"(target) : "memory");
}
__device__ __forceinline__ void publish(unsigned* p) {
  asm volatile("fence.proxy.async.global;\nfence.release.gpu;\nred.relaxed.gpu.global.add.u32 [%0], 1;" ::"l"(p) : "memory");
}
__device__ __forceinline__ uint32_t movm(uint32_t v) { uint32_t r; asm volatile("movmatrix.sync.aligned.m8n8.trans.b16 %0, %1;" : "=r"(r) : "r"(v)); return r; }
__device__ __forceinline__ void fence_async_smem() { asm volatile("fence.proxy.async.shared::cta;" ::: "memory"); }
__device__ __forceinline__ bool elect1() { uint32_t p; asm volatile("{\n.reg .pred P;\nelect.sync _|P, 0xffffffff;\nselp.u32 %0,1,0,P;\n}\n" : "=r"(p)); return p; }
__device__ __forceinline__ void bar_sync(int id, int n) { asm volatile("bar.sync %0, %1;" ::"r"(id), "r"(n) : "memory"); }
__device__ __forceinline__ void bar_arrive(int id, int n) { asm volatile("bar.arrive %0, %1;" ::"r"(id), "r"(n) : "memory"); }
__device__ __forceinline__ void bulk_g2s(uint32_t dst, const void* src, int bytes, uint32_t mb) {
  asm volatile("cp.async.bulk.shared::cluster.global.mbarrier::complete_tx::bytes [%0], [%1], %2, [%3];" ::"r"(dst), "l"(src), "r"(bytes), "r"(mb) : "memory");
}
__device__ __forceinline__ void bulk_prefetch(const void* src, int bytes) { asm volatile("cp.async.bulk.prefetch.L2.global [%0], %1;" ::"l"(src), "r"(bytes) : "memory"); }
__device__ __forceinline__ void tma2d(uint32_t dst, const CUtensorMap* m, int c0, int c1, uint32_t mb) {
  asm volatile("cp.async.bulk.tensor.2d.shared::cluster.global.mbarrier::complete_tx::bytes [%0], [%1, {%3, %4}], [%2];" ::"r"(dst), "l"(m), "r"(mb), "r"(c0), "r"(c1) : "memory");
}
__device__ __forceinline__ void tma3d(uint32_t dst, const CUtensorMap* m, int c0, int c1, int c2, uint32_t mb) {
  asm volatile("cp.async.bulk.tensor.3d.shared::cluster.global.mbarrier::complete_tx::bytes [%0], [%1, {%3, %4, %5}], [%2];" ::"r"(dst), "l"(m), "r"(mb), "r"(c0), "r"(c1), "r"(c2) : "memory");
}
__device__ __forceinline__ unsigned frag_col(unsigned l) { return (l & 0x61) | ((l & 6) << (2 - (l >> 6))) | ((l >> 2) & 6); }
__device__ __forceinline__ void tma5d(uint32_t dst, const CUtensorMap* m, int c0, int c4, uint32_t mb) {
  asm volatile("cp.async.bulk.tensor.5d.shared::cluster.global.mbarrier::complete_tx::bytes [%0], [%1, {%3, %5, %5, %5, %4}], [%2];" ::"r"(dst), "l"(m), "r"(mb), "r"(c0), "r"(c4), "r"(0) : "memory");
}
__device__ __forceinline__ uint64_t dsc(uint32_t lo, uint32_t hi) { return ((uint64_t)hi << 32) | lo; }
__device__ __forceinline__ void wg_fence() { asm volatile("wgmma.fence.sync.aligned;" ::: "memory"); }
__device__ __forceinline__ void wg_commit() { asm volatile("wgmma.commit_group.sync.aligned;" ::: "memory"); }
template <int N> __device__ __forceinline__ void wg_wait() { asm volatile("wgmma.wait_group.sync.aligned %0;" ::"n"(N) : "memory"); }
__device__ __forceinline__ void wgmma_n192(float (&d)[96], uint64_t da, uint64_t db, int scale_d) {
  asm volatile("{\n.reg .pred p;\nsetp.ne.b32 p, %98, 0;\n"
    "wgmma.mma_async.sync.aligned.m64n192k16.f32.bf16.bf16 "
    "{"
    "%0, %1, %2, %3, %4, %5, %6, %7, %8, %9, %10, %11, %12, %13, %14, %15, "
    "%16, %17, %18, %19, %20, %21, %22, %23, %24, %25, %26, %27, %28, %29, %30, %31, "
    "%32, %33, %34, %35, %36, %37, %38, %39, %40, %41, %42, %43, %44, %45, %46, %47, "
    "%48, %49, %50, %51, %52, %53, %54, %55, %56, %57, %58, %59, %60, %61, %62, %63, "
    "%64, %65, %66, %67, %68, %69, %70, %71, %72, %73, %74, %75, %76, %77, %78, %79, "
    "%80, %81, %82, %83, %84, %85, %86, %87, %88, %89, %90, %91, %92, %93, %94, %95"
    "}, "
    "%96, %97, p, 1, 1, 0, 1;\n}\n"
    : "+f"(d[0]), "+f"(d[1]), "+f"(d[2]), "+f"(d[3]), "+f"(d[4]), "+f"(d[5]), "+f"(d[6]), "+f"(d[7]),
      "+f"(d[8]), "+f"(d[9]), "+f"(d[10]), "+f"(d[11]), "+f"(d[12]), "+f"(d[13]), "+f"(d[14]), "+f"(d[15]),
      "+f"(d[16]), "+f"(d[17]), "+f"(d[18]), "+f"(d[19]), "+f"(d[20]), "+f"(d[21]), "+f"(d[22]), "+f"(d[23]),
      "+f"(d[24]), "+f"(d[25]), "+f"(d[26]), "+f"(d[27]), "+f"(d[28]), "+f"(d[29]), "+f"(d[30]), "+f"(d[31]),
      "+f"(d[32]), "+f"(d[33]), "+f"(d[34]), "+f"(d[35]), "+f"(d[36]), "+f"(d[37]), "+f"(d[38]), "+f"(d[39]),
      "+f"(d[40]), "+f"(d[41]), "+f"(d[42]), "+f"(d[43]), "+f"(d[44]), "+f"(d[45]), "+f"(d[46]), "+f"(d[47]),
      "+f"(d[48]), "+f"(d[49]), "+f"(d[50]), "+f"(d[51]), "+f"(d[52]), "+f"(d[53]), "+f"(d[54]), "+f"(d[55]),
      "+f"(d[56]), "+f"(d[57]), "+f"(d[58]), "+f"(d[59]), "+f"(d[60]), "+f"(d[61]), "+f"(d[62]), "+f"(d[63]),
      "+f"(d[64]), "+f"(d[65]), "+f"(d[66]), "+f"(d[67]), "+f"(d[68]), "+f"(d[69]), "+f"(d[70]), "+f"(d[71]),
      "+f"(d[72]), "+f"(d[73]), "+f"(d[74]), "+f"(d[75]), "+f"(d[76]), "+f"(d[77]), "+f"(d[78]), "+f"(d[79]),
      "+f"(d[80]), "+f"(d[81]), "+f"(d[82]), "+f"(d[83]), "+f"(d[84]), "+f"(d[85]), "+f"(d[86]), "+f"(d[87]),
      "+f"(d[88]), "+f"(d[89]), "+f"(d[90]), "+f"(d[91]), "+f"(d[92]), "+f"(d[93]), "+f"(d[94]), "+f"(d[95])
    : "l"(da), "l"(db), "r"(scale_d));
}

__device__ __forceinline__ void wgmma_n80(float (&d)[40], uint64_t da, uint64_t db, int scale_d) {
  asm volatile("{\n.reg .pred p;\nsetp.ne.b32 p, %42, 0;\n"
    "wgmma.mma_async.sync.aligned.m64n80k16.f32.bf16.bf16 "
    "{"
    "%0, %1, %2, %3, %4, %5, %6, %7, %8, %9, %10, %11, %12, %13, %14, %15, "
    "%16, %17, %18, %19, %20, %21, %22, %23, %24, %25, %26, %27, %28, %29, %30, %31, "
    "%32, %33, %34, %35, %36, %37, %38, %39"
    "}, "
    "%40, %41, p, 1, 1, 0, 1;\n}\n"
    : "+f"(d[0]), "+f"(d[1]), "+f"(d[2]), "+f"(d[3]), "+f"(d[4]), "+f"(d[5]), "+f"(d[6]), "+f"(d[7]),
      "+f"(d[8]), "+f"(d[9]), "+f"(d[10]), "+f"(d[11]), "+f"(d[12]), "+f"(d[13]), "+f"(d[14]), "+f"(d[15]),
      "+f"(d[16]), "+f"(d[17]), "+f"(d[18]), "+f"(d[19]), "+f"(d[20]), "+f"(d[21]), "+f"(d[22]), "+f"(d[23]),
      "+f"(d[24]), "+f"(d[25]), "+f"(d[26]), "+f"(d[27]), "+f"(d[28]), "+f"(d[29]), "+f"(d[30]), "+f"(d[31]),
      "+f"(d[32]), "+f"(d[33]), "+f"(d[34]), "+f"(d[35]), "+f"(d[36]), "+f"(d[37]), "+f"(d[38]), "+f"(d[39])
    : "l"(da), "l"(db), "r"(scale_d));
}

__device__ __forceinline__ void hmma(float* c, uint32_t a0, uint32_t a1, uint32_t a2, uint32_t a3, uint32_t b0, uint32_t b1) {
  asm volatile("mma.sync.aligned.m16n8k16.row.col.f32.f16.f16.f32 {%0,%1,%2,%3}, {%4,%5,%6,%7}, {%8,%9}, {%0,%1,%2,%3};"
      : "+f"(c[0]), "+f"(c[1]), "+f"(c[2]), "+f"(c[3]) : "r"(a0), "r"(a1), "r"(a2), "r"(a3), "r"(b0), "r"(b1));
}
__device__ __forceinline__ void ldsm4(uint32_t* r, uint32_t a) { asm volatile("ldmatrix.sync.aligned.m8n8.x4.shared.b16 {%0,%1,%2,%3}, [%4];" : "=r"(r[0]), "=r"(r[1]), "=r"(r[2]), "=r"(r[3]) : "r"(a) : "memory"); }
__device__ __forceinline__ void ldsm4t(uint32_t* r, uint32_t a) { asm volatile("ldmatrix.sync.aligned.m8n8.x4.trans.shared.b16 {%0,%1,%2,%3}, [%4];" : "=r"(r[0]), "=r"(r[1]), "=r"(r[2]), "=r"(r[3]) : "r"(a) : "memory"); }
__device__ __forceinline__ void stsm4(uint32_t a, uint32_t r0, uint32_t r1, uint32_t r2, uint32_t r3) { asm volatile("stmatrix.sync.aligned.m8n8.x4.shared.b16 [%0], {%1,%2,%3,%4};" ::"r"(a), "r"(r0), "r"(r1), "r"(r2), "r"(r3) : "memory"); }
__device__ __forceinline__ void stsm4t(uint32_t a, uint32_t r0, uint32_t r1, uint32_t r2, uint32_t r3) { asm volatile("stmatrix.sync.aligned.m8n8.x4.trans.shared.b16 [%0], {%1,%2,%3,%4};" ::"r"(a), "r"(r0), "r"(r1), "r"(r2), "r"(r3) : "memory"); }
__device__ __forceinline__ uint32_t lds32(uint32_t a) { uint32_t v; asm volatile("ld.shared.u32 %0, [%1];" : "=r"(v) : "r"(a) : "memory"); return v; }
__device__ __forceinline__ uint2 lds64(uint32_t a) { uint2 v; asm volatile("ld.shared.v2.u32 {%0,%1}, [%2];" : "=r"(v.x), "=r"(v.y) : "r"(a) : "memory"); return v; }
__device__ __forceinline__ uint4 lds128(uint32_t a) { uint4 v; asm volatile("ld.shared.v4.u32 {%0,%1,%2,%3}, [%4];" : "=r"(v.x), "=r"(v.y), "=r"(v.z), "=r"(v.w) : "r"(a) : "memory"); return v; }
__device__ __forceinline__ void sts16(uint32_t a, uint32_t v) { asm volatile("st.shared.u16 [%0], %1;" ::"r"(a), "h"((unsigned short)v) : "memory"); }
__device__ __forceinline__ void sts32(uint32_t a, uint32_t v) { asm volatile("st.shared.u32 [%0], %1;" ::"r"(a), "r"(v) : "memory"); }
__device__ __forceinline__ void sts64(uint32_t a, uint32_t x, uint32_t y) { asm volatile("st.shared.v2.u32 [%0], {%1,%2};" ::"r"(a), "r"(x), "r"(y) : "memory"); }
__device__ __forceinline__ void sts128(uint32_t a, uint32_t x, uint32_t y, uint32_t z, uint32_t w) { asm volatile("st.shared.v4.u32 [%0], {%1,%2,%3,%4};" ::"r"(a), "r"(x), "r"(y), "r"(z), "r"(w) : "memory"); }
__device__ __forceinline__ uint32_t ldg32(const void* a) { uint32_t v; asm volatile("ld.global.nc.u32 %0, [%1];" : "=r"(v) : "l"(a)); return v; }
__device__ __forceinline__ uint32_t ldg16(const void* a) { uint32_t v; asm volatile("ld.global.nc.u16 %0, [%1];" : "=r"(v) : "l"(a)); return v; }
__device__ __forceinline__ float bflo(uint32_t v) { return __uint_as_float(v << 16); }
__device__ __forceinline__ float bfhi(uint32_t v) { return __uint_as_float(v & 0xffff0000u); }
__device__ __forceinline__ uint32_t pack_bf(float lo, float hi) { uint32_t r; asm("cvt.rn.bf16x2.f32 %0, %1, %2;" : "=r"(r) : "f"(hi), "f"(lo)); return r; }
__device__ __forceinline__ uint32_t pack_h(float lo, float hi) { uint32_t r; asm("cvt.rn.f16x2.f32 %0, %1, %2;" : "=r"(r) : "f"(hi), "f"(lo)); return r; }
__device__ __forceinline__ float rnd_bf(float v) { return __bfloat162float(__float2bfloat16_rn(v)); }
__device__ __forceinline__ float ex2a(float v) { float r; asm("ex2.approx.ftz.f32 %0, %1;" : "=f"(r) : "f"(v)); return r; }
__device__ __forceinline__ float tanha(float v) { float r; asm("tanh.approx.f32 %0, %1;" : "=f"(r) : "f"(v)); return r; }
__device__ __forceinline__ uint32_t hadd(uint32_t a, uint32_t b) { uint32_t r; asm("add.rn.f16x2 %0, %1, %2;" : "=r"(r) : "r"(a), "r"(b)); return r; }
__device__ __forceinline__ uint32_t badd(uint32_t a, uint32_t b) { uint32_t r; asm("add.rn.bf16x2 %0, %1, %2;" : "=r"(r) : "r"(a), "r"(b)); return r; }
__device__ __forceinline__ uint32_t bmul(uint32_t a, uint32_t b) { uint32_t r; asm("mul.rn.bf16x2 %0, %1, %2;" : "=r"(r) : "r"(a), "r"(b)); return r; }
__device__ __forceinline__ uint32_t bfma(uint32_t a, uint32_t b, uint32_t c) { uint32_t r; asm("fma.rn.bf16x2 %0, %1, %2, %3;" : "=r"(r) : "r"(a), "r"(b), "r"(c)); return r; }
__device__ __forceinline__ float tanhv(float v) { float r; asm volatile("tanh.approx.f32 %0, %1;" : "=f"(r) : "f"(v)); return r; }
__device__ __forceinline__ uint32_t bsub(uint32_t a, uint32_t b) { uint32_t r; asm("sub.rn.bf16x2 %0, %1, %2;" : "=r"(r) : "r"(a), "r"(b)); return r; }
__device__ __forceinline__ uint32_t dup(uint32_t v, uint32_t nz) { uint32_t r; asm volatile("add.rn.f32 %0, %1, %2;" : "=r"(r) : "r"(v), "r"(nz)); return r; }
__device__ __forceinline__ void bmma(float* c, uint32_t a0, uint32_t a1, uint32_t a2, uint32_t a3, uint32_t b0, uint32_t b1) {
  asm("mma.sync.aligned.m16n8k16.row.col.f32.bf16.bf16.f32 {%0,%1,%2,%3}, {%4,%5,%6,%7}, {%8,%9}, {%0,%1,%2,%3};"
      : "+f"(c[0]), "+f"(c[1]), "+f"(c[2]), "+f"(c[3]) : "r"(a0), "r"(a1), "r"(a2), "r"(a3), "r"(b0), "r"(b1));
}
__device__ __forceinline__ uint32_t odd_pair(uint32_t a, uint32_t b) { return __byte_perm(a, b, 0x5432); }
__device__ __forceinline__ int upos(int c) { return c ^ ((c >> 5) & 7) ^ ((c >> 3) & 1); }
__device__ __forceinline__ int uoff(int pos) { return (pos >> 1) * 160 + (pos & 1) * 16; }

struct cf { float r, i; };
__device__ __forceinline__ cf cmul(cf a, cf b) { cf o; o.r = fmaf(a.r, b.r, -a.i * b.i); o.i = fmaf(a.r, b.i, a.i * b.r); return o; }
__device__ __forceinline__ cf cmulj(cf a, cf b) { cf o; o.r = fmaf(a.r, b.r, a.i * b.i); o.i = fmaf(a.i, b.r, -a.r * b.i); return o; }
__device__ __forceinline__ cf csq(cf a) { cf o; o.r = fmaf(a.r, a.r, -a.i * a.i); o.i = (a.r + a.r) * a.i; return o; }
struct hp { uint32_t r, i; };
__device__ __forceinline__ hp hpack(cf a, cf b) { hp o; o.r = pack_h(a.r, b.r); o.i = pack_h(a.i, b.i); return o; }
__device__ __forceinline__ hp hmulc(hp a, uint32_t c) {
  __half2 ar = *reinterpret_cast<__half2*>(&a.r), ai = *reinterpret_cast<__half2*>(&a.i), cc = *reinterpret_cast<__half2*>(&c);
  __half2 orr = __hfma2(ar, __low2half2(cc), __hneg2(__hmul2(ai, __high2half2(cc))));
  __half2 oi = __hfma2(ar, __high2half2(cc), __hmul2(ai, __low2half2(cc)));
  hp o; o.r = *reinterpret_cast<uint32_t*>(&orr); o.i = *reinterpret_cast<uint32_t*>(&oi); return o;
}
__device__ __forceinline__ hp hmulj(hp a, uint32_t c) {
  __half2 ar = *reinterpret_cast<__half2*>(&a.r), ai = *reinterpret_cast<__half2*>(&a.i), cc = *reinterpret_cast<__half2*>(&c);
  __half2 orr = __hfma2(ar, __low2half2(cc), __hmul2(ai, __high2half2(cc)));
  __half2 oi = __hfma2(ai, __low2half2(cc), __hneg2(__hmul2(ar, __high2half2(cc))));
  hp o; o.r = *reinterpret_cast<uint32_t*>(&orr); o.i = *reinterpret_cast<uint32_t*>(&oi); return o;
}
__device__ __forceinline__ hp hmule(hp a, hp b) {
  __half2 ar = *reinterpret_cast<__half2*>(&a.r), ai = *reinterpret_cast<__half2*>(&a.i);
  __half2 br = *reinterpret_cast<__half2*>(&b.r), bi = *reinterpret_cast<__half2*>(&b.i);
  __half2 orr = __hfma2(ar, br, __hneg2(__hmul2(ai, bi))), oi = __hfma2(ar, bi, __hmul2(ai, br));
  hp o; o.r = *reinterpret_cast<uint32_t*>(&orr); o.i = *reinterpret_cast<uint32_t*>(&oi); return o;
}
__device__ __forceinline__ void sts_tile(uint32_t a, const hp* t) {
  sts128(a, t[0].r, t[1].r, t[2].r, t[3].r);
  sts128(a + 512, t[0].i, t[1].i, t[2].i, t[3].i);
}
template <int STEP> __device__ __forceinline__ void put2(uint32_t a0, uint32_t a1, uint32_t h, uint32_t sel) {
  const uint32_t x = __byte_perm(h, h, sel), y = x >> 16;
  sts16(a0, x); sts16(a0 + STEP * 4 + 2, x);
  sts16(a1, y); sts16(a1 + STEP * 4 + 2, y);
}

__device__ __forceinline__ void spare_work(const Params& p, const CUtensorMap* tmW1, int k, int tid) {
  const int lane = tid & 31;
  unsigned ep = 0;
  if (tid >= 480) ep = p.scr->epoch[128 + k] + 1;
  if (tid == 480) {
    for (int i = 0; i < 8; i++) mbar_init(bar + 8 * i, i < 4 ? 1 : 12);
    asm volatile("fence.mbarrier_init.release.cluster;" ::: "memory");
    fence_async_smem();
  }
  __syncthreads();
  float a[2][4] = {{0.f, 0.f, 0.f, 0.f}, {0.f, 0.f, 0.f, 0.f}};
  if (tid >= 480) {
    if (elect1()) {
#pragma unroll 1
      for (int s = 0; s < 10; s++) {
        mbar_wait(bar + 8 * (4 + (s & 3)), ((s >> 2) & 1) ^ 1);
        mbar_expect(bar + 8 * (s & 3), 49152);
#pragma unroll 1
        for (int b = 0; b < 2; b++) tma3d(sb + (s & 3) * 49152 + b * 24576, tmW1, 0, s * 64, k * 6 + b * 3, bar + 8 * (s & 3));
      }
    }
    __syncwarp();
  } else if (tid < 384) {
    const uint32_t idn = (lane >> 3) == (lane & 3) ? ((lane & 4) ? 0x3f800000u : 0x3f80u) : 0u;
#pragma unroll 1
    for (int s = 0; s < 10; s++) {
      mbar_wait(bar + 8 * (s & 3), (s >> 2) & 1);
      const uint32_t ad = sb + (s & 3) * 49152 + (tid >> 6) * 8192 + (tid & 63) * 16;
#pragma unroll
      for (int i = 0; i < 8; i += 2) {
        const uint4 v = lds128(ad + i * 1024), w = lds128(ad + i * 1024 + 1024);
        bmma(a[0], v.x, v.y, w.x, w.y, idn, idn);
        bmma(a[1], v.z, v.w, w.z, w.w, idn, idn);
      }
      __syncwarp();
      if (lane == 0) mbar_arrive(bar + 8 * (4 + (s & 3)));
    }
#pragma unroll
    for (int e = 0; e < 8; e++) {
      float v = a[e >> 2][e & 3];
      v += __shfl_xor_sync(0xffffffffu, v, 9);
      v += __shfl_xor_sync(0xffffffffu, v, 18);
      a[e >> 2][e & 3] = v;
    }
    const int odd = (tid >> 5) & 1, c8 = (tid >> 6) * 8 + ((lane & 7) ^ (odd * 4));
    if (odd && lane < 8) {
      sts128(sb + 196608 + c8 * 32, __float_as_uint(a[0][0]), __float_as_uint(a[0][1]), __float_as_uint(a[0][2]), __float_as_uint(a[0][3]));
      sts128(sb + 196608 + c8 * 32 + 16, __float_as_uint(a[1][0]), __float_as_uint(a[1][1]), __float_as_uint(a[1][2]), __float_as_uint(a[1][3]));
    }
    bar_sync(1 + (tid >> 6), 64);
    if (!odd && lane < 8) {
      const uint4 v = lds128(sb + 196608 + c8 * 32), w = lds128(sb + 196608 + c8 * 32 + 16);
      float2* dst = (float2*)(p.scr->cs + k * 384 + (c8 >> 2) * 32) + (c8 & 3);
      dst[0] = make_float2(a[0][0] + __uint_as_float(v.x), a[0][1] + __uint_as_float(v.y));
      dst[4] = make_float2(a[0][2] + __uint_as_float(v.z), a[0][3] + __uint_as_float(v.w));
      dst[8] = make_float2(a[1][0] + __uint_as_float(w.x), a[1][1] + __uint_as_float(w.y));
      dst[12] = make_float2(a[1][2] + __uint_as_float(w.z), a[1][3] + __uint_as_float(w.w));
    }
  }
  __syncthreads();
  if (tid == 480) {
    publish(p.scr->cnt + (C_CS + k) * 32);
    p.scr->epoch[128 + k] = ep;
    poll_cnt(p.scr->cnt + C_LN * 32, ep * 128);
  }
}

__device__ __forceinline__ void load1(int s, const CUtensorMap* tmX, const CUtensorMap* tmW1, int rg1, int j1) {
  const uint32_t d = sb + (s & 3) * SLOT1, mb = bar + 8 * (B_FULL1 + s);
  mbar_expect(mb, SLOT1);
  tma2d(d, tmX, s * 64, rg1 * 128, mb);
  tma3d(d + 16384, tmW1, 0, s * 64, j1 * 3, mb);
}
__device__ __forceinline__ void load_x(uint32_t (&xv)[2][10], const __nv_bfloat16* xa, const __nv_bfloat16* xb, int rstep) {
#pragma unroll
  for (int r = 0; r < 2; r++) {
    const uint4 a = __ldg((const uint4*)(xa + r * rstep)), b = __ldg((const uint4*)(xa + r * rstep + 32));
    const uint2 c = __ldg((const uint2*)(xb + r * rstep + 64));
    xv[r][0] = a.x; xv[r][1] = a.y; xv[r][2] = a.z; xv[r][3] = a.w; xv[r][4] = b.x; xv[r][5] = b.y; xv[r][6] = b.z; xv[r][7] = b.w;
    xv[r][8] = c.x; xv[r][9] = c.y;
  }
}

__device__ __forceinline__ uint32_t pin(uint32_t v, uint32_t z) { uint32_t r; asm volatile("add.u32 %0, %1, %2;" : "=r"(r) : "r"(v), "r"(z)); return r; }
struct Comb { uint32_t o[7]; };
__device__ __forceinline__ Comb comb_setup(int tid, uint32_t z) {
  Comb k;
  const int c = tid & 127, c1 = c < 112 ? c + 32 : c - 112, c2 = c < 112 ? c + 144 : c - 96;
  const uint32_t zr = ZA1 + (c & 7) * 16, a2 = ZA2 + ((c & ~15) - 32 + ((((c >> 1) & 7) + (c & 1) * 8) ^ ((c & 1) * 4))) * 16;
  k.o[0] = uoff(upos(c1)); k.o[1] = uoff(upos(c2));
  k.o[2] = c < 112 ? ZA1 + 512 + ((2 * c) ^ ((c >> 2) & 1)) * 16 : zr;
  k.o[3] = c1 >= 64 ? a2 : zr; k.o[4] = c < 112 ? a2 + 112 * 16 : zr;
  k.o[5] = ((c1 >> 4) * 1280 + (c & 15)) * 16; k.o[6] = ((c2 >> 4) * 1280 + (c & 15)) * 16;
#pragma unroll
  for (int i = 0; i < 7; i++) k.o[i] = pin(k.o[i], z);
  return k;
}
template <class F> __device__ __forceinline__ void combine(const Comb& k, int ch, int wid, uint4* sT, F&& after_reads) {
  const uint32_t ub = sb + OFF_U + ch * 32, zb = sb + OFF_Z + ch * ZSZ;
  const int row = (wid & 15) * 5 + ch;
  char* dst = (char*)(sT + ((wid >> 4) * 16 * 80 + row) * 16);
  mbar_wait(bar + 8 * (B_PART + ch), 0);
  const uint32_t sc = lds32(sb + OFF_CHC + ch * 8);
  const uint4 y0 = lds128(zb + k.o[2]), y1 = lds128(zb + (k.o[2] ^ 16));
  const uint4 v2 = lds128(zb + k.o[3]), u2 = lds128(zb + k.o[4]);
  const uint4 v0 = lds128(ub + k.o[0]), u0 = lds128(ub + k.o[1]);
  fence_async_smem();
  after_reads();
  *(uint4*)(dst + (k.o[5] ^ ((row & 7) * 16))) =
      make_uint4(bmul(badd(badd(y0.x, v2.x), v0.x), sc), bmul(badd(badd(y0.y, v2.y), v0.y), sc),
                 bmul(badd(badd(y1.x, v2.z), v0.z), sc), bmul(badd(badd(y1.y, v2.w), v0.w), sc));
  *(uint4*)(dst + (k.o[6] ^ ((row & 7) * 16))) =
      make_uint4(bmul(badd(badd(y0.z, u2.x), u0.x), sc), bmul(badd(badd(y0.w, u2.y), u0.y), sc),
                 bmul(badd(badd(y1.z, u2.z), u0.z), sc), bmul(badd(badd(y1.w, u2.w), u0.w), sc));
  __syncwarp();
  if (elect1()) mbar_arrive(bar + 8 * (B_FREE + ch));
}

__device__ __forceinline__ void load2(int s, uint32_t d, const uint4* srcA, const uint4* srcB) {
  const uint32_t mb = bar + 8 * (B_FULL2 + s);
  mbar_expect(mb, SLOT2);
  bulk_g2s(d, srcA, 16384, mb);
  bulk_g2s(d + 16384, srcB, 10240, mb);
}

template <bool USE_SMID>
__global__ void __launch_bounds__(512, 1)
fused_s4_ffn_kernel(const Params p, const __grid_constant__ CUtensorMap tmX, const __grid_constant__ CUtensorMap tmW1,
                    const __grid_constant__ CUtensorMap tmU, const __grid_constant__ CUtensorMap tmW2) {
  extern __shared__ __align__(1024) unsigned char smem_raw[];
  const int tid = threadIdx.x, lane = tid & 31;
  uint32_t sid;
  if (USE_SMID) asm("mov.u32 %0, %smid;" : "=r"(sid)); else sid = blockIdx.x;
  const int wid = sid < 120 ? sid : sid - 4;
  uint32_t pa[6], pld, pds;
  const unsigned pw = min(tid >> 5, 14), part = (pw * 13) >> 6;
  const unsigned ch = (wid >> 4) * 80 + frag_col(((wid & 15) - part) * 5 + pw);
  const unsigned o = (ch * 3 + part) * 32 + lane;
  {
    asm volatile("{\n.reg .pred p;\nsetp.lt.u32 p, %0, 256;\n@p nanosleep.u32 %1;\n}" ::"r"(tid), "n"(LDLY));
    pld = ldg16(p.logdt + ch);
    pa[0] = ldg32((const uint32_t*)p.are + o); pa[1] = ldg32((const uint32_t*)p.aim + o);
    pds = ldg16(p.dskip + ch);
    pa[2] = ldg32((const uint32_t*)p.bre + o); pa[3] = ldg32((const uint32_t*)p.bim + o);
    pa[4] = ldg32((const uint32_t*)p.cre + o); pa[5] = ldg32((const uint32_t*)p.cim + o);
  }
  const int warp = __shfl_sync(0xffffffffu, tid >> 5, 0);
  const int g = lane >> 2, q = lane & 3;
  if (sid - 120u < 4u) { spare_work(p, &tmW1, sid - 120, tid); return; }
  unsigned* const cnt = p.scr->cnt;

  float kacc[6][4];
  const int kch = warp - 10;
  float dt, k0;
  uint32_t xv[2][10], xs[2], mw;
  {
    unsigned ep0;
    if (warp == 15) {
      ep0 = p.scr->epoch[wid];
      if ((uint32_t)__cvta_generic_to_shared(smem_raw) != sb) __trap();
    }
    if (elect1()) {
      const int gi = (warp + 1) & 15;
#pragma unroll
      for (int i = 0; i < 6; i++) mbar_init(bar + 48 * gi + 8 * i, gi < 7 ? 1 : gi == 7 ? 2 : gi < 10 ? 4 : 8);
      asm volatile("fence.mbarrier_init.release.cluster;" ::: "memory");
    }
    const uint32_t z0 = sid >> 8;
#pragma unroll
    for (int j = 0; j < 24; j++) kacc[j >> 2][j & 3] = __uint_as_float(pin(z0, z0));
    const uint32_t ks = sb + OFF_KS + warp * 4096;
    const uint32_t st = pin(ks + lane * 16, z0);
    const uint32_t kw = pin(ks + 3584 + (lane >> 1) * 8 + (lane & 1) * 2, z0), kr = pin(ks + 3584 + q * 8, z0);
    const uint32_t kb = pin(ks + ((lane >> 3) & 1) * 512 + ((lane >> 4) * 8 + (lane & 7)) * 16, z0);
    const __nv_bfloat16* xr = p.x + (wid * 16 + ((g >> 1) << 2) + (g & 1)) * DM;
    const __nv_bfloat16 *xa = xr + (warp & 7) * 80 + q * 8, *xb = xr + (warp & 7) * 80 + q * 4;
    asm volatile("add.u64 %0, %0, %3;\nadd.u64 %1, %1, %3;\nadd.u64 %2, %2, %3;" : "+l"(xr), "+l"(xa), "+l"(xb) : "l"((uint64_t)z0));
    if (warp < 8) bar_sync(14, 512); else bar_arrive(14, 512);
    if (warp == 15) {
      sts32(sb + OFF_ZERO + lane * 4, 0);
      int gpc, i;
      if (sid < 64) { gpc = (sid & 15) >> 1; i = sid >> 4; }
      else if (sid < 120) { const int t = sid - 64; i = t / 14; gpc = 1 + ((t - i * 14) >> 1); i += 4; }
      else { gpc = 0; i = 4 + ((sid - 124) >> 1); }
      const int qi = ((0x52741630 >> (4 * i)) & 7) * 2 + (sid & 1);
      const int rg = 4 * (gpc >> 1) + (qi >> 3) * 2 + (qi & 1), jc = 4 * (gpc & 1) + ((qi >> 1) & 3);
      sts64(sb + OFF_EP + 8, rg, jc);
      __syncwarp();
      if (elect1()) {
        asm volatile("prefetch.tensormap [%0];\nprefetch.tensormap [%1];\nprefetch.tensormap [%2];\nprefetch.tensormap [%3];" ::"l"(&tmW2), "l"(&tmX), "l"(&tmW1), "l"(&tmU) : "memory");
        __nanosleep(DELAY_NS);
        bulk_prefetch(p.x + wid * 16 * DM, 16 * DM * 2);
        mbar_expect(bar + 8 * B_W2, 96 * 176);
      }
      __syncwarp();
      load_x(xv, xa, xb, 2 * DM);
      xs[0] = __ldg((const uint32_t*)xr); xs[1] = __ldg((const uint32_t*)(xr + 2 * DM));
      bar_sync(5, 256);
      sts32(sb + OFF_EP + 4, xv[1][9]);
      if (elect1()) {
        tma5d(sb + OFF_W2S, &tmW2, (wid & 7) * 80, (wid >> 3) * 3, bar + 8 * B_W2);
        p.scr->epoch[wid] = ep0 + 1;
        sts32(sb + OFF_EP, ep0 + 1);
      }
      __syncwarp();
    }
    float zr, th, zr1, th1;
    cf c, c1;
    dt = rnd_bf(expf(bflo(pld)));
    {
      const float dl2 = dt * 1.4426950408889634f;
      zr = bflo(pa[0]) * dl2; th = bflo(pa[1]) * dt; zr1 = bfhi(pa[0]) * dl2; th1 = bfhi(pa[1]) * dt;
    }
    if (warp < 15) {
      c = cmul(cf{bflo(pa[4]), bflo(pa[5])}, cf{bflo(pa[2]), bflo(pa[3])});
      c1 = cmul(cf{bfhi(pa[4]), bfhi(pa[5])}, cf{bfhi(pa[2]), bfhi(pa[3])});
      mw = __reduce_max_sync(0xffffffffu, __float_as_uint(fmaxf(fmaxf(fabsf(c.r), fabsf(c.i)), fmaxf(fabsf(c1.r), fabsf(c1.i)))));
      mw = min(max(mw & 0x7f800000u, 20u << 23), 240u << 23);
      const float sc = __uint_as_float((259u << 23) - mw);
      k0 = c.r + c1.r;
      c.r *= sc; c.i *= -sc; c1.r *= sc; c1.i *= -sc;
      if (warp >= 8) {
        load_x(xv, xa, xb, 2 * DM);
        xs[0] = __ldg((const uint32_t*)xr); xs[1] = __ldg((const uint32_t*)(xr + 2 * DM));
        bar_arrive(5, 256);
      }
    }
    {
#pragma unroll 1
      for (int it = 0; it < 2; it++) {
        if (it == 1 && warp >= 8) {
          float sm[4] = {0.f, 0.f, 0.f, 0.f}, g0[4] = {0.f, 0.f, 0.f, 0.f}, g1[4] = {0.f, 0.f, 0.f, 0.f};
#pragma unroll
          for (int r = 0; r < 2; r++)
            xs[r] = fabsf(bflo(xs[r]) - bfhi(xs[r])) * 8.f < fabsf(bflo(xs[r])) ? __byte_perm(xs[r], 0, 0x1010) : 0u;
#pragma unroll
          for (int i = 0; i < 10; i += 2) {
            const uint32_t a0 = bsub(xv[0][i], xs[0]), a1 = bsub(xv[1][i], xs[1]), a2 = bsub(xv[0][i + 1], xs[0]), a3 = bsub(xv[1][i + 1], xs[1]);
            bmma(sm, a0, a1, a2, a3, 0x3f803f80u, 0x3f803f80u);
            bmma(g0, a0, a1, a2, a3, xv[0][i], xv[0][i + 1]);
            bmma(g1, a0, a1, a2, a3, xv[1][i], xv[1][i + 1]);
          }
          if (q == (g >> 1))
            sts128(sb + OFF_LNP + (warp - 8) * 128 + g * 16, __float_as_uint(sm[0]), __float_as_uint((g & 1) ? g0[1] : g0[0]),
                   __float_as_uint(sm[2]), __float_as_uint((g & 1) ? g1[3] : g1[2]));
          if (warp != 11) bar_arrive(1, 256);
        }
        if (warp == 15) continue;
        float m = ex2a(zr);
        const cf w1 = cf{m * __cosf(th), m * __sinf(th)};
        m = ex2a(zr * 8.f);
        const cf w8 = cf{m * __cosf(th * 8.f), m * __sinf(th * 8.f)};
        const cf w16 = csq(w8), w32 = csq(w16), w64 = csq(w32), w128 = csq(w64), w256 = csq(w128), w512 = csq(w256), w1024 = csq(w512);
        hp lo[4];
        lo[0] = hpack(cf{1.f, 0.f}, w8);
        lo[1] = hmulc(lo[0], pack_h(w16.r, w16.i));
        { const uint32_t k = pack_h(w32.r, w32.i); lo[2] = hmulc(lo[0], k); lo[3] = hmulc(lo[1], k); }
        sts_tile(st, lo);
        { const uint32_t k = pack_h(w64.r, w64.i); sts16(kw, k); sts16(kw + 4, k >> 16); }
        const uint32_t k256 = pack_h(w256.r, w256.i), k512 = pack_h(w512.r, w512.i);
        const cf t8 = cmulj(c, w8);
        { const cf u0 = cmulj(t8, w1024), u1 = cmulj(u0, w256);
          const hp a = hpack(u0, u1), b = hmulj(a, k512);
          sts128(st + 3072, a.r, b.r, a.i, b.i); }
        const cf t1 = cmulj(c, w1), t2 = cmulj(t1, w1), t3 = cmulj(t2, w1), t4 = cmulj(t3, w1);
        const cf t5 = cmulj(t4, w1), t6 = cmulj(t5, w1), t7 = cmulj(t6, w1);
        hp T0[4], T1[4];
        T0[0] = hpack(t4, t8); T0[1] = hpack(t2, t6); T0[2] = hpack(t1, t5); T0[3] = hpack(t3, t7);
        T1[0] = hmulj(T0[0], k256); T1[1] = hmulj(T0[1], k256); T1[2] = hmulj(T0[0], k512); T1[3] = hmulj(T1[0], k512);
        sts_tile(st + 2048, T1);
        sts_tile(st + 1024, T0);
        __syncwarp();
        uint32_t bc[4];
        ldsm4t(bc, st + 3072);
#pragma unroll
        for (int m2 = 0; m2 < 4; m2 += 2) {
          uint32_t l0[4], b0[4], b1[4];
          ldsm4t(l0, kb + m2 * 128);
          ldsm4t(b0, kb + 1024 + m2 * 128);
          ldsm4t(b1, kb + 2048 + m2 * 128);
#pragma unroll
          for (int i = 0; i < 2; i++) {
            const uint2 kv = lds64(kr + (m2 + i) * 32);
            const hp k64 = {kv.x, kv.y}, L0 = {l0[2 * i], l0[2 * i + 1]};
            const hp L1 = hmule(L0, k64), L2 = hmule(L1, k64), L3 = hmule(L2, k64);
            const uint32_t c0 = lane < 16 ? bc[m2 + i] : 0u, c1b = lane < 16 ? 0u : bc[m2 + i];
            const uint32_t a0 = pin(L0.r, z0), a2 = pin(L0.i, z0);
            hmma(kacc[0], a0, L1.r, a2, L1.i, b0[2 * i], b0[2 * i + 1]);
            hmma(kacc[2], a0, L1.r, a2, L1.i, b1[2 * i], b1[2 * i + 1]);
            hmma(kacc[4], a0, L1.r, a2, L1.i, c0, c1b);
            hmma(kacc[1], L2.r, L3.r, L2.i, L3.i, b0[2 * i], b0[2 * i + 1]);
            hmma(kacc[3], L2.r, L3.r, L2.i, L3.i, b1[2 * i], b1[2 * i + 1]);
            hmma(kacc[5], L2.r, L3.r, L2.i, L3.i, c0, c1b);
          }
        }
        __syncwarp();
        zr = zr1; th = th1; c = c1;
      }
    }
    if (warp >= 8) bar_arrive(6, 512);
    if (warp < 10) {
#pragma unroll
      for (int j = 0; j < 6; j++)
        sts128(st + j * 512, __float_as_uint(kacc[j][0]), __float_as_uint(kacc[j][1]), __float_as_uint(kacc[j][2]), __float_as_uint(kacc[j][3]));
      sts64(ks + 3072 + lane * 8, __float_as_uint(k0), mw);
    }
    if (warp == 11) {
      bar_sync(1, 256);
      float s1 = 0.f, s2 = 0.f;
#pragma unroll
      for (int w = 0; w < 8; w++) {
        const uint2 v = lds64(sb + OFF_LNP + w * 128 + g * 16 + (q & 1) * 8);
        s1 += __uint_as_float(v.x); s2 += __uint_as_float(v.y);
      }
      const float md = s1 * (1.f / DM), mean = bflo((q & 1) ? xs[1] : xs[0]) + md;
      const float var = fmaxf(fmaf(-md, mean, s2 * (1.f / DM)), 0.f);
      const float m = rnd_bf(mean);
      float sd, ri;
      asm("sqrt.approx.f32 %0, %1;" : "=f"(sd) : "f"(rnd_bf(rnd_bf(var) + 1e-5f)));
      asm("rcp.approx.f32 %0, %1;" : "=f"(ri) : "f"(rnd_bf(sd)));
      if (q < 2) {
        p.scr->stats[wid * 16 + ((g >> 1) << 2) + (g & 1) + 2 * q] = make_float2(-m, 0.5f * ri);
        sts64(sb + OFF_STAT + g * 16 + q * 8, __float_as_uint(-m * ri), __float_as_uint(ri));
      }
      __syncwarp();
    }
    if (warp == 15) {
      const uint2 rj = lds64(sb + OFF_EP + 8);
      mbar_wait(bar + 8 * B_W2, 0);
#pragma unroll 1
      for (int uu = 0; uu < 3; uu++) {
        if (elect1()) {
          load1(uu, &tmX, &tmW1, rj.x, rj.y);
          if (uu == 2) bulk_prefetch(p.w1 + wid * 5 * FF, 5 * FF * 2);
        }
        const uint32_t a = sb + OFF_W2S + (uu * 32 + lane) * 176;
        const int rem = ((wid >> 3) & 1) * 3 + uu;
        uint4* dst = p.scr->w2p + ((wid & 7) * 24 + 8 * (rem >> 1) + (wid >> 4)) * 640 + ((rem & 1) * 4 + (lane >> 3)) * 80 + (lane & 7);
        uint4 v[10];
#pragma unroll
        for (int i = 0; i < 10; i++) v[i] = lds128(a + i * 16);
#pragma unroll
        for (int i = 0; i < 8; i++)
          dst[8 * i] = make_uint4(bmul((&v[i & 4].x)[i & 3], 0x3f003f00u), bmul((&v[(i & 4) + 1].x)[i & 3], 0x3f003f00u),
                                  bmul((&v[(i & 4) + 2].x)[i & 3], 0x3f003f00u), bmul((&v[(i & 4) + 3].x)[i & 3], 0x3f003f00u));
        dst[64] = make_uint4(bmul(v[8].x, 0x3f003f00u), bmul(v[8].z, 0x3f003f00u), bmul(v[9].x, 0x3f003f00u), bmul(v[9].z, 0x3f003f00u));
        dst[72] = make_uint4(bmul(v[8].y, 0x3f003f00u), bmul(v[8].w, 0x3f003f00u), bmul(v[9].y, 0x3f003f00u), bmul(v[9].w, 0x3f003f00u));
      }
      fence_async_smem();
      __syncwarp();
      if (elect1()) load1(3, &tmX, &tmW1, rj.x, rj.y);
      __syncwarp();
    }
  }

  if (warp < 8) {
    float acc[96];
    const uint32_t alo = ((sb >> 4) | (1 << 16)) + (warp >> 2) * 512;
    bar_arrive(0, 512);
#pragma unroll 1
    for (int s = 0; s < 10; s++) {
      const uint32_t so = (s & 3) * (SLOT1 >> 4);
      mbar_wait(bar + 8 * (B_FULL1 + s), 0);
      if (s == 0) bar_sync(6, 512);
      wg_fence();
#pragma unroll
      for (int kk = 0; kk < 4; kk++)
        wgmma_n192(acc, dsc(alo + so + kk * 2, 0x40000040u), dsc((((sb + 16384) >> 4) | (512 << 16)) + so + kk * 128, 0x40000040u), (s | kk) != 0);
      wg_commit();
      wg_wait<1>();
      if (lane == 0) mbar_arrive(bar + 8 * (B_REL1 + s));
    }
    wg_wait<0>();
    bar_arrive(14, 384);
    bar_arrive(7, 384);
    mbar_wait(bar + 8 * B_EPI, 0);
    const uint2 s0 = lds64(sb + OFF_STAT + (warp * 16 + g) * 8), s1 = lds64(sb + OFF_STAT + (warp * 16 + g + 8) * 8);
    const float nm0 = __uint_as_float(s0.x), r0 = __uint_as_float(s0.y), nm1 = __uint_as_float(s1.x), r1 = __uint_as_float(s1.y);
    const uint4 erj = lds128(sb + OFF_EP);
    const unsigned ep = erj.x;
    const int rg1 = erj.z, j1 = erj.w;
    uint4* hd = p.scr->h + (rg1 * 24 + j1) * 1024 + warp * 128 + q * 8 + g;
#pragma unroll
    for (int grp = 0; grp < 6; grp++) {
      uint32_t o0[4], o1[4];
      const uint4 cs[2] = {lds128(sb + OFF_CS + grp * 128 + q * 32), lds128(sb + OFF_CS + grp * 128 + q * 32 + 16)};
#pragma unroll
      for (int tl = 0; tl < 4; tl++) {
        const int nt = grp * 4 + tl;
        const float ca = __uint_as_float((&cs[tl >> 1].x)[(tl & 1) * 2]), cb = __uint_as_float((&cs[tl >> 1].x)[(tl & 1) * 2 + 1]);
        const float a = fmaf(nm0, ca, acc[4 * nt]) * r0, b = fmaf(nm0, cb, acc[4 * nt + 1]) * r0;
        const float c = fmaf(nm1, ca, acc[4 * nt + 2]) * r1, d = fmaf(nm1, cb, acc[4 * nt + 3]) * r1;
        o0[tl] = pack_bf(fmaf(a, tanha(a), a), fmaf(b, tanha(b), b));
        o1[tl] = pack_bf(fmaf(c, tanha(c), c), fmaf(d, tanha(d), d));
      }
      uint4* dst = hd + (grp >> 1) * 8192 + (grp & 1) * 32;
      dst[0] = make_uint4(o0[0], o0[1], o0[2], o0[3]);
      dst[64] = make_uint4(o1[0], o1[1], o1[2], o1[3]);
      __nanosleep(PACE_NS);
      if (grp == 1) {
        if (warp == 7) { bar_sync(2, 256); if (lane == 0) publish(cnt + (C_H0 + rg1) * 32); __syncwarp(); }
        else bar_arrive(2, 256);
      }
    }
    if (warp == 6) { bar_sync(11, 256); if (lane == 0) publish(cnt + (C_H1 + rg1) * 32); __syncwarp(); }
    else bar_arrive(11, 256);
    const int go = (rg1 * 128 + warp * 16 + g) * DM + j1 * 80;
    load_x(xv, p.x + go + q * 8, p.x + go + q * 4, 8 * DM);
    if (warp < 4) {
      mbar_wait(bar + 8 * B_PART, 0);
      Comb cmb;
      {
        const uint4 a = lds128(sb + OFF_CMB + tid * 16);
        const uint2 b = lds64(sb + OFF_CMB + 2048 + tid * 8);
        cmb.o[0] = a.x; cmb.o[1] = a.y; cmb.o[2] = a.z; cmb.o[3] = a.w; cmb.o[4] = b.x; cmb.o[5] = b.y;
        cmb.o[6] = lds32(sb + OFF_CMB + 3072 + tid * 4);
      }
#pragma unroll 1
      for (int ch = 0; ch < 3; ch++) {
        combine(cmb, ch, wid, p.scr->sT, [] {});
      }
    } else if (warp == 4) {
      if (elect1()) {
        poll_cnt(cnt + (C_H0 + rg1) * 32, ep * 8);
#pragma unroll 1
        for (int s = 0; s < NS2 - 2; s++) {
          if (s == 4) poll_cnt(cnt + (C_H1 + rg1) * 32, ep * 8);
          if (s == 3) mbar_wait(bar + 8 * B_FREE, 0);
          if (s >= 3) mbar_wait(bar + 8 * (B_FREE + s - 2), 0);
          load2(s, sb + s * SLOT2, p.scr->h + (rg1 * 24 + s) * 1024, p.scr->w2p + (j1 * 24 + s) * 640);
        }
      }
      __syncwarp();
    }
    float acc2[40];
    bar_sync(8, 512);
    {
      const uint32_t al2 = ((sb >> 4) | (8 << 16)) + (warp >> 2) * 512;
      uint32_t so = 0;
#pragma unroll 1
      for (int s = 0; s < 24; s++) {
        mbar_wait(bar + 8 * (B_FULL2 + s), 0);
        if (s == SK2 && warp < 4) bar_sync(4, 256);
        wg_fence();
#pragma unroll
        for (int kk = 0; kk < 4; kk++)
          wgmma_n80(acc2, dsc(al2 + so + kk * 16, 64), dsc((((sb + 16384) >> 4) | (80 << 16)) + so + kk * 160, 8), (s | kk) != 0);
        wg_commit();
        so = so == (NS2 - 1) * (SLOT2 >> 4) ? 0 : so + (SLOT2 >> 4);
        if (s < SK2 - 1) {
          wg_wait<1>();
          if (lane == 0) mbar_arrive(bar + 8 * (B_REL2 + s));
        }
      }
      if (warp >= 4) { wg_wait<1>(); bar_arrive(4, 256); }
    }
    mbar_wait(bar + 8 * B_SFULL, 0);
    uint32_t sv[5][4];
    {
      const int i = lane & 7, mi = lane >> 3;
      const uint32_t a = sb + OFF_U + ((mi >> 1) * 8 + i) * 256 + (((2 * warp + (mi & 1)) ^ i) << 4);
#pragma unroll
      for (int k = 0; k < 5; k++) ldsm4t(sv[k], a + k * 4096);
    }
    wg_wait<0>();
#pragma unroll
    for (int hh = 0; hh < 2; hh++) {
      uint32_t o[10];
      __nv_bfloat16* op = p.out + go + hh * 8 * DM;
#pragma unroll
      for (int tl = 0; tl < 10; tl++) {
        const float a = acc2[4 * tl + 2 * hh], b = acc2[4 * tl + 2 * hh + 1];
        o[tl] = bfma(sv[tl >> 1][(tl & 1) * 2 + hh], pack_bf(fmaf(a, tanhv(a), a), fmaf(b, tanhv(b), b)), xv[hh][tl]);
        if ((tl & 3) == 3)
          asm volatile("st.global.v4.u32 [%0], {%1, %2, %3, %4};" ::"l"((uint4*)op + (tl >> 2) * 4 + q), "r"(o[tl - 3]), "r"(o[tl - 2]), "r"(o[tl - 1]), "r"(o[tl]) : "memory");
      }
      asm volatile("st.global.v2.u32 [%0], {%1, %2};" ::"l"((uint2*)(op + 64) + q), "r"(o[8]), "r"(o[9]) : "memory");
    }
  } else {
    const int cw = warp - 8;
    bar_sync(0, 512);
    const uint4 erj = lds128(sb + OFF_EP);
    const unsigned ep = erj.x;
    const int rg1 = erj.z, j1 = erj.w;
    {
      const uint4 st = lds128(sb + OFF_STAT + g * 16);
      const float n0 = __uint_as_float(st.x), r0 = __uint_as_float(st.y), n1 = __uint_as_float(st.z), r1 = __uint_as_float(st.w);
      const int up = upos(2 * wid);
      uint2* dst = (uint2*)p.scr->uT + ((up >> 1) * DM + cw * 80) * 4 + (lane ^ ((up & 1) << 1));
#pragma unroll
      for (int i = 0; i < 10; i++) {
        const uint32_t a = movm(pack_h(fmaf(bflo(xv[0][i]), r0, n0), fmaf(bfhi(xv[0][i]), r0, n0)));
        const uint32_t b = movm(pack_h(fmaf(bflo(xv[1][i]), r1, n1), fmaf(bfhi(xv[1][i]), r1, n1)));
        dst[i * 32] = make_uint2(a, b);
      }
    }
    if (warp == 8) {
      bar_sync(12, 256);
      if (lane == 0) publish(cnt + C_LN * 32);
      __syncwarp();
    } else bar_arrive(12, 256);
    if (warp == 15) {
      if (elect1()) {
#pragma unroll 1
        for (int s = 4; s < 10; s++) {
          mbar_wait(bar + 8 * (B_REL1 + s - 3), 0);
          load1(s, &tmX, &tmW1, rg1, j1);
        }
        poll_cnt(cnt + (C_CS + (j1 >> 1)) * 32, ep);
        bulk_g2s(sb + OFF_CS, p.scr->cs + j1 * 192, 768, bar + 8 * B_EPI);
      }
      __syncwarp();
    }
    if (warp >= 10 && warp < 15) {
      const uint32_t pb = sb + OFF_P + kch * 3072, pk = sb + OFF_KS + kch * 4096;
      const uint2 e0 = lds64(pk + 3072 + lane * 8), e1 = lds64(pk + 5 * 4096 + 3072 + lane * 8);
      const float dsk = bflo(pds);
      uint32_t kex = __float_as_uint(fmaxf(__uint_as_float(max(max(e0.y, e1.y), mw)) * dt, fabsf(dsk) * (1.f / 256.f))) >> 23;
      kex = min(max(kex, 20u), 240u);
      const float s2 = __uint_as_float((258 - kex) << 23), sd = s2 * dt * (1.f / 32.f);
      const float f0 = __uint_as_float(e0.y) * sd, f1 = __uint_as_float(e1.y) * sd, f2 = __uint_as_float(mw) * sd;
      k0 += __uint_as_float(e0.x) + __uint_as_float(e1.x);
#pragma unroll
      for (int o = 16; o; o >>= 1) k0 += __shfl_xor_sync(0xffffffffu, k0, o);
      const float k0n = fmaf(k0, dt, dsk) * s2;
      uint32_t h[5][2];
#pragma unroll
      for (int j = 0; j < 6; j++) {
        const uint4 a = lds128(pk + j * 512 + lane * 16), b = lds128(pk + 5 * 4096 + j * 512 + lane * 16);
#pragma unroll
        for (int e = 0; e < 4; e++) kacc[j][e] = fmaf(__uint_as_float((&a.x)[e]), f0, fmaf(__uint_as_float((&b.x)[e]), f1, kacc[j][e] * f2));
        if (j == 1) {
          const float k256 = __shfl_sync(0xffffffffu, kacc[1][3], 28);
          if (lane == 31) kacc[1][3] -= k256;
        }
        if (j == 2 || j == 3) { h[j][0] = pack_h(kacc[j][0], kacc[j][2]); h[j][1] = pack_h(kacc[j][1], kacc[j][3]); }
        else if (j < 2) { h[j][0] = pack_h(kacc[j][0], kacc[j][1]); h[j][1] = pack_h(kacc[j][2], kacc[j][3]); }
      }
      {
        const bool sw = q >> 1;
        float v[4];
#pragma unroll
        for (int e = 0; e < 4; e++) v[e] = (sw ? kacc[5][e] : kacc[4][e]) + __shfl_xor_sync(0xffffffffu, sw ? kacc[4][e] : kacc[5][e], 2);
        h[4][0] = pack_h(v[0], v[1]); h[4][1] = pack_h(v[2], v[3]);
#pragma unroll
        for (int e = 0; e < 2; e++) {
          const uint32_t r = __shfl_xor_sync(0xffffffffu, sw ? h[2][e] : h[3][e], 2);
          if (sw) h[2][e] = r; else h[3][e] = r;
        }
      }
      fence_async_smem();
      bar_arrive(13, 192);
#pragma unroll
      for (int i = 0; i < 6; i++) sts128(pb + i * 512 + lane * 16, 0, 0, 0, 0);
      __syncwarp();
      {
        const int sw = g >> 2;
        const uint32_t sel = sw ? 0x1032 : 0x3210;
        const uint32_t a = pb + (P0 + 8 * g + ((0x3124 >> (4 * q)) & 7)) * 4, a0 = a + sw * 16, a1 = a + 16 - sw * 16;
        put2<1>(a0, a1, h[0][0], sel);
        put2<1>(a0 + 256, a1 + 256, h[0][1], sel);
        put2<1>(a0 + 512, a1 + 512, h[1][0], sel);
        put2<1>(lane == 28 ? pb + PB1 * 4 : a0 + 768, a1 + 768, h[1][1], sel);
      }
      {
        const int sw = q >> 1;
        const uint32_t sel = sw ? 0x1032 : 0x3210;
        uint32_t a = pb + (((q & 1) ? PA1 : PB1 + 1) + 32 * sw + 2 * g) * 4;
        put2<1>(a + sw * 64, a + 64 - sw * 64, h[2][0], sel);
        put2<1>(a + 4 + sw * 64, a + 68 - sw * 64, h[2][1], sel);
        const int s1 = q & 1;
        const uint32_t sel1 = s1 ? 0x1032 : 0x3210;
        a = pb + (PA2 + g + 16 * sw + 32 * s1) * 4;
        put2<1>(a + s1 * 32, a + 32 - s1 * 32, h[3][0], sel1);
        put2<1>(a + (PB2 - PA2) * 4 + s1 * 32, a + (PB2 - PA2) * 4 + 32 - s1 * 32, h[3][1], sel1);
        a = pb + (((g & 1) ? PB3 : PA3) + (g >> 1) + 8 * sw + 32 * s1) * 4;
        const uint32_t hx = s1 ? h[4][1] : h[4][0], hy = s1 ? h[4][0] : h[4][1];
        put2<1>(a + s1 * 16, a + 64 + s1 * 16, hx, 0x3210);
        put2<1>(a + 16 - s1 * 16, a + 80 - s1 * 16, hy, 0x3210);
      }
      if (lane == 30) put2<1>(pb + P0 * 4, pb + (PA1 + 64) * 4, __byte_perm(pack_h(k0n, 0.f), h[2][1], 0x7610), 0x3210);
      if (lane == 31) sts64(sb + OFF_CHC + kch * 8, (kex - 4) * 0x00800080u, __byte_perm(h[3][1], 0, 0x3232));
    }
    if (warp == 8) {
      bar_sync(13, 192);
      if (elect1()) {
        mbar_expect(bar + 8 * B_UFULL, 144 * 160);
        mbar_expect(bar + 8 * B_EPI, 1024 + 768);
        poll_cnt(cnt + C_LN * 32, ep * 128);
        tma2d(sb + OFF_U - 16 * 160, &tmU, wid * 80, -16, bar + 8 * B_UFULL);
        bulk_g2s(sb + OFF_STAT, p.scr->stats + rg1 * 128, 1024, bar + 8 * B_EPI);
      }
      __syncwarp();
    }
    const int wg = warp >> 2, role = (warp + 2 * wg) & 3;
    uint32_t co[6], cpa = (g - 2 * q) * 4;
    if (role < 2) {
#pragma unroll
      for (int gm = 0; gm < 3; gm++) {
        const int hb = 2 * (lane & 7) + role - 2 + gm, l3 = ((lane >> 3) ^ (hb >> 1)) & 7;
        co[2 * gm] = hb * 1280 + uoff(l3); co[2 * gm + 1] = hb * 1280 + uoff(l3 ^ 4);
      }
    } else {
      const int mi = lane >> 3, hf = (lane >> 2) & 1;
      co[0] = hf * 1792 + (mi ^ hf) * 64 + ((q ^ (mi >> 1) ^ (hf * 2)) << 4);
      co[1] = co[0] ^ 96;
      const int i = lane & 7;
      if (role == 3) co[0] = (16 * (mi >> 1) + ((4 * (mi & 1) + (i >> 1) + 8 * (i & 1)) ^ (4 * (i & 1)))) << 4;
      co[2] = (role == 2 ? (16 * (mi >> 1) + 2 * i + (mi & 1)) ^ (i >> 2) : lane ^ ((lane >> 1) & 4)) << 4;
      co[3] = lane * 16;
      co[4] = (g >> 1) == q ? ((g & 1) ? 0xffff0000u : 0xffffu) : 0u;
      co[5] = (g - q) * 8;
    }
    const uint32_t zero = lds32(sb + OFF_ZERO), nz = zero | 0x80000000u;
#pragma unroll
    for (int i = 0; i < 6; i++) co[i] = pin(co[i], zero);
    cpa = pin(cpa, zero);
    const Comb cmb = comb_setup(tid, zero);
    if (warp >= 10 && warp < 15) bar_sync(15, 160);
    const int qt = ((cw & 1) << 1) | ((cw >> 1) & 1), jz = qt * 32 + lane;
    uint32_t zo[13];
    {
      const int j = jz < 112 ? jz : jz - 128, gr = j >> 1;
      zo[0] = uoff(upos(max(2 * j - 2, -32))); zo[1] = zo[0] ^ 16; zo[2] = uoff(upos(2 * j)); zo[3] = zo[2] ^ 16; zo[4] = uoff(upos(2 * j + 2));
#pragma unroll
      for (int pp = 0; pp < 4; pp++) zo[5 + pp] = ZA1 + 512 + (gr ^ ((gr >> 2) & 1)) * 64 + ((((gr >> 1) & 3) ^ pp) << 4) + (j & 1) * 8;
      zo[9] = ((j >> 3) * 16 + (j & 7)) * 16;
      zo[10] = ((j >> 4) * 32 + (j & 15)) * 16;
      zo[11] = zo[10] + ((j & 15) == 15 ? 272 : 16);
      zo[12] = (zo[9] ^ 64) + 128;
#pragma unroll
      for (int i = 0; i < 13; i++) zo[i] = pin(zo[i], zero);
    }
    if (warp < 12) {
      mbar_wait(bar + 8 * (B_REL1 + 7), 0);
      sts128(sb + OFF_CMB + (tid - 256) * 16, cmb.o[0], cmb.o[1], cmb.o[2], cmb.o[3]);
      sts64(sb + OFF_CMB + 2048 + (tid - 256) * 8, cmb.o[4], cmb.o[5]);
      sts32(sb + OFF_CMB + 3072 + (tid - 256) * 4, cmb.o[6]);
    }
    mbar_wait(bar + 8 * B_UFULL, 0);
#pragma unroll 1
    for (unsigned seq = (cw >> 2) ? 0xb9ac : 0x8; seq; seq >>= 4) {
      const int ch = seq & 7;
      if (ch == 1) bar_arrive(0, 256);
      if (ch == 2) mbar_wait(bar + 8 * (B_REL1 + 8), 0);
      const uint32_t ub = sb + OFF_U + ch * 32, zb = sb + OFF_Z + ch * ZSZ;
      uint32_t w_[20], o_[20], d_[20], b3_[20];
      uint32_t *w = w_ + 8, *o = o_ + 8, *d = d_ + 8, *b3 = b3_ + 8;
      {
        const uint4 c = lds128(ub + zo[2]), e = lds128(ub + zo[3]), b = lds128(ub + zo[1]);
        w[8] = lds32(ub + zo[4]);
        const uint2 a = lds64(ub + zo[0] + 8);
        w[-6] = a.x; w[-5] = a.y; w[-4] = b.x; w[-3] = b.y; w[-2] = b.z; w[-1] = b.w;
        w[0] = c.x; w[1] = c.y; w[2] = c.z; w[3] = c.w; w[4] = e.x; w[5] = e.y; w[6] = e.z; w[7] = e.w;
      }
#pragma unroll
      for (int i = -1; i <= 7; i++) o[i] = odd_pair(w[i], w[i + 1]);
#pragma unroll
      for (int i = 0; i <= 7; i++) { d[i] = hadd(w[i], o[i]); b3[i] = hadd(d[i], o[i - 1]); }
#pragma unroll
      for (int pp = 0; pp < 4; pp++) {
        const uint32_t sel = (pp & 1) ? 0x7632 : 0x5410;
        const int k = pp >> 1;
        sts64(zb + zo[5 + pp], __byte_perm(w[k - 1], w[k + 1], sel), __byte_perm(w[k + 3], w[k + 5], sel));
        sts64(zb + zo[5 + pp] + (ZB1 - ZA1), __byte_perm(b3[k], b3[k + 2], sel), __byte_perm(b3[k + 4], b3[k + 6], sel));
      }
      if (qt < 3) {
        uint32_t e_[20], b5_[20];
        uint32_t *e = e_ + 8, *b5 = b5_ + 8;
#pragma unroll
        for (int i = -6; i <= -2; i++) o[i] = odd_pair(w[i], w[i + 1]);
#pragma unroll
        for (int i = -6; i <= -1; i++) d[i] = hadd(w[i], o[i]);
#pragma unroll
        for (int i = -5; i <= -1; i++) b3[i] = hadd(d[i], o[i - 1]);
#pragma unroll
        for (int i = -5; i <= 4; i++) e[i] = hadd(d[i - 1], d[i]);
#pragma unroll
        for (int i = -4; i <= 4; i++) b5[i] = hadd(e[i], w[i + 1]);
        const uint32_t a2 = zb + zo[9];
        sts128(a2 + ZA2, b3[-2], b3[-1], b3[0], b3[1]);
        sts128(zb + zo[12] + ZA2, b3[2], b3[3], b3[4], b3[5]);
        sts128(a2 + ZB2, b5[-4], b5[-3], b5[-2], b5[-1]);
        sts128(zb + zo[12] + ZB2, b5[0], b5[1], b5[2], b5[3]);
        if (qt < 2) {
          sts128(a2 + ZS, d[-2], d[-1], d[0], d[1]);
          sts128(a2 + ZS + 128, d[2], d[3], d[4], d[5]);
          uint32_t b7[8], b9[8];
#pragma unroll
          for (int i = -4; i <= 3; i++) { b7[i + 4] = hadd(b3[i - 1], e[i + 1]); b9[i + 4] = hadd(e[i - 1], b5[i + 1]); }
          const uint32_t a3 = zb + zo[10];
          sts128(a3 + ZA3, b7[0], b7[1], b7[2], b7[3]);
          sts128(a3 + ZA3 + 256, b7[4], b7[5], b7[6], b7[7]);
          sts128(a3 + ZB3 + 256, b9[0], b9[1], b9[2], b9[3]);
          if (jz < 63) sts128(zb + zo[11] + ZB3, b9[4], b9[5], b9[6], b9[7]);
          else sts128(zb + ZB3, 0, 0, 0, 0);
        }
      }
    }
    bar_sync(wg == 2 ? 14 : 7, 384);
#pragma unroll 1
    for (int ch = wg - 2; ch < 5; ch += 2) {
      const uint32_t ub = sb + OFF_U + ch * 32, zb = sb + OFF_Z + ch * ZSZ, pb = sb + OFF_P + ch * 3072;
      if (ch == 2) bar_sync(0, 256);
      const uint32_t pa = pb + cpa;
      if (role < 2) {
        float acc[8][4];
#pragma unroll
        for (int r = 0; r < 8; r++) { acc[r][0] = acc[r][1] = acc[r][2] = acc[r][3] = 0.f; }
        float fix = 0.f;
        if (role == 1 && lane == 28) {
          const uint32_t k = lds32(pb + PB1 * 4), u0 = lds32(ub);
          fix = __low2float(*reinterpret_cast<const __half2*>(&k)) * __low2float(*reinterpret_cast<const __half2*>(&u0));
        }
        uint32_t b[12][4], A[17][4];
#pragma unroll
        for (int i = 11; i >= 8; i--) ldsm4(b[i], ub + (co[4 + (i & 1)] ^ (((i >> 1) & 1) * 16)) + ((i >> 1) & 1) * 640);
        A[0][0] = lds32(pa + P0 * 4); A[0][1] = lds32(pa + P0 * 4 + 32); A[0][2] = lds32(sb + OFF_ZERO + 4);
#pragma unroll
        for (int m = 0; m <= 16; m++) {
          if (m < 16) {
            A[m + 1][0] = lds32(pa + P0 * 4 + (2 * m + 2) * 32);
            A[m + 1][1] = m < 15 ? lds32(pa + P0 * 4 + (2 * m + 3) * 32) : lds32(sb + OFF_ZERO + 8);
          }
          if ((m & 1) == 0 && m < 16) {
            const int i = 7 - (m >> 1);
            ldsm4(b[i], ub + (co[2 * (i >> 2) + (i & 1)] ^ (((i >> 1) & 1) * 16)) + ((i >> 1) & 1) * 640);
          }
          if (m == 9 && elect1()) mbar_arrive(bar + 8 * (B_PAIR + ch));
          A[m][3] = dup(A[m][0], nz);
          if (m < 16) A[m + 1][2] = dup(A[m][1], nz);
#pragma unroll
          for (int r = 7; r >= 0; r--) {
            const int f = 16 + r - m;
            hmma(acc[r], A[m][0], A[m][1], A[m][2], A[m][3], b[f >> 1][(f & 1) * 2], b[f >> 1][(f & 1) * 2 + 1]);
          }
        }
        acc[7][2] += fix;
        mbar_wait(bar + 8 * (B_PAIR + ch), 0);
#pragma unroll
        for (int i = 3; i >= 0; i--)
          stsm4t(ub + (co[4 + (i & 1)] ^ (((i >> 1) & 1) * 16)) + ((i >> 1) & 1) * 640, pack_bf(acc[2 * i][0], acc[2 * i][1]), pack_bf(acc[2 * i][2], acc[2 * i][3]),
                 pack_bf(acc[2 * i + 1][0], acc[2 * i + 1][1]), pack_bf(acc[2 * i + 1][2], acc[2 * i + 1][3]));
      } else if (role == 2) {
        float acc[14][4];
#pragma unroll
        for (int r = 0; r < 14; r++) { acc[r][0] = acc[r][1] = acc[r][2] = acc[r][3] = 0.f; }
#pragma unroll
        for (int arr = 0; arr < 2; arr++) {
          uint32_t A[5][4];
#pragma unroll
          for (int m = 4; m >= 0; m--) {
            const uint2 v = lds64(pb + co[5] + (arr ? PB1 : PA1) * 4 + m * 64), w = lds64(pb + co[5] + (arr ? PB1 : PA1) * 4 + m * 64 - 32);
            A[m][0] = v.x; A[m][1] = v.y; A[m][2] = w.x; A[m][3] = w.y;
          }
#pragma unroll
          for (int ip = 0; ip < 9; ip++) {
            uint32_t b[4];
            ldsm4(b, zb + co[ip & 1] + (arr ? ZB1 : ZA1) + ip * 256);
#pragma unroll
            for (int hh = 0; hh < 2; hh++)
#pragma unroll
              for (int m = 0; m < 5; m++) {
                const int i = 2 * ip + hh - 4 + m;
                if (i >= 0 && i < 14) hmma(acc[i], A[m][0], A[m][1], A[m][2], A[m][3], b[2 * hh], b[2 * hh + 1]);
              }
          }
        }
        const uint32_t a = zb + ZA1 + 512 + co[2];
#pragma unroll
        for (int i = 0; i < 7; i++)
          stsm4(a + i * 512, pack_bf(acc[2 * i][0], acc[2 * i][1]), pack_bf(acc[2 * i][2], acc[2 * i][3]),
                pack_bf(acc[2 * i + 1][0], acc[2 * i + 1][1]), pack_bf(acc[2 * i + 1][2], acc[2 * i + 1][3]));
      } else {
        float acc[12][4];
        const uint32_t za = zb + co[3];
        {
          float d[4][2][4];
#pragma unroll
          for (int r = 0; r < 8; r++) { d[r >> 1][r & 1][0] = d[r >> 1][r & 1][1] = d[r >> 1][r & 1][2] = d[r >> 1][r & 1][3] = 0.f; }
#pragma unroll
          for (int arr = 0; arr < 2; arr++) {
            uint32_t A[4][4];
#pragma unroll
            for (int m = 0; m < 4; m++) { A[m][0] = lds32(pa + (arr ? PB3 : PA3) * 4 + m * 64); A[m][1] = lds32(pa + (arr ? PB3 : PA3) * 4 + m * 64 + 32); }
#pragma unroll
            for (int m = 0; m < 4; m++) { A[m][2] = m ? dup(A[m - 1][1], nz) : lds32(sb + OFF_ZERO + 4 + arr * 4); A[m][3] = dup(A[m][0], nz); }
#pragma unroll
            for (int io = 0; io < 4; io++) {
              uint32_t b[4];
              ldsm4t(b, za + (arr ? ZB3 : ZA3) + io * 512);
#pragma unroll
              for (int m = 0; m + io < 4; m++) {
                hmma(d[io + m][0], A[m][0], A[m][1], A[m][2], A[m][3], b[0], b[1]);
                hmma(d[io + m][1], A[m][0], A[m][1], A[m][2], A[m][3], b[2], b[3]);
              }
            }
          }
#pragma unroll
          for (int r = 0; r < 4; r++) {
            acc[r][0] = acc[r][1] = acc[r][2] = acc[r][3] = 0.f;
            acc[4 + 2 * r][0] = d[r][0][0]; acc[4 + 2 * r][1] = d[r][0][1]; acc[4 + 2 * r][2] = d[r][1][0]; acc[4 + 2 * r][3] = d[r][1][1];
            acc[5 + 2 * r][0] = d[r][0][2]; acc[5 + 2 * r][1] = d[r][0][3]; acc[5 + 2 * r][2] = d[r][1][2]; acc[5 + 2 * r][3] = d[r][1][3];
          }
        }
        {
          const uint32_t k0 = lds32(sb + OFF_CHC + ch * 8 + 4) & co[4];
          const uint32_t k1 = lds32(sb + OFF_ZERO + 12), k2 = lds32(sb + OFF_ZERO + 16), k3 = dup(k0, nz);
#pragma unroll
          for (int ip = 0; ip < 4; ip++) {
            uint32_t b[4];
            ldsm4t(b, za + ZS + ip * 512);
            hmma(acc[4 + 2 * ip], k0, k1, k2, k3, b[0], b[1]);
            hmma(acc[5 + 2 * ip], k0, k1, k2, k3, b[2], b[3]);
          }
        }
        const uint32_t pa2 = pb + co[5];
#pragma unroll
        for (int arr = 0; arr < 2; arr++) {
          uint32_t A[5][4];
#pragma unroll
          for (int m = 0; m < 5; m++) {
            const uint2 v = lds64(pa2 + (arr ? PB2 : PA2) * 4 + m * 64), w = lds64(pa2 + (arr ? PB2 : PA2) * 4 + m * 64 - 32);
            A[m][0] = v.x; A[m][1] = v.y; A[m][2] = w.x; A[m][3] = w.y;
          }
#pragma unroll
          for (int ip = 0; ip < 6; ip++) {
            uint32_t b[4];
            ldsm4t(b, zb + co[0] + (arr ? ZB2 : ZA2) + ip * 512);
#pragma unroll
            for (int hh = 0; hh < 2; hh++)
#pragma unroll
              for (int m = 0; m < 5; m++) {
                const int i = 2 * ip + hh + m;
                if (i < 12) hmma(acc[i], A[m][0], A[m][1], A[m][2], A[m][3], b[2 * hh], b[2 * hh + 1]);
              }
          }
        }
        const uint32_t a = zb + ZA2 + co[2];
#pragma unroll
        for (int i = 0; i < 6; i++)
          stsm4(a + i * 512, pack_bf(acc[2 * i][0], acc[2 * i][1]), pack_bf(acc[2 * i][2], acc[2 * i][3]),
                pack_bf(acc[2 * i + 1][0], acc[2 * i + 1][1]), pack_bf(acc[2 * i + 1][2], acc[2 * i + 1][3]));
      }
      __syncwarp();
      if (elect1()) mbar_arrive(bar + 8 * (B_PART + ch));
    }
    const uint4* srcA = p.scr->h + (rg1 * 24 + NS2 - 2) * 1024;
    const uint4* srcB = p.scr->w2p + (j1 * 24 + NS2 - 2) * 640;
    combine(cmb, 6 - wg, wid, p.scr->sT, [&] {
      if (warp == 12) {
        bar_sync(8, 512);
        if (elect1()) {
          asm volatile("fence.proxy.async.global;" ::: "memory");
          load2(NS2 - 2, sb + (NS2 - 2) * SLOT2, srcA, srcB);
          load2(NS2 - 1, sb + (NS2 - 1) * SLOT2, srcA + 1024, srcB + 640);
        }
        __syncwarp();
      } else bar_arrive(8, 512);
    });
    if (warp == 12) {
      if (elect1()) {
        uint32_t d = sb;
#pragma unroll 1
        for (int s = NS2; s < 24; s++) {
          mbar_wait(bar + 8 * (B_REL2 + s - NS2 + 1), 0);
          load2(s, d, srcA + 2048, srcB + 1280);
          srcA += 1024; srcB += 640;
          d = d == sb + (NS2 - 1) * SLOT2 ? sb : d + SLOT2;
        }
      }
      __syncwarp();
    } else if (warp == 13) {
      if (elect1()) {
#pragma unroll 1
        for (int c = 2; c < 5; c++) mbar_wait(bar + 8 * (B_FREE + c), 0);
        publish(cnt + (C_S + (wid >> 4)) * 32);
        mbar_expect(bar + 8 * B_SFULL, 20480);
        poll_cnt(cnt + (C_S + j1) * 32, ep * 16);
        mbar_wait(bar + 8 * (B_REL2 + 24 - NS2), 0);
        bulk_g2s(sb + OFF_U, p.scr->sT + (j1 * 16 + rg1) * 1280, 20480, bar + 8 * B_SFULL);
      }
      __syncwarp();
    }
  }
}

typedef CUresult (*EncodeFn)(CUtensorMap*, CUtensorMapDataType, cuuint32_t, void*, const cuuint64_t*, const cuuint64_t*,
                             const cuuint32_t*, const cuuint32_t*, CUtensorMapInterleave, CUtensorMapSwizzle,
                             CUtensorMapL2promotion, CUtensorMapFloatOOBfill);

}

extern "C" void kernel_launch(void* const* d_in, const int* in_sizes, int n_in, void* d_out, int out_size) {
  static EncodeFn enc = nullptr;
  static int nsm = 0;
  static void* scr = nullptr;
  if (!enc) {
    void* fn = nullptr;
    cudaDriverEntryPointQueryResult qr;
    cudaGetDriverEntryPoint("cuTensorMapEncodeTiled", &fn, cudaEnableDefault, &qr);
    enc = (EncodeFn)fn;
    int dev = 0;
    cudaGetDevice(&dev);
    cudaDeviceGetAttribute(&nsm, cudaDevAttrMultiProcessorCount, dev);
    cudaFuncSetAttribute(fused_s4_ffn_kernel<true>, cudaFuncAttributeMaxDynamicSharedMemorySize, SMEM_BYTES);
    cudaFuncSetAttribute(fused_s4_ffn_kernel<false>, cudaFuncAttributeMaxDynamicSharedMemorySize, SMEM_BYTES);
    cudaGetSymbolAddress(&scr, g_scr);
  }
  Params p;
  p.x = (const __nv_bfloat16*)d_in[0];
  p.are = (const __nv_bfloat16*)d_in[1]; p.aim = (const __nv_bfloat16*)d_in[2];
  p.bre = (const __nv_bfloat16*)d_in[3]; p.bim = (const __nv_bfloat16*)d_in[4];
  p.cre = (const __nv_bfloat16*)d_in[5]; p.cim = (const __nv_bfloat16*)d_in[6];
  p.logdt = (const __nv_bfloat16*)d_in[7]; p.dskip = (const __nv_bfloat16*)d_in[8];
  p.w1 = (const __nv_bfloat16*)d_in[10]; p.w2 = (const __nv_bfloat16*)d_in[11];
  p.out = (__nv_bfloat16*)d_out;
  p.scr = (Scratch*)scr;
  CUtensorMap tmX, tmW1, tmU, tmW2;
  const cuuint32_t es[5] = {1, 1, 1, 1, 1};
  {
    const cuuint64_t gd[5] = {DM, 2, 4, 4, FF / 32}, gs[4] = {DM * 2, DM * 16, DM * 4, DM * 64};
    const cuuint32_t bx[5] = {88, 2, 4, 4, 3};
    enc(&tmW2, CU_TENSOR_MAP_DATA_TYPE_BFLOAT16, 5, d_in[11], gd, gs, bx, es, CU_TENSOR_MAP_INTERLEAVE_NONE,
        CU_TENSOR_MAP_SWIZZLE_NONE, CU_TENSOR_MAP_L2_PROMOTION_NONE, CU_TENSOR_MAP_FLOAT_OOB_FILL_NONE);
  }
  {
    const cuuint64_t gd[2] = {16 * DM, 128}, gs[1] = {DM * 32};
    const cuuint32_t bx[2] = {80, 144};
    enc(&tmU, CU_TENSOR_MAP_DATA_TYPE_FLOAT16, 2, p.scr->uT, gd, gs, bx, es, CU_TENSOR_MAP_INTERLEAVE_NONE,
        CU_TENSOR_MAP_SWIZZLE_NONE, CU_TENSOR_MAP_L2_PROMOTION_NONE, CU_TENSOR_MAP_FLOAT_OOB_FILL_NONE);
  }
  {
    const cuuint64_t gd[2] = {DM, SEQ}, gs[1] = {DM * 2};
    const cuuint32_t bx[2] = {64, 128};
    enc(&tmX, CU_TENSOR_MAP_DATA_TYPE_BFLOAT16, 2, d_in[0], gd, gs, bx, es, CU_TENSOR_MAP_INTERLEAVE_NONE,
        CU_TENSOR_MAP_SWIZZLE_128B, CU_TENSOR_MAP_L2_PROMOTION_L2_128B, CU_TENSOR_MAP_FLOAT_OOB_FILL_NONE);
  }
  {
    const cuuint64_t gd[3] = {64, DM, FF / 64}, gs[2] = {FF * 2, 128};
    const cuuint32_t bx[3] = {64, 64, 3};
    enc(&tmW1, CU_TENSOR_MAP_DATA_TYPE_BFLOAT16, 3, d_in[10], gd, gs, bx, es, CU_TENSOR_MAP_INTERLEAVE_NONE,
        CU_TENSOR_MAP_SWIZZLE_128B, CU_TENSOR_MAP_L2_PROMOTION_L2_128B, CU_TENSOR_MAP_FLOAT_OOB_FILL_NONE);
  }
  if (nsm == 132) fused_s4_ffn_kernel<true><<<132, 512, SMEM_BYTES>>>(p, tmX, tmW1, tmU, tmW2);
  else fused_s4_ffn_kernel<false><<<132, 512, SMEM_BYTES>>>(p, tmX, tmW1, tmU, tmW2);
}
```

```cpp
#include <cuda_runtime.h>
#include <cuda_bf16.h>
#include <cuda_fp16.h>
#include <cuda.h>
#include <stdint.h>

namespace {

constexpr int SEQ = 2048, DM = 640, FF = 1536;

constexpr int SLOT1 = 40960;
constexpr int SLOT2 = 26624;
constexpr int NS2 = 7;
#define LDLY 150
#define DELAY_NS 100
#define PACE_NS 20
#define WPR 4
#define QMAP 0x31203120
#define SK2 21
constexpr int OFF_Z = 85504, ZSZ = 20480;
constexpr int ZA3 = 0, ZB3 = 2048, ZS = 4096, ZA2 = 6144, ZB2 = 9216, ZA1 = 12288, ZB1 = 16384;
constexpr int OFF_CMB = 2 * SLOT1;
constexpr int OFF_W2S = 3 * SLOT1;
constexpr int OFF_U = 190464;
constexpr int OFF_P = 210944;
constexpr int OFF_KS = 163840;
constexpr int OFF_LNP = 225280;
constexpr int OFF_MISC = 226304;
constexpr int OFF_CHC = OFF_MISC + 16;
constexpr int OFF_EP = OFF_MISC + 64;
constexpr int OFF_ZERO = OFF_MISC + 128;
constexpr int OFF_STAT = OFF_MISC + 1024;
constexpr int OFF_CS = OFF_MISC + 2048;
constexpr int OFF_BAR = OFF_MISC + 2816;
constexpr int SMEM_BYTES = OFF_MISC + 6144;
constexpr int P0 = 8, PA1 = 280, PB1 = 360, PA2 = 448, PB2 = 544, PA3 = 632, PB3 = 704;
enum { B_W2 = 0, B_FULL1 = 1, B_FULL2 = 11, B_UFULL = 35, B_EPI = 36, B_SFULL = 37,
       B_PAIR = 42,
       B_FREE = 48, B_PART = 54,
       B_REL1 = 60, B_REL2 = 70 };
enum { C_LN = 0, C_H = 2, C_S = 34, C_CS = 42, C_NUM = 46 };

struct Scratch {
  unsigned cnt[64 * 32];
  unsigned epoch[256];
  float2 stats[SEQ];
  float cs[FF];
  uint4 uT[DM * 256];
  uint4 w2p[8 * 24 * 640];
  uint4 sT[8 * 16 * 1280];
  uint4 h[16 * 24 * 1024];
};
__device__ __align__(1024) Scratch g_scr;
constexpr uint32_t sb = 1024;
constexpr uint32_t bar = sb + OFF_BAR;

struct Params {
  const __nv_bfloat16 *are, *aim, *bre, *bim, *cre, *cim, *logdt, *dskip, *x, *w1, *w2;
  __nv_bfloat16* out;
  Scratch* scr;
};

__device__ __forceinline__ void mbar_init(uint32_t a, int c) { asm volatile("mbarrier.init.shared::cta.b64 [%0], %1;" ::"r"(a), "r"(c)); }
__device__ __forceinline__ void mbar_expect(uint32_t a, int b) { asm volatile("mbarrier.arrive.expect_tx.shared::cta.b64 _, [%0], %1;" ::"r"(a), "r"(b) : "memory"); }
__device__ __forceinline__ void mbar_arrive(uint32_t a) { asm volatile("mbarrier.arrive.shared::cta.b64 _, [%0];" ::"r"(a) : "memory"); }
__device__ __forceinline__ void mbar_wait(uint32_t a, int ph) {
  asm volatile(
      "{\n.reg .pred p;\n.reg .u32 n;\n"
      "mbarrier.try_wait.parity.shared::cta.b64 p, [%0], %1;\n@p bra LD;\nmov.u32 n, 0;\n"
      "LW:\nmbarrier.try_wait.parity.shared::cta.b64 p, [%0], %1, 20000;\n@p bra LD;\n"
      "add.u32 n, n, 1;\nsetp.lt.u32 p, n, 100000;\n@p bra LW;\ntrap;\nLD:\n}\n" ::"r"(a), "r"(ph) : "memory");
}
__device__ __forceinline__ void poll_cnt(const unsigned* p, unsigned target) {
  asm volatile(
      "{\n.reg .pred p;\n.reg .u32 n;\n.reg .s32 v;\nmov.u32 n, 0;\n"
      "LW:\nld.relaxed.gpu.global.u32 v, [%0];\nsub.s32 v, v, %1;\nsetp.ge.s32 p, v, 0;\n@p bra LD;\n"
      "nanosleep.u32 64;\nadd.u32 n, n, 1;\nsetp.lt.u32 p, n, 4000000;\n@p bra LW;\ntrap;\n"
      "LD:\nfence.acquire.gpu;\nfence.proxy.async.global;\n}\n" ::"l"(p), "r"(target) : "memory");
}
__device__ __forceinline__ void publish(unsigned* p) {
  asm volatile("fence.proxy.async.global;\nfence.release.gpu;\nred.relaxed.gpu.global.add.u32 [%0], 1;" ::"l"(p) : "memory");
}
__device__ __forceinline__ uint32_t movm(uint32_t v) { uint32_t r; asm volatile("movmatrix.sync.aligned.m8n8.trans.b16 %0, %1;" : "=r"(r) : "r"(v)); return r; }
__device__ __forceinline__ void fence_async_smem() { asm volatile("fence.proxy.async.shared::cta;" ::: "memory"); }
__device__ __forceinline__ bool elect1() { uint32_t p; asm volatile("{\n.reg .pred P;\nelect.sync _|P, 0xffffffff;\nselp.u32 %0,1,0,P;\n}\n" : "=r"(p)); return p; }
__device__ __forceinline__ void bar_sync(int id, int n) { asm volatile("bar.sync %0, %1;" ::"r"(id), "r"(n) : "memory"); }
__device__ __forceinline__ void bar_arrive(int id, int n) { asm volatile("bar.arrive %0, %1;" ::"r"(id), "r"(n) : "memory"); }
__device__ __forceinline__ void bulk_g2s(uint32_t dst, const void* src, int bytes, uint32_t mb) {
  asm volatile("cp.async.bulk.shared::cluster.global.mbarrier::complete_tx::bytes [%0], [%1], %2, [%3];" ::"r"(dst), "l"(src), "r"(bytes), "r"(mb) : "memory");
}
__device__ __forceinline__ void bulk_prefetch(const void* src, int bytes) { asm volatile("cp.async.bulk.prefetch.L2.global [%0], %1;" ::"l"(src), "r"(bytes) : "memory"); }
__device__ __forceinline__ void tma2d(uint32_t dst, const CUtensorMap* m, int c0, int c1, uint32_t mb) {
  asm volatile("cp.async.bulk.tensor.2d.shared::cluster.global.mbarrier::complete_tx::bytes [%0], [%1, {%3, %4}], [%2];" ::"r"(dst), "l"(m), "r"(mb), "r"(c0), "r"(c1) : "memory");
}
__device__ __forceinline__ void tma3d(uint32_t dst, const CUtensorMap* m, int c0, int c1, int c2, uint32_t mb) {
  asm volatile("cp.async.bulk.tensor.3d.shared::cluster.global.mbarrier::complete_tx::bytes [%0], [%1, {%3, %4, %5}], [%2];" ::"r"(dst), "l"(m), "r"(mb), "r"(c0), "r"(c1), "r"(c2) : "memory");
}
__device__ __forceinline__ unsigned frag_col(unsigned l) { return (l & 0x61) | ((l & 6) << (2 - (l >> 6))) | ((l >> 2) & 6); }
__device__ __forceinline__ void tma5d(uint32_t dst, const CUtensorMap* m, int c0, int c4, uint32_t mb) {
  asm volatile("cp.async.bulk.tensor.5d.shared::cluster.global.mbarrier::complete_tx::bytes [%0], [%1, {%3, %5, %5, %5, %4}], [%2];" ::"r"(dst), "l"(m), "r"(mb), "r"(c0), "r"(c4), "r"(0) : "memory");
}
__device__ __forceinline__ uint64_t dsc(uint32_t lo, uint32_t hi) { return ((uint64_t)hi << 32) | lo; }
__device__ __forceinline__ void wg_fence() { asm volatile("wgmma.fence.sync.aligned;" ::: "memory"); }
__device__ __forceinline__ void wg_commit() { asm volatile("wgmma.commit_group.sync.aligned;" ::: "memory"); }
template <int N> __device__ __forceinline__ void wg_wait() { asm volatile("wgmma.wait_group.sync.aligned %0;" ::"n"(N) : "memory"); }
__device__ __forceinline__ void wgmma_n192(float (&d)[96], uint64_t da, uint64_t db, int scale_d) {
  asm volatile("{\n.reg .pred p;\nsetp.ne.b32 p, %98, 0;\n"
    "wgmma.mma_async.sync.aligned.m64n192k16.f32.bf16.bf16 "
    "{"
    "%0, %1, %2, %3, %4, %5, %6, %7, %8, %9, %10, %11, %12, %13, %14, %15, "
    "%16, %17, %18, %19, %20, %21, %22, %23, %24, %25, %26, %27, %28, %29, %30, %31, "
    "%32, %33, %34, %35, %36, %37, %38, %39, %40, %41, %42, %43, %44, %45, %46, %47, "
    "%48, %49, %50, %51, %52, %53, %54, %55, %56, %57, %58, %59, %60, %61, %62, %63, "
    "%64, %65, %66, %67, %68, %69, %70, %71, %72, %73, %74, %75, %76, %77, %78, %79, "
    "%80, %81, %82, %83, %84, %85, %86, %87, %88, %89, %90, %91, %92, %93, %94, %95"
    "}, "
    "%96, %97, p, 1, 1, 0, 1;\n}\n"
    : "+f"(d[0]), "+f"(d[1]), "+f"(d[2]), "+f"(d[3]), "+f"(d[4]), "+f"(d[5]), "+f"(d[6]), "+f"(d[7]),
      "+f"(d[8]), "+f"(d[9]), "+f"(d[10]), "+f"(d[11]), "+f"(d[12]), "+f"(d[13]), "+f"(d[14]), "+f"(d[15]),
      "+f"(d[16]), "+f"(d[17]), "+f"(d[18]), "+f"(d[19]), "+f"(d[20]), "+f"(d[21]), "+f"(d[22]), "+f"(d[23]),
      "+f"(d[24]), "+f"(d[25]), "+f"(d[26]), "+f"(d[27]), "+f"(d[28]), "+f"(d[29]), "+f"(d[30]), "+f"(d[31]),
      "+f"(d[32]), "+f"(d[33]), "+f"(d[34]), "+f"(d[35]), "+f"(d[36]), "+f"(d[37]), "+f"(d[38]), "+f"(d[39]),
      "+f"(d[40]), "+f"(d[41]), "+f"(d[42]), "+f"(d[43]), "+f"(d[44]), "+f"(d[45]), "+f"(d[46]), "+f"(d[47]),
      "+f"(d[48]), "+f"(d[49]), "+f"(d[50]), "+f"(d[51]), "+f"(d[52]), "+f"(d[53]), "+f"(d[54]), "+f"(d[55]),
      "+f"(d[56]), "+f"(d[57]), "+f"(d[58]), "+f"(d[59]), "+f"(d[60]), "+f"(d[61]), "+f"(d[62]), "+f"(d[63]),
      "+f"(d[64]), "+f"(d[65]), "+f"(d[66]), "+f"(d[67]), "+f"(d[68]), "+f"(d[69]), "+f"(d[70]), "+f"(d[71]),
      "+f"(d[72]), "+f"(d[73]), "+f"(d[74]), "+f"(d[75]), "+f"(d[76]), "+f"(d[77]), "+f"(d[78]), "+f"(d[79]),
      "+f"(d[80]), "+f"(d[81]), "+f"(d[82]), "+f"(d[83]), "+f"(d[84]), "+f"(d[85]), "+f"(d[86]), "+f"(d[87]),
      "+f"(d[88]), "+f"(d[89]), "+f"(d[90]), "+f"(d[91]), "+f"(d[92]), "+f"(d[93]), "+f"(d[94]), "+f"(d[95])
    : "l"(da), "l"(db), "r"(scale_d));
}

__device__ __forceinline__ void wgmma_n80(float (&d)[40], uint64_t da, uint64_t db, int scale_d) {
  asm volatile("{\n.reg .pred p;\nsetp.ne.b32 p, %42, 0;\n"
    "wgmma.mma_async.sync.aligned.m64n80k16.f32.bf16.bf16 "
    "{"
    "%0, %1, %2, %3, %4, %5, %6, %7, %8, %9, %10, %11, %12, %13, %14, %15, "
    "%16, %17, %18, %19, %20, %21, %22, %23, %24, %25, %26, %27, %28, %29, %30, %31, "
    "%32, %33, %34, %35, %36, %37, %38, %39"
    "}, "
    "%40, %41, p, 1, 1, 0, 1;\n}\n"
    : "+f"(d[0]), "+f"(d[1]), "+f"(d[2]), "+f"(d[3]), "+f"(d[4]), "+f"(d[5]), "+f"(d[6]), "+f"(d[7]),
      "+f"(d[8]), "+f"(d[9]), "+f"(d[10]), "+f"(d[11]), "+f"(d[12]), "+f"(d[13]), "+f"(d[14]), "+f"(d[15]),
      "+f"(d[16]), "+f"(d[17]), "+f"(d[18]), "+f"(d[19]), "+f"(d[20]), "+f"(d[21]), "+f"(d[22]), "+f"(d[23]),
      "+f"(d[24]), "+f"(d[25]), "+f"(d[26]), "+f"(d[27]), "+f"(d[28]), "+f"(d[29]), "+f"(d[30]), "+f"(d[31]),
      "+f"(d[32]), "+f"(d[33]), "+f"(d[34]), "+f"(d[35]), "+f"(d[36]), "+f"(d[37]), "+f"(d[38]), "+f"(d[39])
    : "l"(da), "l"(db), "r"(scale_d));
}

__device__ __forceinline__ void hmma(float* c, uint32_t a0, uint32_t a1, uint32_t a2, uint32_t a3, uint32_t b0, uint32_t b1) {
  asm volatile("mma.sync.aligned.m16n8k16.row.col.f32.f16.f16.f32 {%0,%1,%2,%3}, {%4,%5,%6,%7}, {%8,%9}, {%0,%1,%2,%3};"
      : "+f"(c[0]), "+f"(c[1]), "+f"(c[2]), "+f"(c[3]) : "r"(a0), "r"(a1), "r"(a2), "r"(a3), "r"(b0), "r"(b1));
}
__device__ __forceinline__ void ldsm4(uint32_t* r, uint32_t a) { asm volatile("ldmatrix.sync.aligned.m8n8.x4.shared.b16 {%0,%1,%2,%3}, [%4];" : "=r"(r[0]), "=r"(r[1]), "=r"(r[2]), "=r"(r[3]) : "r"(a) : "memory"); }
__device__ __forceinline__ void ldsm4t(uint32_t* r, uint32_t a) { asm volatile("ldmatrix.sync.aligned.m8n8.x4.trans.shared.b16 {%0,%1,%2,%3}, [%4];" : "=r"(r[0]), "=r"(r[1]), "=r"(r[2]), "=r"(r[3]) : "r"(a) : "memory"); }
__device__ __forceinline__ void stsm4(uint32_t a, uint32_t r0, uint32_t r1, uint32_t r2, uint32_t r3) { asm volatile("stmatrix.sync.aligned.m8n8.x4.shared.b16 [%0], {%1,%2,%3,%4};" ::"r"(a), "r"(r0), "r"(r1), "r"(r2), "r"(r3) : "memory"); }
__device__ __forceinline__ void stsm4t(uint32_t a, uint32_t r0, uint32_t r1, uint32_t r2, uint32_t r3) { asm volatile("stmatrix.sync.aligned.m8n8.x4.trans.shared.b16 [%0], {%1,%2,%3,%4};" ::"r"(a), "r"(r0), "r"(r1), "r"(r2), "r"(r3) : "memory"); }
__device__ __forceinline__ uint32_t lds32(uint32_t a) { uint32_t v; asm volatile("ld.shared.u32 %0, [%1];" : "=r"(v) : "r"(a) : "memory"); return v; }
__device__ __forceinline__ uint2 lds64(uint32_t a) { uint2 v; asm volatile("ld.shared.v2.u32 {%0,%1}, [%2];" : "=r"(v.x), "=r"(v.y) : "r"(a) : "memory"); return v; }
__device__ __forceinline__ uint4 lds128(uint32_t a) { uint4 v; asm volatile("ld.shared.v4.u32 {%0,%1,%2,%3}, [%4];" : "=r"(v.x), "=r"(v.y), "=r"(v.z), "=r"(v.w) : "r"(a) : "memory"); return v; }
__device__ __forceinline__ void sts16(uint32_t a, uint32_t v) { asm volatile("st.shared.u16 [%0], %1;" ::"r"(a), "h"((unsigned short)v) : "memory"); }
__device__ __forceinline__ void sts32(uint32_t a, uint32_t v) { asm volatile("st.shared.u32 [%0], %1;" ::"r"(a), "r"(v) : "memory"); }
__device__ __forceinline__ void sts64(uint32_t a, uint32_t x, uint32_t y) { asm volatile("st.shared.v2.u32 [%0], {%1,%2};" ::"r"(a), "r"(x), "r"(y) : "memory"); }
__device__ __forceinline__ void sts128(uint32_t a, uint32_t x, uint32_t y, uint32_t z, uint32_t w) { asm volatile("st.shared.v4.u32 [%0], {%1,%2,%3,%4};" ::"r"(a), "r"(x), "r"(y), "r"(z), "r"(w) : "memory"); }
__device__ __forceinline__ uint32_t ldg32(const void* a) { uint32_t v; asm volatile("ld.global.nc.u32 %0, [%1];" : "=r"(v) : "l"(a)); return v; }
__device__ __forceinline__ uint32_t ldg16(const void* a) { uint32_t v; asm volatile("ld.global.nc.u16 %0, [%1];" : "=r"(v) : "l"(a)); return v; }
__device__ __forceinline__ float bflo(uint32_t v) { return __uint_as_float(v << 16); }
__device__ __forceinline__ float bfhi(uint32_t v) { return __uint_as_float(v & 0xffff0000u); }
__device__ __forceinline__ uint32_t pack_bf(float lo, float hi) { uint32_t r; asm("cvt.rn.bf16x2.f32 %0, %1, %2;" : "=r"(r) : "f"(hi), "f"(lo)); return r; }
__device__ __forceinline__ uint32_t pack_h(float lo, float hi) { uint32_t r; asm("cvt.rn.f16x2.f32 %0, %1, %2;" : "=r"(r) : "f"(hi), "f"(lo)); return r; }
__device__ __forceinline__ float rnd_bf(float v) { return __bfloat162float(__float2bfloat16_rn(v)); }
__device__ __forceinline__ float ex2a(float v) { float r; asm("ex2.approx.ftz.f32 %0, %1;" : "=f"(r) : "f"(v)); return r; }
__device__ __forceinline__ float tanha(float v) { float r; asm("tanh.approx.f32 %0, %1;" : "=f"(r) : "f"(v)); return r; }
__device__ __forceinline__ uint32_t hadd(uint32_t a, uint32_t b) { uint32_t r; asm("add.rn.f16x2 %0, %1, %2;" : "=r"(r) : "r"(a), "r"(b)); return r; }
__device__ __forceinline__ uint32_t badd(uint32_t a, uint32_t b) { uint32_t r; asm("add.rn.bf16x2 %0, %1, %2;" : "=r"(r) : "r"(a), "r"(b)); return r; }
__device__ __forceinline__ uint32_t bmul(uint32_t a, uint32_t b) { uint32_t r; asm("mul.rn.bf16x2 %0, %1, %2;" : "=r"(r) : "r"(a), "r"(b)); return r; }
__device__ __forceinline__ uint32_t bfma(uint32_t a, uint32_t b, uint32_t c) { uint32_t r; asm("fma.rn.bf16x2 %0, %1, %2, %3;" : "=r"(r) : "r"(a), "r"(b), "r"(c)); return r; }
__device__ __forceinline__ float tanhv(float v) { float r; asm volatile("tanh.approx.f32 %0, %1;" : "=f"(r) : "f"(v)); return r; }
__device__ __forceinline__ uint32_t bsub(uint32_t a, uint32_t b) { uint32_t r; asm("sub.rn.bf16x2 %0, %1, %2;" : "=r"(r) : "r"(a), "r"(b)); return r; }
__device__ __forceinline__ uint32_t dup(uint32_t v, uint32_t nz) { uint32_t r; asm volatile("add.rn.f32 %0, %1, %2;" : "=r"(r) : "r"(v), "r"(nz)); return r; }
__device__ __forceinline__ void bmma(float* c, uint32_t a0, uint32_t a1, uint32_t a2, uint32_t a3, uint32_t b0, uint32_t b1) {
  asm("mma.sync.aligned.m16n8k16.row.col.f32.bf16.bf16.f32 {%0,%1,%2,%3}, {%4,%5,%6,%7}, {%8,%9}, {%0,%1,%2,%3};"
      : "+f"(c[0]), "+f"(c[1]), "+f"(c[2]), "+f"(c[3]) : "r"(a0), "r"(a1), "r"(a2), "r"(a3), "r"(b0), "r"(b1));
}
__device__ __forceinline__ uint32_t odd_pair(uint32_t a, uint32_t b) { return __byte_perm(a, b, 0x5432); }
__device__ __forceinline__ int upos(int c) { return c ^ ((c >> 5) & 7) ^ ((c >> 3) & 1); }
__device__ __forceinline__ int uoff(int pos) { return (pos >> 1) * 160 + (pos & 1) * 16; }

struct cf { float r, i; };
__device__ __forceinline__ cf cmul(cf a, cf b) { cf o; o.r = fmaf(a.r, b.r, -a.i * b.i); o.i = fmaf(a.r, b.i, a.i * b.r); return o; }
__device__ __forceinline__ cf cmulj(cf a, cf b) { cf o; o.r = fmaf(a.r, b.r, a.i * b.i); o.i = fmaf(a.i, b.r, -a.r * b.i); return o; }
__device__ __forceinline__ cf csq(cf a) { cf o; o.r = fmaf(a.r, a.r, -a.i * a.i); o.i = (a.r + a.r) * a.i; return o; }
struct hp { uint32_t r, i; };
__device__ __forceinline__ hp hpack(cf a, cf b) { hp o; o.r = pack_h(a.r, b.r); o.i = pack_h(a.i, b.i); return o; }
__device__ __forceinline__ hp hmulc(hp a, uint32_t c) {
  __half2 ar = *reinterpret_cast<__half2*>(&a.r), ai = *reinterpret_cast<__half2*>(&a.i), cc = *reinterpret_cast<__half2*>(&c);
  __half2 orr = __hfma2(ar, __low2half2(cc), __hneg2(__hmul2(ai, __high2half2(cc))));
  __half2 oi = __hfma2(ar, __high2half2(cc), __hmul2(ai, __low2half2(cc)));
  hp o; o.r = *reinterpret_cast<uint32_t*>(&orr); o.i = *reinterpret_cast<uint32_t*>(&oi); return o;
}
__device__ __forceinline__ hp hmulj(hp a, uint32_t c) {
  __half2 ar = *reinterpret_cast<__half2*>(&a.r), ai = *reinterpret_cast<__half2*>(&a.i), cc = *reinterpret_cast<__half2*>(&c);
  __half2 orr = __hfma2(ar, __low2half2(cc), __hmul2(ai, __high2half2(cc)));
  __half2 oi = __hfma2(ai, __low2half2(cc), __hneg2(__hmul2(ar, __high2half2(cc))));
  hp o; o.r = *reinterpret_cast<uint32_t*>(&orr); o.i = *reinterpret_cast<uint32_t*>(&oi); return o;
}
__device__ __forceinline__ hp hmule(hp a, hp b) {
  __half2 ar = *reinterpret_cast<__half2*>(&a.r), ai = *reinterpret_cast<__half2*>(&a.i);
  __half2 br = *reinterpret_cast<__half2*>(&b.r), bi = *reinterpret_cast<__half2*>(&b.i);
  __half2 orr = __hfma2(ar, br, __hneg2(__hmul2(ai, bi))), oi = __hfma2(ar, bi, __hmul2(ai, br));
  hp o; o.r = *reinterpret_cast<uint32_t*>(&orr); o.i = *reinterpret_cast<uint32_t*>(&oi); return o;
}
__device__ __forceinline__ void sts_tile(uint32_t a, const hp* t) {
  sts128(a, t[0].r, t[1].r, t[2].r, t[3].r);
  sts128(a + 512, t[0].i, t[1].i, t[2].i, t[3].i);
}
template <int STEP> __device__ __forceinline__ void put2(uint32_t a0, uint32_t a1, uint32_t h, uint32_t sel) {
  const uint32_t x = __byte_perm(h, h, sel), y = x >> 16;
  sts16(a0, x); sts16(a0 + STEP * 4 + 2, x);
  sts16(a1, y); sts16(a1 + STEP * 4 + 2, y);
}

__device__ __forceinline__ void spare_work(const Params& p, const CUtensorMap* tmW1, int k, int tid) {
  const int lane = tid & 31;
  unsigned ep = 0;
  if (tid >= 480) ep = p.scr->epoch[128 + k] + 1;
  if (tid == 480) {
    for (int i = 0; i < 8; i++) mbar_init(bar + 8 * i, i < 4 ? 1 : 12);
    asm volatile("fence.mbarrier_init.release.cluster;" ::: "memory");
    fence_async_smem();
  }
  __syncthreads();
  float a[2][4] = {{0.f, 0.f, 0.f, 0.f}, {0.f, 0.f, 0.f, 0.f}};
  if (tid >= 480) {
    if (elect1()) {
#pragma unroll 1
      for (int s = 0; s < 10; s++) {
        mbar_wait(bar + 8 * (4 + (s & 3)), ((s >> 2) & 1) ^ 1);
        mbar_expect(bar + 8 * (s & 3), 49152);
#pragma unroll 1
        for (int b = 0; b < 2; b++) tma3d(sb + (s & 3) * 49152 + b * 24576, tmW1, 0, s * 64, k * 6 + b * 3, bar + 8 * (s & 3));
      }
    }
    __syncwarp();
  } else if (tid < 384) {
    const uint32_t idn = (lane >> 3) == (lane & 3) ? ((lane & 4) ? 0x3f800000u : 0x3f80u) : 0u;
#pragma unroll 1
    for (int s = 0; s < 10; s++) {
      mbar_wait(bar + 8 * (s & 3), (s >> 2) & 1);
      const uint32_t ad = sb + (s & 3) * 49152 + (tid >> 6) * 8192 + (tid & 63) * 16;
#pragma unroll
      for (int i = 0; i < 8; i += 2) {
        const uint4 v = lds128(ad + i * 1024), w = lds128(ad + i * 1024 + 1024);
        bmma(a[0], v.x, v.y, w.x, w.y, idn, idn);
        bmma(a[1], v.z, v.w, w.z, w.w, idn, idn);
      }
      __syncwarp();
      if (lane == 0) mbar_arrive(bar + 8 * (4 + (s & 3)));
    }
#pragma unroll
    for (int e = 0; e < 8; e++) {
      float v = a[e >> 2][e & 3];
      v += __shfl_xor_sync(0xffffffffu, v, 9);
      v += __shfl_xor_sync(0xffffffffu, v, 18);
      a[e >> 2][e & 3] = v;
    }
    const int odd = (tid >> 5) & 1, c8 = (tid >> 6) * 8 + ((lane & 7) ^ (odd * 4));
    if (odd && lane < 8) {
      sts128(sb + 196608 + c8 * 32, __float_as_uint(a[0][0]), __float_as_uint(a[0][1]), __float_as_uint(a[0][2]), __float_as_uint(a[0][3]));
      sts128(sb + 196608 + c8 * 32 + 16, __float_as_uint(a[1][0]), __float_as_uint(a[1][1]), __float_as_uint(a[1][2]), __float_as_uint(a[1][3]));
    }
    bar_sync(1 + (tid >> 6), 64);
    if (!odd && lane < 8) {
      const uint4 v = lds128(sb + 196608 + c8 * 32), w = lds128(sb + 196608 + c8 * 32 + 16);
      float2* dst = (float2*)(p.scr->cs + k * 384 + (c8 >> 2) * 32) + (c8 & 3);
      dst[0] = make_float2(a[0][0] + __uint_as_float(v.x), a[0][1] + __uint_as_float(v.y));
      dst[4] = make_float2(a[0][2] + __uint_as_float(v.z), a[0][3] + __uint_as_float(v.w));
      dst[8] = make_float2(a[1][0] + __uint_as_float(w.x), a[1][1] + __uint_as_float(w.y));
      dst[12] = make_float2(a[1][2] + __uint_as_float(w.z), a[1][3] + __uint_as_float(w.w));
    }
  }
  __syncthreads();
  if (tid == 480) {
    publish(p.scr->cnt + (C_CS + k) * 32);
    p.scr->epoch[128 + k] = ep;
    poll_cnt(p.scr->cnt + C_LN * 32, ep * 128);
  }
}

__device__ __forceinline__ void load1(int s, const CUtensorMap* tmX, const CUtensorMap* tmW1, int rg1, int j1) {
  const uint32_t d = sb + (s & 3) * SLOT1, mb = bar + 8 * (B_FULL1 + s);
  mbar_expect(mb, SLOT1);
  tma2d(d, tmX, s * 64, rg1 * 128, mb);
  tma3d(d + 16384, tmW1, 0, s * 64, j1 * 3, mb);
}
__device__ __forceinline__ void load_x(uint32_t (&xv)[2][10], const __nv_bfloat16* xa, const __nv_bfloat16* xb, int rstep) {
#pragma unroll
  for (int r = 0; r < 2; r++) {
    const uint4 a = __ldg((const uint4*)(xa + r * rstep)), b = __ldg((const uint4*)(xa + r * rstep + 32));
    const uint2 c = __ldg((const uint2*)(xb + r * rstep + 64));
    xv[r][0] = a.x; xv[r][1] = a.y; xv[r][2] = a.z; xv[r][3] = a.w; xv[r][4] = b.x; xv[r][5] = b.y; xv[r][6] = b.z; xv[r][7] = b.w;
    xv[r][8] = c.x; xv[r][9] = c.y;
  }
}

__device__ __forceinline__ uint32_t pin(uint32_t v, uint32_t z) { uint32_t r; asm volatile("add.u32 %0, %1, %2;" : "=r"(r) : "r"(v), "r"(z)); return r; }
struct Comb { uint32_t o[7]; };
__device__ __forceinline__ Comb comb_setup(int tid, uint32_t z) {
  Comb k;
  const int c = tid & 127, c1 = c < 112 ? c + 32 : c - 112, c2 = c < 112 ? c + 144 : c - 96;
  const uint32_t zr = ZA1 + (c & 7) * 16, a2 = ZA2 + ((c & ~15) - 32 + ((((c >> 1) & 7) + (c & 1) * 8) ^ ((c & 1) * 4))) * 16;
  k.o[0] = uoff(upos(c1)); k.o[1] = uoff(upos(c2));
  k.o[2] = c < 112 ? ZA1 + 512 + ((2 * c) ^ ((c >> 2) & 1)) * 16 : zr;
  k.o[3] = c1 >= 64 ? a2 : zr; k.o[4] = c < 112 ? a2 + 112 * 16 : zr;
  k.o[5] = ((c1 >> 4) * 1280 + (c & 15)) * 16; k.o[6] = ((c2 >> 4) * 1280 + (c & 15)) * 16;
#pragma unroll
  for (int i = 0; i < 7; i++) k.o[i] = pin(k.o[i], z);
  return k;
}
template <class F> __device__ __forceinline__ void combine(const Comb& k, int ch, int wid, uint4* sT, F&& after_reads) {
  const uint32_t ub = sb + OFF_U + ch * 32, zb = sb + OFF_Z + ch * ZSZ;
  const int row = (wid & 15) * 5 + ch;
  char* dst = (char*)(sT + ((wid >> 4) * 16 * 80 + row) * 16);
  mbar_wait(bar + 8 * (B_PART + ch), 0);
  const uint32_t sc = lds32(sb + OFF_CHC + ch * 8);
  const uint4 y0 = lds128(zb + k.o[2]), y1 = lds128(zb + (k.o[2] ^ 16));
  const uint4 v2 = lds128(zb + k.o[3]), u2 = lds128(zb + k.o[4]);
  const uint4 v0 = lds128(ub + k.o[0]), u0 = lds128(ub + k.o[1]);
  fence_async_smem();
  after_reads();
  *(uint4*)(dst + (k.o[5] ^ ((row & 7) * 16))) =
      make_uint4(bmul(badd(badd(y0.x, v2.x), v0.x), sc), bmul(badd(badd(y0.y, v2.y), v0.y), sc),
                 bmul(badd(badd(y1.x, v2.z), v0.z), sc), bmul(badd(badd(y1.y, v2.w), v0.w), sc));
  *(uint4*)(dst + (k.o[6] ^ ((row & 7) * 16))) =
      make_uint4(bmul(badd(badd(y0.z, u2.x), u0.x), sc), bmul(badd(badd(y0.w, u2.y), u0.y), sc),
                 bmul(badd(badd(y1.z, u2.z), u0.z), sc), bmul(badd(badd(y1.w, u2.w), u0.w), sc));
  __syncwarp();
  if (elect1()) mbar_arrive(bar + 8 * (B_FREE + ch));
}

__device__ __forceinline__ void load2(int s, uint32_t d, const uint4* srcA, const uint4* srcB) {
  const uint32_t mb = bar + 8 * (B_FULL2 + s);
  mbar_expect(mb, SLOT2);
  bulk_g2s(d, srcA, 16384, mb);
  bulk_g2s(d + 16384, srcB, 10240, mb);
}

template <bool USE_SMID>
__global__ void __launch_bounds__(512, 1)
fused_s4_ffn_kernel(const Params p, const __grid_constant__ CUtensorMap tmX, const __grid_constant__ CUtensorMap tmW1,
                    const __grid_constant__ CUtensorMap tmU, const __grid_constant__ CUtensorMap tmW2) {
  extern __shared__ __align__(1024) unsigned char smem_raw[];
  const int tid = threadIdx.x, lane = tid & 31;
  uint32_t sid;
  if (USE_SMID) asm("mov.u32 %0, %smid;" : "=r"(sid)); else sid = blockIdx.x;
  const int wid = sid < 120 ? sid : sid - 4;
  uint32_t pa[6], pld, pds;
  const unsigned pw = min(tid >> 5, 14), part = (pw * 13) >> 6;
  const unsigned ch = (wid >> 4) * 80 + frag_col(((wid & 15) - part) * 5 + pw);
  const unsigned o = (ch * 3 + part) * 32 + lane;
  {
    asm volatile("{\n.reg .pred p;\nsetp.lt.u32 p, %0, 256;\n@p nanosleep.u32 %1;\n}" ::"r"(tid), "n"(LDLY));
    pld = ldg16(p.logdt + ch);
    pa[0] = ldg32((const uint32_t*)p.are + o); pa[1] = ldg32((const uint32_t*)p.aim + o);
    pds = ldg16(p.dskip + ch);
    pa[2] = ldg32((const uint32_t*)p.bre + o); pa[3] = ldg32((const uint32_t*)p.bim + o);
    pa[4] = ldg32((const uint32_t*)p.cre + o); pa[5] = ldg32((const uint32_t*)p.cim + o);
  }
  const int warp = __shfl_sync(0xffffffffu, tid >> 5, 0);
  const int g = lane >> 2, q = lane & 3;
  if (sid - 120u < 4u) { spare_work(p, &tmW1, sid - 120, tid); return; }
  unsigned* const cnt = p.scr->cnt;

  float kacc[6][4];
  const int kch = warp - 10;
  float dt, k0;
  uint32_t xv[2][10], xs[2], mw;
  {
    unsigned ep0;
    if (warp == 15) {
      ep0 = p.scr->epoch[wid];
      if ((uint32_t)__cvta_generic_to_shared(smem_raw) != sb) __trap();
    }
    if (elect1()) {
      const int gi = (warp + 1) & 15;
#pragma unroll
      for (int i = 0; i < 6; i++) mbar_init(bar + 48 * gi + 8 * i, gi < 7 ? 1 : gi == 7 ? 2 : gi < 10 ? 4 : 8);
      asm volatile("fence.mbarrier_init.release.cluster;" ::: "memory");
    }
    const uint32_t z0 = sid >> 8;
#pragma unroll
    for (int j = 0; j < 24; j++) kacc[j >> 2][j & 3] = __uint_as_float(pin(z0, z0));
    const uint32_t ks = sb + OFF_KS + warp * 4096;
    const uint32_t st = pin(ks + lane * 16, z0);
    const uint32_t kw = pin(ks + 3584 + (lane >> 1) * 8 + (lane & 1) * 2, z0), kr = pin(ks + 3584 + q * 8, z0);
    const uint32_t kb = pin(ks + ((lane >> 3) & 1) * 512 + ((lane >> 4) * 8 + (lane & 7)) * 16, z0);
    const __nv_bfloat16* xr = p.x + (wid * 16 + ((g >> 1) << 2) + (g & 1)) * DM;
    const __nv_bfloat16 *xa = xr + (warp & 7) * 80 + q * 8, *xb = xr + (warp & 7) * 80 + q * 4;
    asm volatile("add.u64 %0, %0, %3;\nadd.u64 %1, %1, %3;\nadd.u64 %2, %2, %3;" : "+l"(xr), "+l"(xa), "+l"(xb) : "l"((uint64_t)z0));
    if (warp < 8) bar_sync(14, 512); else bar_arrive(14, 512);
    if (warp == 15) {
      sts32(sb + OFF_ZERO + lane * 4, 0);
      int gpc, i;
      if (sid < 64) { gpc = (sid & 15) >> 1; i = sid >> 4; }
      else if (sid < 120) { const int t = sid - 64; i = t / 14; gpc = 1 + ((t - i * 14) >> 1); i += 4; }
      else { gpc = 0; i = 4 + ((sid - 124) >> 1); }
      const int qi = ((0x52741630 >> (4 * i)) & 7) * 2 + (sid & 1);
      const int rg = 4 * (gpc >> 1) + (qi >> 3) * 2 + (qi & 1), jc = 4 * (gpc & 1) + ((qi >> 1) & 3);
      sts64(sb + OFF_EP + 8, rg, jc);
      __syncwarp();
      if (elect1()) {
        asm volatile("prefetch.tensormap [%0];\nprefetch.tensormap [%1];\nprefetch.tensormap [%2];\nprefetch.tensormap [%3];" ::"l"(&tmW2), "l"(&tmX), "l"(&tmW1), "l"(&tmU) : "memory");
        __nanosleep(DELAY_NS);
        bulk_prefetch(p.x + wid * 16 * DM, 16 * DM * 2);
        mbar_expect(bar + 8 * B_W2, 96 * 176);
      }
      __syncwarp();
      load_x(xv, xa, xb, 2 * DM);
      xs[0] = __ldg((const uint32_t*)xr); xs[1] = __ldg((const uint32_t*)(xr + 2 * DM));
      bar_sync(5, 256);
      sts32(sb + OFF_EP + 4, xv[1][9]);
      if (elect1()) {
        tma5d(sb + OFF_W2S, &tmW2, (wid & 7) * 80, (wid >> 3) * 3, bar + 8 * B_W2);
        p.scr->epoch[wid] = ep0 + 1;
        sts32(sb + OFF_EP, ep0 + 1);
      }
      __syncwarp();
    }
    float zr, th, zr1, th1;
    cf c, c1;
    dt = rnd_bf(expf(bflo(pld)));
    {
      const float dl2 = dt * 1.4426950408889634f;
      zr = bflo(pa[0]) * dl2; th = bflo(pa[1]) * dt; zr1 = bfhi(pa[0]) * dl2; th1 = bfhi(pa[1]) * dt;
    }
    if (warp < 15) {
      c = cmul(cf{bflo(pa[4]), bflo(pa[5])}, cf{bflo(pa[2]), bflo(pa[3])});
      c1 = cmul(cf{bfhi(pa[4]), bfhi(pa[5])}, cf{bfhi(pa[2]), bfhi(pa[3])});
      mw = __reduce_max_sync(0xffffffffu, __float_as_uint(fmaxf(fmaxf(fabsf(c.r), fabsf(c.i)), fmaxf(fabsf(c1.r), fabsf(c1.i)))));
      mw = min(max(mw & 0x7f800000u, 20u << 23), 240u << 23);
      const float sc = __uint_as_float((259u << 23) - mw);
      k0 = c.r + c1.r;
      c.r *= sc; c.i *= -sc; c1.r *= sc; c1.i *= -sc;
      if (warp >= 8) {
        load_x(xv, xa, xb, 2 * DM);
        xs[0] = __ldg((const uint32_t*)xr); xs[1] = __ldg((const uint32_t*)(xr + 2 * DM));
        bar_arrive(5, 256);
      }
    }
    {
#pragma unroll 1
      for (int it = 0; it < 2; it++) {
        if (it == 1 && warp >= 8) {
          float sm[4] = {0.f, 0.f, 0.f, 0.f}, g0[4] = {0.f, 0.f, 0.f, 0.f}, g1[4] = {0.f, 0.f, 0.f, 0.f};
#pragma unroll
          for (int r = 0; r < 2; r++)
            xs[r] = fabsf(bflo(xs[r]) - bfhi(xs[r])) * 8.f < fabsf(bflo(xs[r])) ? __byte_perm(xs[r], 0, 0x1010) : 0u;
#pragma unroll
          for (int i = 0; i < 10; i += 2) {
            const uint32_t a0 = bsub(xv[0][i], xs[0]), a1 = bsub(xv[1][i], xs[1]), a2 = bsub(xv[0][i + 1], xs[0]), a3 = bsub(xv[1][i + 1], xs[1]);
            bmma(sm, a0, a1, a2, a3, 0x3f803f80u, 0x3f803f80u);
            bmma(g0, a0, a1, a2, a3, xv[0][i], xv[0][i + 1]);
            bmma(g1, a0, a1, a2, a3, xv[1][i], xv[1][i + 1]);
          }
          if (q == (g >> 1))
            sts128(sb + OFF_LNP + (warp - 8) * 128 + g * 16, __float_as_uint(sm[0]), __float_as_uint((g & 1) ? g0[1] : g0[0]),
                   __float_as_uint(sm[2]), __float_as_uint((g & 1) ? g1[3] : g1[2]));
          if (warp != 11) bar_arrive(1, 256);
        }
        if (warp == 15) continue;
        float m = ex2a(zr);
        const cf w1 = cf{m * __cosf(th), m * __sinf(th)};
        m = ex2a(zr * 8.f);
        const cf w8 = cf{m * __cosf(th * 8.f), m * __sinf(th * 8.f)};
        const cf w16 = csq(w8), w32 = csq(w16), w64 = csq(w32), w128 = csq(w64), w256 = csq(w128), w512 = csq(w256), w1024 = csq(w512);
        hp lo[4];
        lo[0] = hpack(cf{1.f, 0.f}, w8);
        lo[1] = hmulc(lo[0], pack_h(w16.r, w16.i));
        { const uint32_t k = pack_h(w32.r, w32.i); lo[2] = hmulc(lo[0], k); lo[3] = hmulc(lo[1], k); }
        sts_tile(st, lo);
        { const uint32_t k = pack_h(w64.r, w64.i); sts16(kw, k); sts16(kw + 4, k >> 16); }
        const uint32_t k256 = pack_h(w256.r, w256.i), k512 = pack_h(w512.r, w512.i);
        const cf t8 = cmulj(c, w8);
        { const cf u0 = cmulj(t8, w1024), u1 = cmulj(u0, w256);
          const hp a = hpack(u0, u1), b = hmulj(a, k512);
          sts128(st + 3072, a.r, b.r, a.i, b.i); }
        const cf t1 = cmulj(c, w1), t2 = cmulj(t1, w1), t3 = cmulj(t2, w1), t4 = cmulj(t3, w1);
        const cf t5 = cmulj(t4, w1), t6 = cmulj(t5, w1), t7 = cmulj(t6, w1);
        hp T0[4], T1[4];
        T0[0] = hpack(t4, t8); T0[1] = hpack(t2, t6); T0[2] = hpack(t1, t5); T0[3] = hpack(t3, t7);
        T1[0] = hmulj(T0[0], k256); T1[1] = hmulj(T0[1], k256); T1[2] = hmulj(T0[0], k512); T1[3] = hmulj(T1[0], k512);
        sts_tile(st + 2048, T1);
        sts_tile(st + 1024, T0);
        __syncwarp();
        uint32_t bc[4];
        ldsm4t(bc, st + 3072);
#pragma unroll
        for (int m2 = 0; m2 < 4; m2 += 2) {
          uint32_t l0[4], b0[4], b1[4];
          ldsm4t(l0, kb + m2 * 128);
          ldsm4t(b0, kb + 1024 + m2 * 128);
          ldsm4t(b1, kb + 2048 + m2 * 128);
#pragma unroll
          for (int i = 0; i < 2; i++) {
            const uint2 kv = lds64(kr + (m2 + i) * 32);
            const hp k64 = {kv.x, kv.y}, L0 = {l0[2 * i], l0[2 * i + 1]};
            const hp L1 = hmule(L0, k64), L2 = hmule(L1, k64), L3 = hmule(L2, k64);
            const uint32_t c0 = lane < 16 ? bc[m2 + i] : 0u, c1b = lane < 16 ? 0u : bc[m2 + i];
            const uint32_t a0 = pin(L0.r, z0), a2 = pin(L0.i, z0);
            hmma(kacc[0], a0, L1.r, a2, L1.i, b0[2 * i], b0[2 * i + 1]);
            hmma(kacc[2], a0, L1.r, a2, L1.i, b1[2 * i], b1[2 * i + 1]);
            hmma(kacc[4], a0, L1.r, a2, L1.i, c0, c1b);
            hmma(kacc[1], L2.r, L3.r, L2.i, L3.i, b0[2 * i], b0[2 * i + 1]);
            hmma(kacc[3], L2.r, L3.r, L2.i, L3.i, b1[2 * i], b1[2 * i + 1]);
            hmma(kacc[5], L2.r, L3.r, L2.i, L3.i, c0, c1b);
          }
        }
        __syncwarp();
        zr = zr1; th = th1; c = c1;
      }
    }
    if (warp >= 8) bar_arrive(6, 512);
    if (warp < 10) {
#pragma unroll
      for (int j = 0; j < 6; j++)
        sts128(st + j * 512, __float_as_uint(kacc[j][0]), __float_as_uint(kacc[j][1]), __float_as_uint(kacc[j][2]), __float_as_uint(kacc[j][3]));
      sts64(ks + 3072 + lane * 8, __float_as_uint(k0), mw);
    }
    if (warp == 11) {
      bar_sync(1, 256);
      float s1 = 0.f, s2 = 0.f;
#pragma unroll
      for (int w = 0; w < 8; w++) {
        const uint2 v = lds64(sb + OFF_LNP + w * 128 + g * 16 + (q & 1) * 8);
        s1 += __uint_as_float(v.x); s2 += __uint_as_float(v.y);
      }
      const float md = s1 * (1.f / DM), mean = bflo((q & 1) ? xs[1] : xs[0]) + md;
      const float var = fmaxf(fmaf(-md, mean, s2 * (1.f / DM)), 0.f);
      const float m = rnd_bf(mean);
      float sd, ri;
      asm("sqrt.approx.f32 %0, %1;" : "=f"(sd) : "f"(rnd_bf(rnd_bf(var) + 1e-5f)));
      asm("rcp.approx.f32 %0, %1;" : "=f"(ri) : "f"(rnd_bf(sd)));
      if (q < 2) {
        p.scr->stats[wid * 16 + ((g >> 1) << 2) + (g & 1) + 2 * q] = make_float2(-m, 0.5f * ri);
        sts64(sb + OFF_STAT + g * 16 + q * 8, __float_as_uint(-m * ri), __float_as_uint(ri));
      }
      __syncwarp();
    }
    if (warp == 15) {
      const uint2 rj = lds64(sb + OFF_EP + 8);
      mbar_wait(bar + 8 * B_W2, 0);
#pragma unroll 1
      for (int uu = 0; uu < 3; uu++) {
        if (elect1()) {
          load1(uu, &tmX, &tmW1, rj.x, rj.y);
          if (uu == 2) bulk_prefetch(p.w1 + wid * 5 * FF, 5 * FF * 2);
        }
        const uint32_t a = sb + OFF_W2S + (uu * 32 + lane) * 176;
        const int rem = ((wid >> 3) & 1) * 3 + uu;
        uint4* dst = p.scr->w2p + ((wid & 7) * 24 + 8 * (rem >> 1) + (wid >> 4)) * 640 + ((rem & 1) * 4 + (lane >> 3)) * 80 + (lane & 7);
        uint4 v[10];
#pragma unroll
        for (int i = 0; i < 10; i++) v[i] = lds128(a + i * 16);
#pragma unroll
        for (int i = 0; i < 8; i++)
          dst[8 * i] = make_uint4(bmul((&v[i & 4].x)[i & 3], 0x3f003f00u), bmul((&v[(i & 4) + 1].x)[i & 3], 0x3f003f00u),
                                  bmul((&v[(i & 4) + 2].x)[i & 3], 0x3f003f00u), bmul((&v[(i & 4) + 3].x)[i & 3], 0x3f003f00u));
        dst[64] = make_uint4(bmul(v[8].x, 0x3f003f00u), bmul(v[8].z, 0x3f003f00u), bmul(v[9].x, 0x3f003f00u), bmul(v[9].z, 0x3f003f00u));
        dst[72] = make_uint4(bmul(v[8].y, 0x3f003f00u), bmul(v[8].w, 0x3f003f00u), bmul(v[9].y, 0x3f003f00u), bmul(v[9].w, 0x3f003f00u));
      }
      fence_async_smem();
      __syncwarp();
      if (elect1()) load1(3, &tmX, &tmW1, rj.x, rj.y);
      __syncwarp();
    }
  }

  if (warp < 8) {
    float acc[96];
    const uint32_t alo = ((sb >> 4) | (1 << 16)) + (warp >> 2) * 512;
    bar_arrive(0, 512);
#pragma unroll 1
    for (int s = 0; s < 10; s++) {
      const uint32_t so = (s & 3) * (SLOT1 >> 4);
      mbar_wait(bar + 8 * (B_FULL1 + s), 0);
      if (s == 0) bar_sync(6, 512);
      wg_fence();
#pragma unroll
      for (int kk = 0; kk < 4; kk++)
        wgmma_n192(acc, dsc(alo + so + kk * 2, 0x40000040u), dsc((((sb + 16384) >> 4) | (512 << 16)) + so + kk * 128, 0x40000040u), (s | kk) != 0);
      wg_commit();
      wg_wait<1>();
      if (lane == 0) mbar_arrive(bar + 8 * (B_REL1 + s));
    }
    wg_wait<0>();
    bar_arrive(14, 384);
    bar_arrive(7, 384);
    mbar_wait(bar + 8 * B_EPI, 0);
    const uint2 s0 = lds64(sb + OFF_STAT + (warp * 16 + g) * 8), s1 = lds64(sb + OFF_STAT + (warp * 16 + g + 8) * 8);
    const float nm0 = __uint_as_float(s0.x), r0 = __uint_as_float(s0.y), nm1 = __uint_as_float(s1.x), r1 = __uint_as_float(s1.y);
    const uint4 erj = lds128(sb + OFF_EP);
    const unsigned ep = erj.x;
    const int rg1 = erj.z, j1 = erj.w;
    uint4* hd = p.scr->h + (rg1 * 24 + j1) * 1024 + warp * 128 + g * 4 + (q ^ (g >> 1));
#pragma unroll
    for (int grp = 0; grp < 6; grp++) {
      uint32_t o0[4], o1[4];
      const uint4 cs[2] = {lds128(sb + OFF_CS + grp * 128 + q * 32), lds128(sb + OFF_CS + grp * 128 + q * 32 + 16)};
#pragma unroll
      for (int tl = 0; tl < 4; tl++) {
        const int nt = grp * 4 + tl;
        const float ca = __uint_as_float((&cs[tl >> 1].x)[(tl & 1) * 2]), cb = __uint_as_float((&cs[tl >> 1].x)[(tl & 1) * 2 + 1]);
        const float a = fmaf(nm0, ca, acc[4 * nt]) * r0, b = fmaf(nm0, cb, acc[4 * nt + 1]) * r0;
        const float c = fmaf(nm1, ca, acc[4 * nt + 2]) * r1, d = fmaf(nm1, cb, acc[4 * nt + 3]) * r1;
        o0[tl] = pack_bf(fmaf(a, tanha(a), a), fmaf(b, tanha(b), b));
        o1[tl] = pack_bf(fmaf(c, tanha(c), c), fmaf(d, tanha(d), d));
      }
      uint4* dst = hd + (grp >> 1) * 8192 + (grp & 1) * 32;
      dst[0] = make_uint4(o0[0], o0[1], o0[2], o0[3]);
      dst[64] = make_uint4(o1[0], o1[1], o1[2], o1[3]);
      if (grp < 5) __nanosleep(PACE_NS);
    }
    if (warp == 7) { bar_sync(11, 256); if (lane == 0) publish(cnt + (C_H + rg1) * 32); __syncwarp(); }
    else bar_arrive(11, 256);
    const int go = (rg1 * 128 + warp * 16 + g) * DM + j1 * 80;
    load_x(xv, p.x + go + q * 8, p.x + go + q * 4, 8 * DM);
    if (warp < 4) {
      mbar_wait(bar + 8 * B_PART, 0);
      Comb cmb;
      {
        const uint4 a = lds128(sb + OFF_CMB + tid * 16);
        const uint2 b = lds64(sb + OFF_CMB + 2048 + tid * 8);
        cmb.o[0] = a.x; cmb.o[1] = a.y; cmb.o[2] = a.z; cmb.o[3] = a.w; cmb.o[4] = b.x; cmb.o[5] = b.y;
        cmb.o[6] = lds32(sb + OFF_CMB + 3072 + tid * 4);
      }
#pragma unroll 1
      for (int ch = 0; ch < 3; ch++) {
        combine(cmb, ch, wid, p.scr->sT, [] {});
      }
    } else if (warp == WPR) {
      if (elect1()) {
        const uint4* srcA = p.scr->h + rg1 * 24 * 1024;
        const uint4* srcB = p.scr->w2p + j1 * 24 * 640;
        asm volatile("fence.proxy.async.global;" ::: "memory");
        mbar_wait(bar + 8 * B_PART, 0);
#pragma unroll
        for (int s = 0; s < 3; s++) {
          mbar_expect(bar + 8 * (B_FULL2 + s), SLOT2);
          bulk_g2s(sb + s * SLOT2 + 16384, srcB + s * 640, 10240, bar + 8 * (B_FULL2 + s));
        }
        poll_cnt(cnt + (C_H + rg1) * 32, ep * 8);
#pragma unroll
        for (int s = 0; s < 3; s++) bulk_g2s(sb + s * SLOT2, srcA + s * 1024, 16384, bar + 8 * (B_FULL2 + s));
#pragma unroll
        for (int s = 3; s < 5; s++) {
          mbar_wait(bar + 8 * (B_FREE + s - 2), 0);
          load2(s, sb + s * SLOT2, srcA + s * 1024, srcB + s * 640);
        }
      }
      __syncwarp();
    }
    float acc2[40];
    bar_sync(8, 512);
    {
      const uint32_t al2 = ((sb >> 4) | (1 << 16)) + (warp >> 2) * 512;
      uint32_t so = 0;
#pragma unroll 1
      for (int s = 0; s < 24; s++) {
        mbar_wait(bar + 8 * (B_FULL2 + s), 0);
        if (s == SK2 && warp < 4) bar_sync(4, 256);
        wg_fence();
#pragma unroll
        for (int kk = 0; kk < 4; kk++)
          wgmma_n80(acc2, dsc(al2 + so + (kk >> 1) * 32 + (kk & 1) * 2, 0x80000040u), dsc((((sb + 16384) >> 4) | (80 << 16)) + so + kk * 160, 8), (s | kk) != 0);
        wg_commit();
        so = so == (NS2 - 1) * (SLOT2 >> 4) ? 0 : so + (SLOT2 >> 4);
        if (s < SK2 - 1) {
          wg_wait<1>();
          if (lane == 0) mbar_arrive(bar + 8 * (B_REL2 + s));
        }
      }
      if (warp >= 4) { wg_wait<1>(); bar_arrive(4, 256); }
    }
    mbar_wait(bar + 8 * B_SFULL, 0);
    uint32_t sv[5][4];
    {
      const int i = lane & 7, mi = lane >> 3;
      const uint32_t a = sb + OFF_U + ((mi >> 1) * 8 + i) * 256 + (((2 * warp + (mi & 1)) ^ i) << 4);
#pragma unroll
      for (int k = 0; k < 5; k++) ldsm4t(sv[k], a + k * 4096);
    }
    wg_wait<0>();
#pragma unroll
    for (int hh = 0; hh < 2; hh++) {
      uint32_t o[10];
      __nv_bfloat16* op = p.out + go + hh * 8 * DM;
#pragma unroll
      for (int tl = 0; tl < 10; tl++) {
        const float a = acc2[4 * tl + 2 * hh], b = acc2[4 * tl + 2 * hh + 1];
        o[tl] = bfma(sv[tl >> 1][(tl & 1) * 2 + hh], pack_bf(fmaf(a, tanhv(a), a), fmaf(b, tanhv(b), b)), xv[hh][tl]);
        if ((tl & 3) == 3)
          asm volatile("st.global.v4.u32 [%0], {%1, %2, %3, %4};" ::"l"((uint4*)op + (tl >> 2) * 4 + q), "r"(o[tl - 3]), "r"(o[tl - 2]), "r"(o[tl - 1]), "r"(o[tl]) : "memory");
      }
      asm volatile("st.global.v2.u32 [%0], {%1, %2};" ::"l"((uint2*)(op + 64) + q), "r"(o[8]), "r"(o[9]) : "memory");
    }
  } else {
    const int cw = warp - 8;
    bar_sync(0, 512);
    const uint4 erj = lds128(sb + OFF_EP);
    const unsigned ep = erj.x;
    const int rg1 = erj.z, j1 = erj.w;
    {
      const uint4 st = lds128(sb + OFF_STAT + g * 16);
      const float n0 = __uint_as_float(st.x), r0 = __uint_as_float(st.y), n1 = __uint_as_float(st.z), r1 = __uint_as_float(st.w);
      const int up = upos(2 * wid);
      uint2* dst = (uint2*)p.scr->uT + ((up >> 1) * DM + cw * 80) * 4 + (lane ^ ((up & 1) << 1));
#pragma unroll
      for (int i = 0; i < 10; i++) {
        const uint32_t a = movm(pack_h(fmaf(bflo(xv[0][i]), r0, n0), fmaf(bfhi(xv[0][i]), r0, n0)));
        const uint32_t b = movm(pack_h(fmaf(bflo(xv[1][i]), r1, n1), fmaf(bfhi(xv[1][i]), r1, n1)));
        dst[i * 32] = make_uint2(a, b);
      }
    }
    if (warp == 8) {
      bar_sync(12, 256);
      if (lane == 0) publish(cnt + C_LN * 32);
      __syncwarp();
    } else bar_arrive(12, 256);
    if (warp == 15) {
      if (elect1()) {
#pragma unroll 1
        for (int s = 4; s < 10; s++) {
          mbar_wait(bar + 8 * (B_REL1 + s - 3), 0);
          load1(s, &tmX, &tmW1, rg1, j1);
        }
        poll_cnt(cnt + (C_CS + (j1 >> 1)) * 32, ep);
        bulk_g2s(sb + OFF_CS, p.scr->cs + j1 * 192, 768, bar + 8 * B_EPI);
      }
      __syncwarp();
    }
    if (warp >= 10 && warp < 15) {
      const uint32_t pb = sb + OFF_P + kch * 3072, pk = sb + OFF_KS + kch * 4096;
      const uint2 e0 = lds64(pk + 3072 + lane * 8), e1 = lds64(pk + 5 * 4096 + 3072 + lane * 8);
      const float dsk = bflo(pds);
      uint32_t kex = __float_as_uint(fmaxf(__uint_as_float(max(max(e0.y, e1.y), mw)) * dt, fabsf(dsk) * (1.f / 256.f))) >> 23;
      kex = min(max(kex, 20u), 240u);
      const float s2 = __uint_as_float((258 - kex) << 23), sd = s2 * dt * (1.f / 32.f);
      const float f0 = __uint_as_float(e0.y) * sd, f1 = __uint_as_float(e1.y) * sd, f2 = __uint_as_float(mw) * sd;
      k0 += __uint_as_float(e0.x) + __uint_as_float(e1.x);
#pragma unroll
      for (int o = 16; o; o >>= 1) k0 += __shfl_xor_sync(0xffffffffu, k0, o);
      const float k0n = fmaf(k0, dt, dsk) * s2;
      uint32_t h[5][2];
#pragma unroll
      for (int j = 0; j < 6; j++) {
        const uint4 a = lds128(pk + j * 512 + lane * 16), b = lds128(pk + 5 * 4096 + j * 512 + lane * 16);
#pragma unroll
        for (int e = 0; e < 4; e++) kacc[j][e] = fmaf(__uint_as_float((&a.x)[e]), f0, fmaf(__uint_as_float((&b.x)[e]), f1, kacc[j][e] * f2));
        if (j == 1) {
          const float k256 = __shfl_sync(0xffffffffu, kacc[1][3], 28);
          if (lane == 31) kacc[1][3] -= k256;
        }
        if (j == 2 || j == 3) { h[j][0] = pack_h(kacc[j][0], kacc[j][2]); h[j][1] = pack_h(kacc[j][1], kacc[j][3]); }
        else if (j < 2) { h[j][0] = pack_h(kacc[j][0], kacc[j][1]); h[j][1] = pack_h(kacc[j][2], kacc[j][3]); }
      }
      {
        const bool sw = q >> 1;
        float v[4];
#pragma unroll
        for (int e = 0; e < 4; e++) v[e] = (sw ? kacc[5][e] : kacc[4][e]) + __shfl_xor_sync(0xffffffffu, sw ? kacc[4][e] : kacc[5][e], 2);
        h[4][0] = pack_h(v[0], v[1]); h[4][1] = pack_h(v[2], v[3]);
#pragma unroll
        for (int e = 0; e < 2; e++) {
          const uint32_t r = __shfl_xor_sync(0xffffffffu, sw ? h[2][e] : h[3][e], 2);
          if (sw) h[2][e] = r; else h[3][e] = r;
        }
      }
      fence_async_smem();
      bar_arrive(13, 192);
#pragma unroll
      for (int i = 0; i < 6; i++) sts128(pb + i * 512 + lane * 16, 0, 0, 0, 0);
      __syncwarp();
      {
        const int sw = g >> 2;
        const uint32_t sel = sw ? 0x1032 : 0x3210;
        const uint32_t a = pb + (P0 + 8 * g + ((0x3124 >> (4 * q)) & 7)) * 4, a0 = a + sw * 16, a1 = a + 16 - sw * 16;
        put2<1>(a0, a1, h[0][0], sel);
        put2<1>(a0 + 256, a1 + 256, h[0][1], sel);
        put2<1>(a0 + 512, a1 + 512, h[1][0], sel);
        put2<1>(lane == 28 ? pb + PB1 * 4 : a0 + 768, a1 + 768, h[1][1], sel);
      }
      {
        const int sw = q >> 1;
        const uint32_t sel = sw ? 0x1032 : 0x3210;
        uint32_t a = pb + (((q & 1) ? PA1 : PB1 + 1) + 32 * sw + 2 * g) * 4;
        put2<1>(a + sw * 64, a + 64 - sw * 64, h[2][0], sel);
        put2<1>(a + 4 + sw * 64, a + 68 - sw * 64, h[2][1], sel);
        const int s1 = q & 1;
        const uint32_t sel1 = s1 ? 0x1032 : 0x3210;
        a = pb + (PA2 + g + 16 * sw + 32 * s1) * 4;
        put2<1>(a + s1 * 32, a + 32 - s1 * 32, h[3][0], sel1);
        put2<1>(a + (PB2 - PA2) * 4 + s1 * 32, a + (PB2 - PA2) * 4 + 32 - s1 * 32, h[3][1], sel1);
        a = pb + (((g & 1) ? PB3 : PA3) + (g >> 1) + 8 * sw + 32 * s1) * 4;
        const uint32_t hx = s1 ? h[4][1] : h[4][0], hy = s1 ? h[4][0] : h[4][1];
        put2<1>(a + s1 * 16, a + 64 + s1 * 16, hx, 0x3210);
        put2<1>(a + 16 - s1 * 16, a + 80 - s1 * 16, hy, 0x3210);
      }
      if (lane == 30) put2<1>(pb + P0 * 4, pb + (PA1 + 64) * 4, __byte_perm(pack_h(k0n, 0.f), h[2][1], 0x7610), 0x3210);
      if (lane == 31) sts64(sb + OFF_CHC + kch * 8, (kex - 4) * 0x00800080u, __byte_perm(h[3][1], 0, 0x3232));
    }
    if (warp == 8) {
      bar_sync(13, 192);
      if (elect1()) {
        mbar_expect(bar + 8 * B_UFULL, 144 * 160);
        mbar_expect(bar + 8 * B_EPI, 1024 + 768);
        poll_cnt(cnt + C_LN * 32, ep * 128);
        tma2d(sb + OFF_U - 16 * 160, &tmU, wid * 80, -16, bar + 8 * B_UFULL);
        bulk_g2s(sb + OFF_STAT, p.scr->stats + rg1 * 128, 1024, bar + 8 * B_EPI);
      }
      __syncwarp();
    }
    const int wg = warp >> 2, role = (warp + 2 * wg) & 3;
    uint32_t co[6], cpa = (g - 2 * q) * 4;
    if (role < 2) {
#pragma unroll
      for (int gm = 0; gm < 3; gm++) {
        const int hb = 2 * (lane & 7) + role - 2 + gm, l3 = ((lane >> 3) ^ (hb >> 1)) & 7;
        co[2 * gm] = hb * 1280 + uoff(l3); co[2 * gm + 1] = hb * 1280 + uoff(l3 ^ 4);
      }
    } else {
      const int mi = lane >> 3, hf = (lane >> 2) & 1;
      co[0] = hf * 1792 + (mi ^ hf) * 64 + ((q ^ (mi >> 1) ^ (hf * 2)) << 4);
      co[1] = co[0] ^ 96;
      const int i = lane & 7;
      if (role == 3) co[0] = (16 * (mi >> 1) + ((4 * (mi & 1) + (i >> 1) + 8 * (i & 1)) ^ (4 * (i & 1)))) << 4;
      co[2] = (role == 2 ? (16 * (mi >> 1) + 2 * i + (mi & 1)) ^ (i >> 2) : lane ^ ((lane >> 1) & 4)) << 4;
      co[3] = lane * 16;
      co[4] = (g >> 1) == q ? ((g & 1) ? 0xffff0000u : 0xffffu) : 0u;
      co[5] = (g - q) * 8;
    }
    const uint32_t zero = lds32(sb + OFF_ZERO), nz = zero | 0x80000000u;
#pragma unroll
    for (int i = 0; i < 6; i++) co[i] = pin(co[i], zero);
    cpa = pin(cpa, zero);
    const Comb cmb = comb_setup(tid, zero);
    if (warp >= 10 && warp < 15) bar_sync(15, 160);
    const int qt = (QMAP >> (4 * cw)) & 3, jz = qt * 32 + lane;
    uint32_t zo[13];
    {
      const int j = jz < 112 ? jz : jz - 128, gr = j >> 1;
      zo[0] = uoff(upos(max(2 * j - 2, -32))); zo[1] = zo[0] ^ 16; zo[2] = uoff(upos(2 * j)); zo[3] = zo[2] ^ 16; zo[4] = uoff(upos(2 * j + 2));
#pragma unroll
      for (int pp = 0; pp < 4; pp++) zo[5 + pp] = ZA1 + 512 + (gr ^ ((gr >> 2) & 1)) * 64 + ((((gr >> 1) & 3) ^ pp) << 4) + (j & 1) * 8;
      zo[9] = ((j >> 3) * 16 + (j & 7)) * 16;
      zo[10] = ((j >> 4) * 32 + (j & 15)) * 16;
      zo[11] = zo[10] + ((j & 15) == 15 ? 272 : 16);
      zo[12] = (zo[9] ^ 64) + 128;
#pragma unroll
      for (int i = 0; i < 13; i++) zo[i] = pin(zo[i], zero);
    }
    if (warp < 12) {
      mbar_wait(bar + 8 * (B_REL1 + 7), 0);
      sts128(sb + OFF_CMB + (tid - 256) * 16, cmb.o[0], cmb.o[1], cmb.o[2], cmb.o[3]);
      sts64(sb + OFF_CMB + 2048 + (tid - 256) * 8, cmb.o[4], cmb.o[5]);
      sts32(sb + OFF_CMB + 3072 + (tid - 256) * 4, cmb.o[6]);
    }
    mbar_wait(bar + 8 * B_UFULL, 0);
#pragma unroll 1
    for (unsigned seq = (cw >> 2) ? 0xb9ac : 0x8; seq; seq >>= 4) {
      const int ch = seq & 7;
      if (ch == 1) bar_arrive(0, 256);
      if (ch == 2) mbar_wait(bar + 8 * (B_REL1 + 8), 0);
      const uint32_t ub = sb + OFF_U + ch * 32, zb = sb + OFF_Z + ch * ZSZ;
      uint32_t w_[20], o_[20], d_[20], b3_[20];
      uint32_t *w = w_ + 8, *o = o_ + 8, *d = d_ + 8, *b3 = b3_ + 8;
      {
        const uint4 c = lds128(ub + zo[2]), e = lds128(ub + zo[3]), b = lds128(ub + zo[1]);
        w[8] = lds32(ub + zo[4]);
        const uint2 a = lds64(ub + zo[0] + 8);
        w[-6] = a.x; w[-5] = a.y; w[-4] = b.x; w[-3] = b.y; w[-2] = b.z; w[-1] = b.w;
        w[0] = c.x; w[1] = c.y; w[2] = c.z; w[3] = c.w; w[4] = e.x; w[5] = e.y; w[6] = e.z; w[7] = e.w;
      }
#pragma unroll
      for (int i = -1; i <= 7; i++) o[i] = odd_pair(w[i], w[i + 1]);
#pragma unroll
      for (int i = 0; i <= 7; i++) { d[i] = hadd(w[i], o[i]); b3[i] = hadd(d[i], o[i - 1]); }
#pragma unroll
      for (int pp = 0; pp < 4; pp++) {
        const uint32_t sel = (pp & 1) ? 0x7632 : 0x5410;
        const int k = pp >> 1;
        sts64(zb + zo[5 + pp], __byte_perm(w[k - 1], w[k + 1], sel), __byte_perm(w[k + 3], w[k + 5], sel));
        sts64(zb + zo[5 + pp] + (ZB1 - ZA1), __byte_perm(b3[k], b3[k + 2], sel), __byte_perm(b3[k + 4], b3[k + 6], sel));
      }
      if (qt < 3) {
        uint32_t e_[20], b5_[20];
        uint32_t *e = e_ + 8, *b5 = b5_ + 8;
#pragma unroll
        for (int i = -6; i <= -2; i++) o[i] = odd_pair(w[i], w[i + 1]);
#pragma unroll
        for (int i = -6; i <= -1; i++) d[i] = hadd(w[i], o[i]);
#pragma unroll
        for (int i = -5; i <= -1; i++) b3[i] = hadd(d[i], o[i - 1]);
#pragma unroll
        for (int i = -5; i <= 4; i++) e[i] = hadd(d[i - 1], d[i]);
#pragma unroll
        for (int i = -4; i <= 4; i++) b5[i] = hadd(e[i], w[i + 1]);
        const uint32_t a2 = zb + zo[9];
        sts128(a2 + ZA2, b3[-2], b3[-1], b3[0], b3[1]);
        sts128(zb + zo[12] + ZA2, b3[2], b3[3], b3[4], b3[5]);
        sts128(a2 + ZB2, b5[-4], b5[-3], b5[-2], b5[-1]);
        sts128(zb + zo[12] + ZB2, b5[0], b5[1], b5[2], b5[3]);
        if (qt < 2) {
          sts128(a2 + ZS, d[-2], d[-1], d[0], d[1]);
          sts128(a2 + ZS + 128, d[2], d[3], d[4], d[5]);
          uint32_t b7[8], b9[8];
#pragma unroll
          for (int i = -4; i <= 3; i++) { b7[i + 4] = hadd(b3[i - 1], e[i + 1]); b9[i + 4] = hadd(e[i - 1], b5[i + 1]); }
          const uint32_t a3 = zb + zo[10];
          sts128(a3 + ZA3, b7[0], b7[1], b7[2], b7[3]);
          sts128(a3 + ZA3 + 256, b7[4], b7[5], b7[6], b7[7]);
          sts128(a3 + ZB3 + 256, b9[0], b9[1], b9[2], b9[3]);
          if (jz < 63) sts128(zb + zo[11] + ZB3, b9[4], b9[5], b9[6], b9[7]);
          else sts128(zb + ZB3, 0, 0, 0, 0);
        }
      }
    }
    bar_sync(wg == 2 ? 14 : 7, 384);
#pragma unroll 1
    for (int ch = wg - 2; ch < 5; ch += 2) {
      const uint32_t ub = sb + OFF_U + ch * 32, zb = sb + OFF_Z + ch * ZSZ, pb = sb + OFF_P + ch * 3072;
      if (ch == 2) bar_sync(0, 256);
      const uint32_t pa = pb + cpa;
      if (role < 2) {
        float acc[8][4];
#pragma unroll
        for (int r = 0; r < 8; r++) { acc[r][0] = acc[r][1] = acc[r][2] = acc[r][3] = 0.f; }
        float fix = 0.f;
        if (role == 1 && lane == 28) {
          const uint32_t k = lds32(pb + PB1 * 4), u0 = lds32(ub);
          fix = __low2float(*reinterpret_cast<const __half2*>(&k)) * __low2float(*reinterpret_cast<const __half2*>(&u0));
        }
        uint32_t b[12][4], A[17][4];
#pragma unroll
        for (int i = 11; i >= 8; i--) ldsm4(b[i], ub + (co[4 + (i & 1)] ^ (((i >> 1) & 1) * 16)) + ((i >> 1) & 1) * 640);
        A[0][0] = lds32(pa + P0 * 4); A[0][1] = lds32(pa + P0 * 4 + 32); A[0][2] = lds32(sb + OFF_ZERO + 4);
#pragma unroll
        for (int m = 0; m <= 16; m++) {
          if (m < 16) {
            A[m + 1][0] = lds32(pa + P0 * 4 + (2 * m + 2) * 32);
            A[m + 1][1] = m < 15 ? lds32(pa + P0 * 4 + (2 * m + 3) * 32) : lds32(sb + OFF_ZERO + 8);
          }
          if ((m & 1) == 0 && m < 16) {
            const int i = 7 - (m >> 1);
            ldsm4(b[i], ub + (co[2 * (i >> 2) + (i & 1)] ^ (((i >> 1) & 1) * 16)) + ((i >> 1) & 1) * 640);
          }
          if (m == 9 && elect1()) mbar_arrive(bar + 8 * (B_PAIR + ch));
          A[m][3] = dup(A[m][0], nz);
          if (m < 16) A[m + 1][2] = dup(A[m][1], nz);
#pragma unroll
          for (int r = 7; r >= 0; r--) {
            const int f = 16 + r - m;
            hmma(acc[r], A[m][0], A[m][1], A[m][2], A[m][3], b[f >> 1][(f & 1) * 2], b[f >> 1][(f & 1) * 2 + 1]);
          }
        }
        acc[7][2] += fix;
        mbar_wait(bar + 8 * (B_PAIR + ch), 0);
#pragma unroll
        for (int i = 3; i >= 0; i--)
          stsm4t(ub + (co[4 + (i & 1)] ^ (((i >> 1) & 1) * 16)) + ((i >> 1) & 1) * 640, pack_bf(acc[2 * i][0], acc[2 * i][1]), pack_bf(acc[2 * i][2], acc[2 * i][3]),
                 pack_bf(acc[2 * i + 1][0], acc[2 * i + 1][1]), pack_bf(acc[2 * i + 1][2], acc[2 * i + 1][3]));
      } else if (role == 2) {
        float acc[14][4];
#pragma unroll
        for (int r = 0; r < 14; r++) { acc[r][0] = acc[r][1] = acc[r][2] = acc[r][3] = 0.f; }
#pragma unroll
        for (int arr = 0; arr < 2; arr++) {
          uint32_t A[5][4];
#pragma unroll
          for (int m = 4; m >= 0; m--) {
            const uint2 v = lds64(pb + co[5] + (arr ? PB1 : PA1) * 4 + m * 64), w = lds64(pb + co[5] + (arr ? PB1 : PA1) * 4 + m * 64 - 32);
            A[m][0] = v.x; A[m][1] = v.y; A[m][2] = w.x; A[m][3] = w.y;
          }
#pragma unroll
          for (int ip = 0; ip < 9; ip++) {
            uint32_t b[4];
            ldsm4(b, zb + co[ip & 1] + (arr ? ZB1 : ZA1) + ip * 256);
#pragma unroll
            for (int hh = 0; hh < 2; hh++)
#pragma unroll
              for (int m = 0; m < 5; m++) {
                const int i = 2 * ip + hh - 4 + m;
                if (i >= 0 && i < 14) hmma(acc[i], A[m][0], A[m][1], A[m][2], A[m][3], b[2 * hh], b[2 * hh + 1]);
              }
          }
        }
        const uint32_t a = zb + ZA1 + 512 + co[2];
#pragma unroll
        for (int i = 0; i < 7; i++)
          stsm4(a + i * 512, pack_bf(acc[2 * i][0], acc[2 * i][1]), pack_bf(acc[2 * i][2], acc[2 * i][3]),
                pack_bf(acc[2 * i + 1][0], acc[2 * i + 1][1]), pack_bf(acc[2 * i + 1][2], acc[2 * i + 1][3]));
      } else {
        float acc[12][4];
        const uint32_t za = zb + co[3];
        {
          float d[4][2][4];
#pragma unroll
          for (int r = 0; r < 8; r++) { d[r >> 1][r & 1][0] = d[r >> 1][r & 1][1] = d[r >> 1][r & 1][2] = d[r >> 1][r & 1][3] = 0.f; }
#pragma unroll
          for (int arr = 0; arr < 2; arr++) {
            uint32_t A[4][4];
#pragma unroll
            for (int m = 0; m < 4; m++) { A[m][0] = lds32(pa + (arr ? PB3 : PA3) * 4 + m * 64); A[m][1] = lds32(pa + (arr ? PB3 : PA3) * 4 + m * 64 + 32); }
#pragma unroll
            for (int m = 0; m < 4; m++) { A[m][2] = m ? dup(A[m - 1][1], nz) : lds32(sb + OFF_ZERO + 4 + arr * 4); A[m][3] = dup(A[m][0], nz); }
#pragma unroll
            for (int io = 0; io < 4; io++) {
              uint32_t b[4];
              ldsm4t(b, za + (arr ? ZB3 : ZA3) + io * 512);
#pragma unroll
              for (int m = 0; m + io < 4; m++) {
                hmma(d[io + m][0], A[m][0], A[m][1], A[m][2], A[m][3], b[0], b[1]);
                hmma(d[io + m][1], A[m][0], A[m][1], A[m][2], A[m][3], b[2], b[3]);
              }
            }
          }
#pragma unroll
          for (int r = 0; r < 4; r++) {
            acc[r][0] = acc[r][1] = acc[r][2] = acc[r][3] = 0.f;
            acc[4 + 2 * r][0] = d[r][0][0]; acc[4 + 2 * r][1] = d[r][0][1]; acc[4 + 2 * r][2] = d[r][1][0]; acc[4 + 2 * r][3] = d[r][1][1];
            acc[5 + 2 * r][0] = d[r][0][2]; acc[5 + 2 * r][1] = d[r][0][3]; acc[5 + 2 * r][2] = d[r][1][2]; acc[5 + 2 * r][3] = d[r][1][3];
          }
        }
        {
          const uint32_t k0 = lds32(sb + OFF_CHC + ch * 8 + 4) & co[4];
          const uint32_t k1 = lds32(sb + OFF_ZERO + 12), k2 = lds32(sb + OFF_ZERO + 16), k3 = dup(k0, nz);
#pragma unroll
          for (int ip = 0; ip < 4; ip++) {
            uint32_t b[4];
            ldsm4t(b, za + ZS + ip * 512);
            hmma(acc[4 + 2 * ip], k0, k1, k2, k3, b[0], b[1]);
            hmma(acc[5 + 2 * ip], k0, k1, k2, k3, b[2], b[3]);
          }
        }
        const uint32_t pa2 = pb + co[5];
#pragma unroll
        for (int arr = 0; arr < 2; arr++) {
          uint32_t A[5][4];
#pragma unroll
          for (int m = 0; m < 5; m++) {
            const uint2 v = lds64(pa2 + (arr ? PB2 : PA2) * 4 + m * 64), w = lds64(pa2 + (arr ? PB2 : PA2) * 4 + m * 64 - 32);
            A[m][0] = v.x; A[m][1] = v.y; A[m][2] = w.x; A[m][3] = w.y;
          }
#pragma unroll
          for (int ip = 0; ip < 6; ip++) {
            uint32_t b[4];
            ldsm4t(b, zb + co[0] + (arr ? ZB2 : ZA2) + ip * 512);
#pragma unroll
            for (int hh = 0; hh < 2; hh++)
#pragma unroll
              for (int m = 0; m < 5; m++) {
                const int i = 2 * ip + hh + m;
                if (i < 12) hmma(acc[i], A[m][0], A[m][1], A[m][2], A[m][3], b[2 * hh], b[2 * hh + 1]);
              }
          }
        }
        const uint32_t a = zb + ZA2 + co[2];
#pragma unroll
        for (int i = 0; i < 6; i++)
          stsm4(a + i * 512, pack_bf(acc[2 * i][0], acc[2 * i][1]), pack_bf(acc[2 * i][2], acc[2 * i][3]),
                pack_bf(acc[2 * i + 1][0], acc[2 * i + 1][1]), pack_bf(acc[2 * i + 1][2], acc[2 * i + 1][3]));
      }
      __syncwarp();
      if (elect1()) mbar_arrive(bar + 8 * (B_PART + ch));
    }
    const uint4* srcA = p.scr->h + (rg1 * 24 + NS2 - 2) * 1024;
    const uint4* srcB = p.scr->w2p + (j1 * 24 + NS2 - 2) * 640;
    combine(cmb, 6 - wg, wid, p.scr->sT, [&] {
      if (warp == 12) {
        bar_sync(8, 512);
        if (elect1()) {
          asm volatile("fence.proxy.async.global;" ::: "memory");
          load2(NS2 - 2, sb + (NS2 - 2) * SLOT2, srcA, srcB);
          load2(NS2 - 1, sb + (NS2 - 1) * SLOT2, srcA + 1024, srcB + 640);
        }
        __syncwarp();
      } else bar_arrive(8, 512);
    });
    if (warp == 12) {
      if (elect1()) {
        uint32_t d = sb;
#pragma unroll 1
        for (int s = NS2; s < 24; s++) {
          mbar_wait(bar + 8 * (B_REL2 + s - NS2 + 1), 0);
          load2(s, d, srcA + 2048, srcB + 1280);
          srcA += 1024; srcB += 640;
          d = d == sb + (NS2 - 1) * SLOT2 ? sb : d + SLOT2;
        }
      }
      __syncwarp();
    } else if (warp == 13) {
      if (elect1()) {
#pragma unroll 1
        for (int c = 2; c < 5; c++) mbar_wait(bar + 8 * (B_FREE + c), 0);
        publish(cnt + (C_S + (wid >> 4)) * 32);
        mbar_expect(bar + 8 * B_SFULL, 20480);
        poll_cnt(cnt + (C_S + j1) * 32, ep * 16);
        mbar_wait(bar + 8 * (B_REL2 + 24 - NS2), 0);
        bulk_g2s(sb + OFF_U, p.scr->sT + (j1 * 16 + rg1) * 1280, 20480, bar + 8 * B_SFULL);
      }
      __syncwarp();
    }
  }
}

typedef CUresult (*EncodeFn)(CUtensorMap*, CUtensorMapDataType, cuuint32_t, void*, const cuuint64_t*, const cuuint64_t*,
                             const cuuint32_t*, const cuuint32_t*, CUtensorMapInterleave, CUtensorMapSwizzle,
                             CUtensorMapL2promotion, CUtensorMapFloatOOBfill);

}

extern "C" void kernel_launch(void* const* d_in, const int* in_sizes, int n_in, void* d_out, int out_size) {
  static EncodeFn enc = nullptr;
  static int nsm = 0;
  static void* scr = nullptr;
  if (!enc) {
    void* fn = nullptr;
    cudaDriverEntryPointQueryResult qr;
    cudaGetDriverEntryPoint("cuTensorMapEncodeTiled", &fn, cudaEnableDefault, &qr);
    enc = (EncodeFn)fn;
    int dev = 0;
    cudaGetDevice(&dev);
    cudaDeviceGetAttribute(&nsm, cudaDevAttrMultiProcessorCount, dev);
    cudaFuncSetAttribute(fused_s4_ffn_kernel<true>, cudaFuncAttributeMaxDynamicSharedMemorySize, SMEM_BYTES);
    cudaFuncSetAttribute(fused_s4_ffn_kernel<false>, cudaFuncAttributeMaxDynamicSharedMemorySize, SMEM_BYTES);
    cudaGetSymbolAddress(&scr, g_scr);
  }
  Params p;
  p.x = (const __nv_bfloat16*)d_in[0];
  p.are = (const __nv_bfloat16*)d_in[1]; p.aim = (const __nv_bfloat16*)d_in[2];
  p.bre = (const __nv_bfloat16*)d_in[3]; p.bim = (const __nv_bfloat16*)d_in[4];
  p.cre = (const __nv_bfloat16*)d_in[5]; p.cim = (const __nv_bfloat16*)d_in[6];
  p.logdt = (const __nv_bfloat16*)d_in[7]; p.dskip = (const __nv_bfloat16*)d_in[8];
  p.w1 = (const __nv_bfloat16*)d_in[10]; p.w2 = (const __nv_bfloat16*)d_in[11];
  p.out = (__nv_bfloat16*)d_out;
  p.scr = (Scratch*)scr;
  CUtensorMap tmX, tmW1, tmU, tmW2;
  const cuuint32_t es[5] = {1, 1, 1, 1, 1};
  {
    const cuuint64_t gd[5] = {DM, 2, 4, 4, FF / 32}, gs[4] = {DM * 2, DM * 16, DM * 4, DM * 64};
    const cuuint32_t bx[5] = {88, 2, 4, 4, 3};
    enc(&tmW2, CU_TENSOR_MAP_DATA_TYPE_BFLOAT16, 5, d_in[11], gd, gs, bx, es, CU_TENSOR_MAP_INTERLEAVE_NONE,
        CU_TENSOR_MAP_SWIZZLE_NONE, CU_TENSOR_MAP_L2_PROMOTION_NONE, CU_TENSOR_MAP_FLOAT_OOB_FILL_NONE);
  }
  {
    const cuuint64_t gd[2] = {16 * DM, 128}, gs[1] = {DM * 32};
    const cuuint32_t bx[2] = {80, 144};
    enc(&tmU, CU_TENSOR_MAP_DATA_TYPE_FLOAT16, 2, p.scr->uT, gd, gs, bx, es, CU_TENSOR_MAP_INTERLEAVE_NONE,
        CU_TENSOR_MAP_SWIZZLE_NONE, CU_TENSOR_MAP_L2_PROMOTION_NONE, CU_TENSOR_MAP_FLOAT_OOB_FILL_NONE);
  }
  {
    const cuuint64_t gd[2] = {DM, SEQ}, gs[1] = {DM * 2};
    const cuuint32_t bx[2] = {64, 128};
    enc(&tmX, CU_TENSOR_MAP_DATA_TYPE_BFLOAT16, 2, d_in[0], gd, gs, bx, es, CU_TENSOR_MAP_INTERLEAVE_NONE,
        CU_TENSOR_MAP_SWIZZLE_128B, CU_TENSOR_MAP_L2_PROMOTION_L2_128B, CU_TENSOR_MAP_FLOAT_OOB_FILL_NONE);
  }
  {
    const cuuint64_t gd[3] = {64, DM, FF / 64}, gs[2] = {FF * 2, 128};
    const cuuint32_t bx[3] = {64, 64, 3};
    enc(&tmW1, CU_TENSOR_MAP_DATA_TYPE_BFLOAT16, 3, d_in[10], gd, gs, bx, es, CU_TENSOR_MAP_INTERLEAVE_NONE,
        CU_TENSOR_MAP_SWIZZLE_128B, CU_TENSOR_MAP_L2_PROMOTION_L2_128B, CU_TENSOR_MAP_FLOAT_OOB_FILL_NONE);
  }
  if (nsm == 132) fused_s4_ffn_kernel<true><<<132, 512, SMEM_BYTES>>>(p, tmX, tmW1, tmU, tmW2);
  else fused_s4_ffn_kernel<false><<<132, 512, SMEM_BYTES>>>(p, tmX, tmW1, tmU, tmW2);
}
```

```cpp
#include <cuda_runtime.h>
#include <cuda_bf16.h>
#include <cuda_fp16.h>
#include <cuda.h>
#include <stdint.h>

namespace {

constexpr int SEQ = 2048, DM = 640, FF = 1536;

constexpr int SLOT1 = 40960;
constexpr int SLOT2 = 26624;
constexpr int NS2 = 7;
constexpr int LDLY = 150;
constexpr int XDLY = 300;
constexpr int PACE = 20;
constexpr int SK2 = 21;
constexpr int OFF_Z = 85504, ZSZ = 20480;
constexpr int ZA3 = 0, ZB3 = 2048, ZS = 4096, ZA2 = 6144, ZB2 = 9216, ZA1 = 12288, ZB1 = 16384;
constexpr int OFF_CMB = 2 * SLOT1;
constexpr int OFF_W2S = 3 * SLOT1;
constexpr int OFF_U = 190464;
constexpr int OFF_P = 210944;
constexpr int OFF_KS = 163840;
constexpr int OFF_LNP = 225280;
constexpr int OFF_MISC = 226304;
constexpr int OFF_CHC = OFF_MISC + 16;
constexpr int OFF_EP = OFF_MISC + 64;
constexpr int OFF_ZERO = OFF_MISC + 128;
constexpr int OFF_STAT = OFF_MISC + 1024;
constexpr int OFF_CS = OFF_MISC + 2048;
constexpr int OFF_BAR = OFF_MISC + 2816;
constexpr int SMEM_BYTES = OFF_MISC + 6144;
constexpr int P0 = 8, PA1 = 280, PB1 = 360, PA2 = 448, PB2 = 544, PA3 = 632, PB3 = 704;
enum { B_W2 = 0, B_FULL1 = 1, B_FULL2 = 11, B_UFULL = 35, B_EPI = 36, B_SFULL = 37,
       B_PAIR = 42,
       B_FREE = 48, B_PART = 54,
       B_REL1 = 60, B_REL2 = 70 };
enum { C_LN = 0, C_H = 2, C_S = 34, C_CS = 42, C_NUM = 46 };

struct Scratch {
  unsigned cnt[64 * 32];
  unsigned epoch[256];
  float2 stats[SEQ];
  float cs[FF];
  uint4 uT[DM * 256];
  uint4 w2p[8 * 24 * 640];
  uint4 sT[8 * 16 * 1280];
  uint4 h[16 * 24 * 1024];
};
__device__ __align__(1024) Scratch g_scr;
constexpr uint32_t sb = 1024;
constexpr uint32_t bar = sb + OFF_BAR;

struct Params {
  const __nv_bfloat16 *are, *aim, *bre, *bim, *cre, *cim, *logdt, *dskip, *x, *w1, *w2;
  __nv_bfloat16* out;
  Scratch* scr;
};

__device__ __forceinline__ void mbar_init(uint32_t a, int c) { asm volatile("mbarrier.init.shared::cta.b64 [%0], %1;" ::"r"(a), "r"(c)); }
__device__ __forceinline__ void mbar_expect(uint32_t a, int b) { asm volatile("mbarrier.arrive.expect_tx.shared::cta.b64 _, [%0], %1;" ::"r"(a), "r"(b) : "memory"); }
__device__ __forceinline__ void mbar_arrive(uint32_t a) { asm volatile("mbarrier.arrive.shared::cta.b64 _, [%0];" ::"r"(a) : "memory"); }
__device__ __forceinline__ void mbar_wait(uint32_t a, int ph) {
  asm volatile(
      "{\n.reg .pred p;\n.reg .u32 n;\n"
      "mbarrier.try_wait.parity.shared::cta.b64 p, [%0], %1;\n@p bra LD;\nmov.u32 n, 0;\n"
      "LW:\nmbarrier.try_wait.parity.shared::cta.b64 p, [%0], %1, 20000;\n@p bra LD;\n"
      "add.u32 n, n, 1;\nsetp.lt.u32 p, n, 100000;\n@p bra LW;\ntrap;\nLD:\n}\n" ::"r"(a), "r"(ph) : "memory");
}
__device__ __forceinline__ void poll_cnt(const unsigned* p, unsigned target) {
  asm volatile(
      "{\n.reg .pred p;\n.reg .u32 n;\n.reg .s32 v;\nmov.u32 n, 0;\n"
      "LW:\nld.relaxed.gpu.global.u32 v, [%0];\nsub.s32 v, v, %1;\nsetp.ge.s32 p, v, 0;\n@p bra LD;\n"
      "nanosleep.u32 64;\nadd.u32 n, n, 1;\nsetp.lt.u32 p, n, 4000000;\n@p bra LW;\ntrap;\n"
      "LD:\nfence.acquire.gpu;\nfence.proxy.async.global;\n}\n" ::"l"(p), "r"(target) : "memory");
}
__device__ __forceinline__ void publish(unsigned* p) {
  asm volatile("fence.proxy.async.global;\nfence.release.gpu;\nred.relaxed.gpu.global.add.u32 [%0], 1;" ::"l"(p) : "memory");
}
__device__ __forceinline__ uint32_t movm(uint32_t v) { uint32_t r; asm volatile("movmatrix.sync.aligned.m8n8.trans.b16 %0, %1;" : "=r"(r) : "r"(v)); return r; }
__device__ __forceinline__ void fence_async_smem() { asm volatile("fence.proxy.async.shared::cta;" ::: "memory"); }
__device__ __forceinline__ bool elect1() { uint32_t p; asm volatile("{\n.reg .pred P;\nelect.sync _|P, 0xffffffff;\nselp.u32 %0,1,0,P;\n}\n" : "=r"(p)); return p; }
__device__ __forceinline__ void bar_sync(int id, int n) { asm volatile("bar.sync %0, %1;" ::"r"(id), "r"(n) : "memory"); }
__device__ __forceinline__ void bar_arrive(int id, int n) { asm volatile("bar.arrive %0, %1;" ::"r"(id), "r"(n) : "memory"); }
__device__ __forceinline__ void bulk_g2s(uint32_t dst, const void* src, int bytes, uint32_t mb) {
  asm volatile("cp.async.bulk.shared::cluster.global.mbarrier::complete_tx::bytes [%0], [%1], %2, [%3];" ::"r"(dst), "l"(src), "r"(bytes), "r"(mb) : "memory");
}
__device__ __forceinline__ void bulk_prefetch(const void* src, int bytes) { asm volatile("cp.async.bulk.prefetch.L2.global [%0], %1;" ::"l"(src), "r"(bytes) : "memory"); }
__device__ __forceinline__ void tma2d(uint32_t dst, const CUtensorMap* m, int c0, int c1, uint32_t mb) {
  asm volatile("cp.async.bulk.tensor.2d.shared::cluster.global.mbarrier::complete_tx::bytes [%0], [%1, {%3, %4}], [%2];" ::"r"(dst), "l"(m), "r"(mb), "r"(c0), "r"(c1) : "memory");
}
__device__ __forceinline__ void tma3d(uint32_t dst, const CUtensorMap* m, int c0, int c1, int c2, uint32_t mb) {
  asm volatile("cp.async.bulk.tensor.3d.shared::cluster.global.mbarrier::complete_tx::bytes [%0], [%1, {%3, %4, %5}], [%2];" ::"r"(dst), "l"(m), "r"(mb), "r"(c0), "r"(c1), "r"(c2) : "memory");
}
__device__ __forceinline__ unsigned frag_col(unsigned l) { return (l & 0x61) | ((l & 6) << (2 - (l >> 6))) | ((l >> 2) & 6); }
__device__ __forceinline__ void tma5d(uint32_t dst, const CUtensorMap* m, int c0, int c4, uint32_t mb) {
  asm volatile("cp.async.bulk.tensor.5d.shared::cluster.global.mbarrier::complete_tx::bytes [%0], [%1, {%3, %5, %5, %5, %4}], [%2];" ::"r"(dst), "l"(m), "r"(mb), "r"(c0), "r"(c4), "r"(0) : "memory");
}
__device__ __forceinline__ uint64_t dsc(uint32_t lo, uint32_t hi) { return ((uint64_t)hi << 32) | lo; }
__device__ __forceinline__ void wg_fence() { asm volatile("wgmma.fence.sync.aligned;" ::: "memory"); }
__device__ __forceinline__ void wg_commit() { asm volatile("wgmma.commit_group.sync.aligned;" ::: "memory"); }
template <int N> __device__ __forceinline__ void wg_wait() { asm volatile("wgmma.wait_group.sync.aligned %0;" ::"n"(N) : "memory"); }
__device__ __forceinline__ void wgmma_n192(float (&d)[96], uint64_t da, uint64_t db, int scale_d) {
  asm volatile("{\n.reg .pred p;\nsetp.ne.b32 p, %98, 0;\n"
    "wgmma.mma_async.sync.aligned.m64n192k16.f32.bf16.bf16 "
    "{"
    "%0, %1, %2, %3, %4, %5, %6, %7, %8, %9, %10, %11, %12, %13, %14, %15, "
    "%16, %17, %18, %19, %20, %21, %22, %23, %24, %25, %26, %27, %28, %29, %30, %31, "
    "%32, %33, %34, %35, %36, %37, %38, %39, %40, %41, %42, %43, %44, %45, %46, %47, "
    "%48, %49, %50, %51, %52, %53, %54, %55, %56, %57, %58, %59, %60, %61, %62, %63, "
    "%64, %65, %66, %67, %68, %69, %70, %71, %72, %73, %74, %75, %76, %77, %78, %79, "
    "%80, %81, %82, %83, %84, %85, %86, %87, %88, %89, %90, %91, %92, %93, %94, %95"
    "}, "
    "%96, %97, p, 1, 1, 0, 1;\n}\n"
    : "+f"(d[0]), "+f"(d[1]), "+f"(d[2]), "+f"(d[3]), "+f"(d[4]), "+f"(d[5]), "+f"(d[6]), "+f"(d[7]),
      "+f"(d[8]), "+f"(d[9]), "+f"(d[10]), "+f"(d[11]), "+f"(d[12]), "+f"(d[13]), "+f"(d[14]), "+f"(d[15]),
      "+f"(d[16]), "+f"(d[17]), "+f"(d[18]), "+f"(d[19]), "+f"(d[20]), "+f"(d[21]), "+f"(d[22]), "+f"(d[23]),
      "+f"(d[24]), "+f"(d[25]), "+f"(d[26]), "+f"(d[27]), "+f"(d[28]), "+f"(d[29]), "+f"(d[30]), "+f"(d[31]),
      "+f"(d[32]), "+f"(d[33]), "+f"(d[34]), "+f"(d[35]), "+f"(d[36]), "+f"(d[37]), "+f"(d[38]), "+f"(d[39]),
      "+f"(d[40]), "+f"(d[41]), "+f"(d[42]), "+f"(d[43]), "+f"(d[44]), "+f"(d[45]), "+f"(d[46]), "+f"(d[47]),
      "+f"(d[48]), "+f"(d[49]), "+f"(d[50]), "+f"(d[51]), "+f"(d[52]), "+f"(d[53]), "+f"(d[54]), "+f"(d[55]),
      "+f"(d[56]), "+f"(d[57]), "+f"(d[58]), "+f"(d[59]), "+f"(d[60]), "+f"(d[61]), "+f"(d[62]), "+f"(d[63]),
      "+f"(d[64]), "+f"(d[65]), "+f"(d[66]), "+f"(d[67]), "+f"(d[68]), "+f"(d[69]), "+f"(d[70]), "+f"(d[71]),
      "+f"(d[72]), "+f"(d[73]), "+f"(d[74]), "+f"(d[75]), "+f"(d[76]), "+f"(d[77]), "+f"(d[78]), "+f"(d[79]),
      "+f"(d[80]), "+f"(d[81]), "+f"(d[82]), "+f"(d[83]), "+f"(d[84]), "+f"(d[85]), "+f"(d[86]), "+f"(d[87]),
      "+f"(d[88]), "+f"(d[89]), "+f"(d[90]), "+f"(d[91]), "+f"(d[92]), "+f"(d[93]), "+f"(d[94]), "+f"(d[95])
    : "l"(da), "l"(db), "r"(scale_d));
}

__device__ __forceinline__ void wgmma_n80(float (&d)[40], uint64_t da, uint64_t db, int scale_d) {
  asm volatile("{\n.reg .pred p;\nsetp.ne.b32 p, %42, 0;\n"
    "wgmma.mma_async.sync.aligned.m64n80k16.f32.bf16.bf16 "
    "{"
    "%0, %1, %2, %3, %4, %5, %6, %7, %8, %9, %10, %11, %12, %13, %14, %15, "
    "%16, %17, %18, %19, %20, %21, %22, %23, %24, %25, %26, %27, %28, %29, %30, %31, "
    "%32, %33, %34, %35, %36, %37, %38, %39"
    "}, "
    "%40, %41, p, 1, 1, 0, 1;\n}\n"
    : "+f"(d[0]), "+f"(d[1]), "+f"(d[2]), "+f"(d[3]), "+f"(d[4]), "+f"(d[5]), "+f"(d[6]), "+f"(d[7]),
      "+f"(d[8]), "+f"(d[9]), "+f"(d[10]), "+f"(d[11]), "+f"(d[12]), "+f"(d[13]), "+f"(d[14]), "+f"(d[15]),
      "+f"(d[16]), "+f"(d[17]), "+f"(d[18]), "+f"(d[19]), "+f"(d[20]), "+f"(d[21]), "+f"(d[22]), "+f"(d[23]),
      "+f"(d[24]), "+f"(d[25]), "+f"(d[26]), "+f"(d[27]), "+f"(d[28]), "+f"(d[29]), "+f"(d[30]), "+f"(d[31]),
      "+f"(d[32]), "+f"(d[33]), "+f"(d[34]), "+f"(d[35]), "+f"(d[36]), "+f"(d[37]), "+f"(d[38]), "+f"(d[39])
    : "l"(da), "l"(db), "r"(scale_d));
}

__device__ __forceinline__ void hmma(float* c, uint32_t a0, uint32_t a1, uint32_t a2, uint32_t a3, uint32_t b0, uint32_t b1) {
  asm volatile("mma.sync.aligned.m16n8k16.row.col.f32.f16.f16.f32 {%0,%1,%2,%3}, {%4,%5,%6,%7}, {%8,%9}, {%0,%1,%2,%3};"
      : "+f"(c[0]), "+f"(c[1]), "+f"(c[2]), "+f"(c[3]) : "r"(a0), "r"(a1), "r"(a2), "r"(a3), "r"(b0), "r"(b1));
}
__device__ __forceinline__ void ldsm4(uint32_t* r, uint32_t a) { asm volatile("ldmatrix.sync.aligned.m8n8.x4.shared.b16 {%0,%1,%2,%3}, [%4];" : "=r"(r[0]), "=r"(r[1]), "=r"(r[2]), "=r"(r[3]) : "r"(a) : "memory"); }
__device__ __forceinline__ void ldsm4t(uint32_t* r, uint32_t a) { asm volatile("ldmatrix.sync.aligned.m8n8.x4.trans.shared.b16 {%0,%1,%2,%3}, [%4];" : "=r"(r[0]), "=r"(r[1]), "=r"(r[2]), "=r"(r[3]) : "r"(a) : "memory"); }
__device__ __forceinline__ void stsm4(uint32_t a, uint32_t r0, uint32_t r1, uint32_t r2, uint32_t r3) { asm volatile("stmatrix.sync.aligned.m8n8.x4.shared.b16 [%0], {%1,%2,%3,%4};" ::"r"(a), "r"(r0), "r"(r1), "r"(r2), "r"(r3) : "memory"); }
__device__ __forceinline__ void stsm4t(uint32_t a, uint32_t r0, uint32_t r1, uint32_t r2, uint32_t r3) { asm volatile("stmatrix.sync.aligned.m8n8.x4.trans.shared.b16 [%0], {%1,%2,%3,%4};" ::"r"(a), "r"(r0), "r"(r1), "r"(r2), "r"(r3) : "memory"); }
__device__ __forceinline__ uint32_t lds32(uint32_t a) { uint32_t v; asm volatile("ld.shared.u32 %0, [%1];" : "=r"(v) : "r"(a) : "memory"); return v; }
__device__ __forceinline__ uint2 lds64(uint32_t a) { uint2 v; asm volatile("ld.shared.v2.u32 {%0,%1}, [%2];" : "=r"(v.x), "=r"(v.y) : "r"(a) : "memory"); return v; }
__device__ __forceinline__ uint4 lds128(uint32_t a) { uint4 v; asm volatile("ld.shared.v4.u32 {%0,%1,%2,%3}, [%4];" : "=r"(v.x), "=r"(v.y), "=r"(v.z), "=r"(v.w) : "r"(a) : "memory"); return v; }
__device__ __forceinline__ void sts16(uint32_t a, uint32_t v) { asm volatile("st.shared.u16 [%0], %1;" ::"r"(a), "h"((unsigned short)v) : "memory"); }
__device__ __forceinline__ void sts32(uint32_t a, uint32_t v) { asm volatile("st.shared.u32 [%0], %1;" ::"r"(a), "r"(v) : "memory"); }
__device__ __forceinline__ void sts64(uint32_t a, uint32_t x, uint32_t y) { asm volatile("st.shared.v2.u32 [%0], {%1,%2};" ::"r"(a), "r"(x), "r"(y) : "memory"); }
__device__ __forceinline__ void sts128(uint32_t a, uint32_t x, uint32_t y, uint32_t z, uint32_t w) { asm volatile("st.shared.v4.u32 [%0], {%1,%2,%3,%4};" ::"r"(a), "r"(x), "r"(y), "r"(z), "r"(w) : "memory"); }
__device__ __forceinline__ uint32_t ldg32(const void* a) { uint32_t v; asm volatile("ld.global.nc.u32 %0, [%1];" : "=r"(v) : "l"(a)); return v; }
__device__ __forceinline__ uint32_t ldg16(const void* a) { uint32_t v; asm volatile("ld.global.nc.u16 %0, [%1];" : "=r"(v) : "l"(a)); return v; }
__device__ __forceinline__ float bflo(uint32_t v) { return __uint_as_float(v << 16); }
__device__ __forceinline__ float bfhi(uint32_t v) { return __uint_as_float(v & 0xffff0000u); }
__device__ __forceinline__ uint32_t pack_bf(float lo, float hi) { uint32_t r; asm("cvt.rn.bf16x2.f32 %0, %1, %2;" : "=r"(r) : "f"(hi), "f"(lo)); return r; }
__device__ __forceinline__ uint32_t pack_h(float lo, float hi) { uint32_t r; asm("cvt.rn.f16x2.f32 %0, %1, %2;" : "=r"(r) : "f"(hi), "f"(lo)); return r; }
__device__ __forceinline__ float rnd_bf(float v) { return __bfloat162float(__float2bfloat16_rn(v)); }
__device__ __forceinline__ float ex2a(float v) { float r; asm("ex2.approx.ftz.f32 %0, %1;" : "=f"(r) : "f"(v)); return r; }
__device__ __forceinline__ float tanha(float v) { float r; asm("tanh.approx.f32 %0, %1;" : "=f"(r) : "f"(v)); return r; }
__device__ __forceinline__ uint32_t hadd(uint32_t a, uint32_t b) { uint32_t r; asm("add.rn.f16x2 %0, %1, %2;" : "=r"(r) : "r"(a), "r"(b)); return r; }
__device__ __forceinline__ uint32_t badd(uint32_t a, uint32_t b) { uint32_t r; asm("add.rn.bf16x2 %0, %1, %2;" : "=r"(r) : "r"(a), "r"(b)); return r; }
__device__ __forceinline__ uint32_t bmul(uint32_t a, uint32_t b) { uint32_t r; asm("mul.rn.bf16x2 %0, %1, %2;" : "=r"(r) : "r"(a), "r"(b)); return r; }
__device__ __forceinline__ uint32_t bfma(uint32_t a, uint32_t b, uint32_t c) { uint32_t r; asm("fma.rn.bf16x2 %0, %1, %2, %3;" : "=r"(r) : "r"(a), "r"(b), "r"(c)); return r; }
__device__ __forceinline__ float tanhv(float v) { float r; asm volatile("tanh.approx.f32 %0, %1;" : "=f"(r) : "f"(v)); return r; }
__device__ __forceinline__ uint32_t bsub(uint32_t a, uint32_t b) { uint32_t r; asm("sub.rn.bf16x2 %0, %1, %2;" : "=r"(r) : "r"(a), "r"(b)); return r; }
__device__ __forceinline__ uint32_t dup(uint32_t v, uint32_t nz) { uint32_t r; asm volatile("add.rn.f32 %0, %1, %2;" : "=r"(r) : "r"(v), "r"(nz)); return r; }
__device__ __forceinline__ void bmma(float* c, uint32_t a0, uint32_t a1, uint32_t a2, uint32_t a3, uint32_t b0, uint32_t b1) {
  asm("mma.sync.aligned.m16n8k16.row.col.f32.bf16.bf16.f32 {%0,%1,%2,%3}, {%4,%5,%6,%7}, {%8,%9}, {%0,%1,%2,%3};"
      : "+f"(c[0]), "+f"(c[1]), "+f"(c[2]), "+f"(c[3]) : "r"(a0), "r"(a1), "r"(a2), "r"(a3), "r"(b0), "r"(b1));
}
__device__ __forceinline__ uint32_t odd_pair(uint32_t a, uint32_t b) { return __byte_perm(a, b, 0x5432); }
__device__ __forceinline__ int upos(int c) { return c ^ ((c >> 5) & 7) ^ ((c >> 3) & 1); }
__device__ __forceinline__ int uoff(int pos) { return (pos >> 1) * 160 + (pos & 1) * 16; }

struct cf { float r, i; };
__device__ __forceinline__ cf cmul(cf a, cf b) { cf o; o.r = fmaf(a.r, b.r, -a.i * b.i); o.i = fmaf(a.r, b.i, a.i * b.r); return o; }
__device__ __forceinline__ cf cmulj(cf a, cf b) { cf o; o.r = fmaf(a.r, b.r, a.i * b.i); o.i = fmaf(a.i, b.r, -a.r * b.i); return o; }
__device__ __forceinline__ cf csq(cf a) { cf o; o.r = fmaf(a.r, a.r, -a.i * a.i); o.i = (a.r + a.r) * a.i; return o; }
struct hp { uint32_t r, i; };
__device__ __forceinline__ hp hpack(cf a, cf b) { hp o; o.r = pack_h(a.r, b.r); o.i = pack_h(a.i, b.i); return o; }
__device__ __forceinline__ hp hmulc(hp a, uint32_t c) {
  __half2 ar = *reinterpret_cast<__half2*>(&a.r), ai = *reinterpret_cast<__half2*>(&a.i), cc = *reinterpret_cast<__half2*>(&c);
  __half2 orr = __hfma2(ar, __low2half2(cc), __hneg2(__hmul2(ai, __high2half2(cc))));
  __half2 oi = __hfma2(ar, __high2half2(cc), __hmul2(ai, __low2half2(cc)));
  hp o; o.r = *reinterpret_cast<uint32_t*>(&orr); o.i = *reinterpret_cast<uint32_t*>(&oi); return o;
}
__device__ __forceinline__ hp hmulj(hp a, uint32_t c) {
  __half2 ar = *reinterpret_cast<__half2*>(&a.r), ai = *reinterpret_cast<__half2*>(&a.i), cc = *reinterpret_cast<__half2*>(&c);
  __half2 orr = __hfma2(ar, __low2half2(cc), __hmul2(ai, __high2half2(cc)));
  __half2 oi = __hfma2(ai, __low2half2(cc), __hneg2(__hmul2(ar, __high2half2(cc))));
  hp o; o.r = *reinterpret_cast<uint32_t*>(&orr); o.i = *reinterpret_cast<uint32_t*>(&oi); return o;
}
__device__ __forceinline__ hp hmule(hp a, hp b) {
  __half2 ar = *reinterpret_cast<__half2*>(&a.r), ai = *reinterpret_cast<__half2*>(&a.i);
  __half2 br = *reinterpret_cast<__half2*>(&b.r), bi = *reinterpret_cast<__half2*>(&b.i);
  __half2 orr = __hfma2(ar, br, __hneg2(__hmul2(ai, bi))), oi = __hfma2(ar, bi, __hmul2(ai, br));
  hp o; o.r = *reinterpret_cast<uint32_t*>(&orr); o.i = *reinterpret_cast<uint32_t*>(&oi); return o;
}
__device__ __forceinline__ void sts_tile(uint32_t a, const hp* t) {
  sts128(a, t[0].r, t[1].r, t[2].r, t[3].r);
  sts128(a + 512, t[0].i, t[1].i, t[2].i, t[3].i);
}
template <int STEP> __device__ __forceinline__ void put2(uint32_t a0, uint32_t a1, uint32_t h, uint32_t sel) {
  const uint32_t x = __byte_perm(h, h, sel), y = x >> 16;
  sts16(a0, x); sts16(a0 + STEP * 4 + 2, x);
  sts16(a1, y); sts16(a1 + STEP * 4 + 2, y);
}

__device__ __forceinline__ void spare_work(const Params& p, const CUtensorMap* tmW1, int k, int tid) {
  const int lane = tid & 31;
  unsigned ep = 0;
  if (tid >= 480) ep = p.scr->epoch[128 + k] + 1;
  if (tid == 480) {
    for (int i = 0; i < 8; i++) mbar_init(bar + 8 * i, i < 4 ? 1 : 12);
    asm volatile("fence.mbarrier_init.release.cluster;" ::: "memory");
    fence_async_smem();
  }
  __syncthreads();
  float a[2][4] = {{0.f, 0.f, 0.f, 0.f}, {0.f, 0.f, 0.f, 0.f}};
  if (tid >= 480) {
    if (elect1()) {
#pragma unroll 1
      for (int s = 0; s < 10; s++) {
        mbar_wait(bar + 8 * (4 + (s & 3)), ((s >> 2) & 1) ^ 1);
        mbar_expect(bar + 8 * (s & 3), 49152);
#pragma unroll 1
        for (int b = 0; b < 2; b++) tma3d(sb + (s & 3) * 49152 + b * 24576, tmW1, 0, s * 64, k * 6 + b * 3, bar + 8 * (s & 3));
      }
    }
    __syncwarp();
  } else if (tid < 384) {
    const uint32_t idn = (lane >> 3) == (lane & 3) ? ((lane & 4) ? 0x3f800000u : 0x3f80u) : 0u;
#pragma unroll 1
    for (int s = 0; s < 10; s++) {
      mbar_wait(bar + 8 * (s & 3), (s >> 2) & 1);
      const uint32_t ad = sb + (s & 3) * 49152 + (tid >> 6) * 8192 + (tid & 63) * 16;
#pragma unroll
      for (int i = 0; i < 8; i += 2) {
        const uint4 v = lds128(ad + i * 1024), w = lds128(ad + i * 1024 + 1024);
        bmma(a[0], v.x, v.y, w.x, w.y, idn, idn);
        bmma(a[1], v.z, v.w, w.z, w.w, idn, idn);
      }
      __syncwarp();
      if (lane == 0) mbar_arrive(bar + 8 * (4 + (s & 3)));
    }
#pragma unroll
    for (int e = 0; e < 8; e++) {
      float v = a[e >> 2][e & 3];
      v += __shfl_xor_sync(0xffffffffu, v, 9);
      v += __shfl_xor_sync(0xffffffffu, v, 18);
      a[e >> 2][e & 3] = v;
    }
    const int odd = (tid >> 5) & 1, c8 = (tid >> 6) * 8 + ((lane & 7) ^ (odd * 4));
    if (odd && lane < 8) {
      sts128(sb + 196608 + c8 * 32, __float_as_uint(a[0][0]), __float_as_uint(a[0][1]), __float_as_uint(a[0][2]), __float_as_uint(a[0][3]));
      sts128(sb + 196608 + c8 * 32 + 16, __float_as_uint(a[1][0]), __float_as_uint(a[1][1]), __float_as_uint(a[1][2]), __float_as_uint(a[1][3]));
    }
    __syncwarp();
    bar_sync(1 + (tid >> 6), 64);
    if (!odd && lane < 8) {
      const uint4 v = lds128(sb + 196608 + c8 * 32), w = lds128(sb + 196608 + c8 * 32 + 16);
      float2* dst = (float2*)(p.scr->cs + k * 384 + (c8 >> 2) * 32) + (c8 & 3);
      dst[0] = make_float2(a[0][0] + __uint_as_float(v.x), a[0][1] + __uint_as_float(v.y));
      dst[4] = make_float2(a[0][2] + __uint_as_float(v.z), a[0][3] + __uint_as_float(v.w));
      dst[8] = make_float2(a[1][0] + __uint_as_float(w.x), a[1][1] + __uint_as_float(w.y));
      dst[12] = make_float2(a[1][2] + __uint_as_float(w.z), a[1][3] + __uint_as_float(w.w));
    }
  }
  __syncthreads();
  if (tid == 480) {
    publish(p.scr->cnt + (C_CS + k) * 32);
    p.scr->epoch[128 + k] = ep;
    poll_cnt(p.scr->cnt + C_LN * 32, ep * 128);
  }
}

__device__ __forceinline__ void load1(int s, const CUtensorMap* tmX, const CUtensorMap* tmW1, int rg1, int j1) {
  const uint32_t d = sb + (s & 3) * SLOT1, mb = bar + 8 * (B_FULL1 + s);
  mbar_expect(mb, SLOT1);
  tma2d(d, tmX, s * 64, rg1 * 128, mb);
  tma3d(d + 16384, tmW1, 0, s * 64, j1 * 3, mb);
}
__device__ __forceinline__ void load_x(uint32_t (&xv)[2][10], const __nv_bfloat16* xa, const __nv_bfloat16* xb, int rstep) {
#pragma unroll
  for (int r = 0; r < 2; r++) {
    const uint4 a = __ldg((const uint4*)(xa + r * rstep)), b = __ldg((const uint4*)(xa + r * rstep + 32));
    const uint2 c = __ldg((const uint2*)(xb + r * rstep + 64));
    xv[r][0] = a.x; xv[r][1] = a.y; xv[r][2] = a.z; xv[r][3] = a.w; xv[r][4] = b.x; xv[r][5] = b.y; xv[r][6] = b.z; xv[r][7] = b.w;
    xv[r][8] = c.x; xv[r][9] = c.y;
  }
}

__device__ __forceinline__ uint32_t pin(uint32_t v, uint32_t z) { uint32_t r; asm volatile("add.u32 %0, %1, %2;" : "=r"(r) : "r"(v), "r"(z)); return r; }
struct Comb { uint32_t o[7]; };
__device__ __forceinline__ Comb comb_setup(int tid, uint32_t z) {
  Comb k;
  const int c = tid & 127, c1 = c < 112 ? c + 32 : c - 112, c2 = c < 112 ? c + 144 : c - 96;
  const uint32_t zr = ZA1 + (c & 7) * 16, a2 = ZA2 + ((c & ~15) - 32 + ((((c >> 1) & 7) + (c & 1) * 8) ^ ((c & 1) * 4))) * 16;
  k.o[0] = uoff(upos(c1)); k.o[1] = uoff(upos(c2));
  k.o[2] = c < 112 ? ZA1 + 512 + ((2 * c) ^ ((c >> 2) & 1)) * 16 : zr;
  k.o[3] = c1 >= 64 ? a2 : zr; k.o[4] = c < 112 ? a2 + 112 * 16 : zr;
  k.o[5] = ((c1 >> 4) * 1280 + (c & 15)) * 16; k.o[6] = ((c2 >> 4) * 1280 + (c & 15)) * 16;
#pragma unroll
  for (int i = 0; i < 7; i++) k.o[i] = pin(k.o[i], z);
  return k;
}
template <class F> __device__ __forceinline__ void combine(const Comb& k, int ch, int wid, uint4* sT, F&& after_reads) {
  const uint32_t ub = sb + OFF_U + ch * 32, zb = sb + OFF_Z + ch * ZSZ;
  const int row = (wid & 15) * 5 + ch;
  char* dst = (char*)(sT + ((wid >> 4) * 16 * 80 + row) * 16);
  mbar_wait(bar + 8 * (B_PART + ch), 0);
  const uint32_t sc = lds32(sb + OFF_CHC + ch * 8);
  const uint4 y0 = lds128(zb + k.o[2]), y1 = lds128(zb + (k.o[2] ^ 16));
  const uint4 v2 = lds128(zb + k.o[3]), u2 = lds128(zb + k.o[4]);
  const uint4 v0 = lds128(ub + k.o[0]), u0 = lds128(ub + k.o[1]);
  fence_async_smem();
  after_reads();
  *(uint4*)(dst + (k.o[5] ^ ((row & 7) * 16))) =
      make_uint4(bmul(badd(badd(y0.x, v2.x), v0.x), sc), bmul(badd(badd(y0.y, v2.y), v0.y), sc),
                 bmul(badd(badd(y1.x, v2.z), v0.z), sc), bmul(badd(badd(y1.y, v2.w), v0.w), sc));
  *(uint4*)(dst + (k.o[6] ^ ((row & 7) * 16))) =
      make_uint4(bmul(badd(badd(y0.z, u2.x), u0.x), sc), bmul(badd(badd(y0.w, u2.y), u0.y), sc),
                 bmul(badd(badd(y1.z, u2.z), u0.z), sc), bmul(badd(badd(y1.w, u2.w), u0.w), sc));
  __syncwarp();
  if (elect1()) mbar_arrive(bar + 8 * (B_FREE + ch));
}

__device__ __forceinline__ void load2(int s, uint32_t d, const uint4* srcA, const uint4* srcB) {
  const uint32_t mb = bar + 8 * (B_FULL2 + s);
  mbar_expect(mb, SLOT2);
  bulk_g2s(d, srcA, 16384, mb);
  bulk_g2s(d + 16384, srcB, 10240, mb);
}

template <bool USE_SMID>
__global__ void __launch_bounds__(512, 1)
fused_s4_ffn_kernel(const Params p, const __grid_constant__ CUtensorMap tmX, const __grid_constant__ CUtensorMap tmW1,
                    const __grid_constant__ CUtensorMap tmU, const __grid_constant__ CUtensorMap tmW2) {
  extern __shared__ __align__(1024) unsigned char smem_raw[];
  const int tid = threadIdx.x, lane = tid & 31;
  uint32_t sid;
  if (USE_SMID) asm("mov.u32 %0, %smid;" : "=r"(sid)); else sid = blockIdx.x;
  const int wid = sid < 120 ? sid : sid - 4;
  uint32_t pa[6], pld, pds;
  const unsigned pw = min(tid >> 5, 14), part = (pw * 13) >> 6;
  const unsigned ch = (wid >> 4) * 80 + frag_col(((wid & 15) - part) * 5 + pw);
  const unsigned o = (ch * 3 + part) * 32 + lane;
  {
    asm volatile("{\n.reg .pred p;\nsetp.lt.u32 p, %0, 256;\n@p nanosleep.u32 %1;\n}" ::"r"(tid), "n"(LDLY));
    pld = ldg16(p.logdt + ch);
    pa[0] = ldg32((const uint32_t*)p.are + o); pa[1] = ldg32((const uint32_t*)p.aim + o);
    pds = ldg16(p.dskip + ch);
    pa[2] = ldg32((const uint32_t*)p.bre + o); pa[3] = ldg32((const uint32_t*)p.bim + o);
    pa[4] = ldg32((const uint32_t*)p.cre + o); pa[5] = ldg32((const uint32_t*)p.cim + o);
  }
  const int warp = __shfl_sync(0xffffffffu, tid >> 5, 0);
  const int g = lane >> 2, q = lane & 3;
  if (sid - 120u < 4u) { spare_work(p, &tmW1, sid - 120, tid); return; }
  unsigned* const cnt = p.scr->cnt;

  float kacc[6][4];
  const int kch = warp - 10;
  float dt, k0;
  uint32_t xv[2][10], xs[2], mw;
  {
    unsigned ep0;
    if (warp == 15) {
      ep0 = p.scr->epoch[wid];
      if ((uint32_t)__cvta_generic_to_shared(smem_raw) != sb) __trap();
    }
    if (elect1()) {
      const int gi = (warp + 1) & 15;
#pragma unroll
      for (int i = 0; i < 6; i++) mbar_init(bar + 48 * gi + 8 * i, gi < 7 ? 1 : gi == 7 ? 2 : gi < 10 ? 4 : 8);
      asm volatile("fence.mbarrier_init.release.cluster;" ::: "memory");
    }
    const uint32_t z0 = sid >> 8;
#pragma unroll
    for (int j = 0; j < 24; j++) kacc[j >> 2][j & 3] = __uint_as_float(pin(z0, z0));
    const uint32_t ks = sb + OFF_KS + warp * 4096;
    const uint32_t st = pin(ks + lane * 16, z0);
    const uint32_t kw = pin(ks + 3584 + (lane >> 1) * 8 + (lane & 1) * 2, z0), kr = pin(ks + 3584 + q * 8, z0);
    const uint32_t kb = pin(ks + ((lane >> 3) & 1) * 512 + ((lane >> 4) * 8 + (lane & 7)) * 16, z0);
    const __nv_bfloat16* xr = p.x + (wid * 16 + ((g >> 1) << 2) + (g & 1)) * DM;
    const __nv_bfloat16 *xa = xr + (warp & 7) * 80 + q * 8, *xb = xr + (warp & 7) * 80 + q * 4;
    asm volatile("add.u64 %0, %0, %3;\nadd.u64 %1, %1, %3;\nadd.u64 %2, %2, %3;" : "+l"(xr), "+l"(xa), "+l"(xb) : "l"((uint64_t)z0));
    if (warp < 8) bar_sync(14, 512); else bar_arrive(14, 512);
    if (warp == 15) {
      sts32(sb + OFF_ZERO + lane * 4, 0);
      int gpc, i;
      if (sid < 64) { gpc = (sid & 15) >> 1; i = sid >> 4; }
      else if (sid < 120) { const int t = sid - 64; i = t / 14; gpc = 1 + ((t - i * 14) >> 1); i += 4; }
      else { gpc = 0; i = 4 + ((sid - 124) >> 1); }
      const int qi = ((0x52741630 >> (4 * i)) & 7) * 2 + (sid & 1);
      const int rg = 4 * (gpc >> 1) + (qi >> 3) * 2 + (qi & 1), jc = 4 * (gpc & 1) + ((qi >> 1) & 3);
      sts64(sb + OFF_EP + 8, rg, jc);
      __syncwarp();
      if (elect1()) {
        asm volatile("prefetch.tensormap [%0];\nprefetch.tensormap [%1];\nprefetch.tensormap [%2];\nprefetch.tensormap [%3];" ::"l"(&tmW2), "l"(&tmX), "l"(&tmW1), "l"(&tmU) : "memory");
        __nanosleep(XDLY);
        bulk_prefetch(p.x + wid * 16 * DM, 16 * DM * 2);
        mbar_expect(bar + 8 * B_W2, 96 * 176);
      }
      __syncwarp();
      load_x(xv, xa, xb, 2 * DM);
      xs[0] = __ldg((const uint32_t*)xr); xs[1] = __ldg((const uint32_t*)(xr + 2 * DM));
      bar_sync(5, 256);
      sts32(sb + OFF_EP + 4, xv[1][9]);
      if (elect1()) {
        tma5d(sb + OFF_W2S, &tmW2, (wid & 7) * 80, (wid >> 3) * 3, bar + 8 * B_W2);
        p.scr->epoch[wid] = ep0 + 1;
        sts32(sb + OFF_EP, ep0 + 1);
      }
      __syncwarp();
    }
    float zr, th, zr1, th1;
    cf c, c1;
    dt = rnd_bf(expf(bflo(pld)));
    {
      const float dl2 = dt * 1.4426950408889634f;
      zr = bflo(pa[0]) * dl2; th = bflo(pa[1]) * dt; zr1 = bfhi(pa[0]) * dl2; th1 = bfhi(pa[1]) * dt;
    }
    if (warp < 15) {
      c = cmul(cf{bflo(pa[4]), bflo(pa[5])}, cf{bflo(pa[2]), bflo(pa[3])});
      c1 = cmul(cf{bfhi(pa[4]), bfhi(pa[5])}, cf{bfhi(pa[2]), bfhi(pa[3])});
      mw = __reduce_max_sync(0xffffffffu, __float_as_uint(fmaxf(fmaxf(fabsf(c.r), fabsf(c.i)), fmaxf(fabsf(c1.r), fabsf(c1.i)))));
      mw = min(max(mw & 0x7f800000u, 20u << 23), 240u << 23);
      const float sc = __uint_as_float((259u << 23) - mw);
      k0 = c.r + c1.r;
      c.r *= sc; c.i *= -sc; c1.r *= sc; c1.i *= -sc;
      if (warp >= 8) {
        load_x(xv, xa, xb, 2 * DM);
        xs[0] = __ldg((const uint32_t*)xr); xs[1] = __ldg((const uint32_t*)(xr + 2 * DM));
        bar_arrive(5, 256);
      }
    }
    {
#pragma unroll 1
      for (int it = 0; it < 2; it++) {
        if (it == 1 && warp >= 8) {
          float sm[4] = {0.f, 0.f, 0.f, 0.f}, g0[4] = {0.f, 0.f, 0.f, 0.f}, g1[4] = {0.f, 0.f, 0.f, 0.f};
#pragma unroll
          for (int r = 0; r < 2; r++)
            xs[r] = fabsf(bflo(xs[r]) - bfhi(xs[r])) * 8.f < fabsf(bflo(xs[r])) ? __byte_perm(xs[r], 0, 0x1010) : 0u;
#pragma unroll
          for (int i = 0; i < 10; i += 2) {
            const uint32_t a0 = bsub(xv[0][i], xs[0]), a1 = bsub(xv[1][i], xs[1]), a2 = bsub(xv[0][i + 1], xs[0]), a3 = bsub(xv[1][i + 1], xs[1]);
            bmma(sm, a0, a1, a2, a3, 0x3f803f80u, 0x3f803f80u);
            bmma(g0, a0, a1, a2, a3, xv[0][i], xv[0][i + 1]);
            bmma(g1, a0, a1, a2, a3, xv[1][i], xv[1][i + 1]);
          }
          if (q == (g >> 1))
            sts128(sb + OFF_LNP + (warp - 8) * 128 + g * 16, __float_as_uint(sm[0]), __float_as_uint((g & 1) ? g0[1] : g0[0]),
                   __float_as_uint(sm[2]), __float_as_uint((g & 1) ? g1[3] : g1[2]));
          __syncwarp();
          if (warp != 11) bar_arrive(1, 256);
        }
        if (warp == 15) continue;
        float m = ex2a(zr);
        const cf w1 = cf{m * __cosf(th), m * __sinf(th)};
        m = ex2a(zr * 8.f);
        const cf w8 = cf{m * __cosf(th * 8.f), m * __sinf(th * 8.f)};
        const cf w16 = csq(w8), w32 = csq(w16), w64 = csq(w32), w128 = csq(w64), w256 = csq(w128), w512 = csq(w256), w1024 = csq(w512);
        hp lo[4];
        lo[0] = hpack(cf{1.f, 0.f}, w8);
        lo[1] = hmulc(lo[0], pack_h(w16.r, w16.i));
        { const uint32_t k = pack_h(w32.r, w32.i); lo[2] = hmulc(lo[0], k); lo[3] = hmulc(lo[1], k); }
        sts_tile(st, lo);
        { const uint32_t k = pack_h(w64.r, w64.i); sts16(kw, k); sts16(kw + 4, k >> 16); }
        const uint32_t k256 = pack_h(w256.r, w256.i), k512 = pack_h(w512.r, w512.i);
        const cf t8 = cmulj(c, w8);
        { const cf u0 = cmulj(t8, w1024), u1 = cmulj(u0, w256);
          const hp a = hpack(u0, u1), b = hmulj(a, k512);
          sts128(st + 3072, a.r, b.r, a.i, b.i); }
        const cf t1 = cmulj(c, w1), t2 = cmulj(t1, w1), t3 = cmulj(t2, w1), t4 = cmulj(t3, w1);
        const cf t5 = cmulj(t4, w1), t6 = cmulj(t5, w1), t7 = cmulj(t6, w1);
        hp T0[4], T1[4];
        T0[0] = hpack(t4, t8); T0[1] = hpack(t2, t6); T0[2] = hpack(t1, t5); T0[3] = hpack(t3, t7);
        T1[0] = hmulj(T0[0], k256); T1[1] = hmulj(T0[1], k256); T1[2] = hmulj(T0[0], k512); T1[3] = hmulj(T1[0], k512);
        sts_tile(st + 2048, T1);
        sts_tile(st + 1024, T0);
        __syncwarp();
        uint32_t bc[4];
        ldsm4t(bc, st + 3072);
#pragma unroll
        for (int m2 = 0; m2 < 4; m2 += 2) {
          uint32_t l0[4], b0[4], b1[4];
          ldsm4t(l0, kb + m2 * 128);
          ldsm4t(b0, kb + 1024 + m2 * 128);
          ldsm4t(b1, kb + 2048 + m2 * 128);
#pragma unroll
          for (int i = 0; i < 2; i++) {
            const uint2 kv = lds64(kr + (m2 + i) * 32);
            const hp k64 = {kv.x, kv.y}, L0 = {l0[2 * i], l0[2 * i + 1]};
            const hp L1 = hmule(L0, k64), L2 = hmule(L1, k64), L3 = hmule(L2, k64);
            const uint32_t c0 = lane < 16 ? bc[m2 + i] : 0u, c1b = lane < 16 ? 0u : bc[m2 + i];
            const uint32_t a0 = pin(L0.r, z0), a2 = pin(L0.i, z0);
            hmma(kacc[0], a0, L1.r, a2, L1.i, b0[2 * i], b0[2 * i + 1]);
            hmma(kacc[2], a0, L1.r, a2, L1.i, b1[2 * i], b1[2 * i + 1]);
            hmma(kacc[4], a0, L1.r, a2, L1.i, c0, c1b);
            hmma(kacc[1], L2.r, L3.r, L2.i, L3.i, b0[2 * i], b0[2 * i + 1]);
            hmma(kacc[3], L2.r, L3.r, L2.i, L3.i, b1[2 * i], b1[2 * i + 1]);
            hmma(kacc[5], L2.r, L3.r, L2.i, L3.i, c0, c1b);
          }
        }
        __syncwarp();
        zr = zr1; th = th1; c = c1;
      }
    }
    if (warp >= 8) bar_arrive(6, 512);
    if (warp < 10) {
#pragma unroll
      for (int j = 0; j < 6; j++)
        sts128(st + j * 512, __float_as_uint(kacc[j][0]), __float_as_uint(kacc[j][1]), __float_as_uint(kacc[j][2]), __float_as_uint(kacc[j][3]));
      sts64(ks + 3072 + lane * 8, __float_as_uint(k0), mw);
    }
    if (warp == 11) {
      bar_sync(1, 256);
      float s1 = 0.f, s2 = 0.f;
#pragma unroll
      for (int w = 0; w < 8; w++) {
        const uint2 v = lds64(sb + OFF_LNP + w * 128 + g * 16 + (q & 1) * 8);
        s1 += __uint_as_float(v.x); s2 += __uint_as_float(v.y);
      }
      const float md = s1 * (1.f / DM), mean = bflo((q & 1) ? xs[1] : xs[0]) + md;
      const float var = fmaxf(fmaf(-md, mean, s2 * (1.f / DM)), 0.f);
      const float m = rnd_bf(mean);
      float sd, ri;
      asm("sqrt.approx.f32 %0, %1;" : "=f"(sd) : "f"(rnd_bf(rnd_bf(var) + 1e-5f)));
      asm("rcp.approx.f32 %0, %1;" : "=f"(ri) : "f"(rnd_bf(sd)));
      if (q < 2) {
        p.scr->stats[wid * 16 + ((g >> 1) << 2) + (g & 1) + 2 * q] = make_float2(-m, 0.5f * ri);
        sts64(sb + OFF_STAT + g * 16 + q * 8, __float_as_uint(-m * ri), __float_as_uint(ri));
      }
      __syncwarp();
    }
    if (warp == 15) {
      const uint2 rj = lds64(sb + OFF_EP + 8);
      mbar_wait(bar + 8 * B_W2, 0);
#pragma unroll 1
      for (int uu = 0; uu < 3; uu++) {
        if (elect1()) load1(uu, &tmX, &tmW1, rj.x, rj.y);
        const uint32_t a = sb + OFF_W2S + (uu * 32 + lane) * 176;
        const int rem = ((wid >> 3) & 1) * 3 + uu;
        uint4* dst = p.scr->w2p + ((wid & 7) * 24 + 8 * (rem >> 1) + (wid >> 4)) * 640 + ((rem & 1) * 4 + (lane >> 3)) * 80 + (lane & 7);
        uint4 v[10];
#pragma unroll
        for (int i = 0; i < 10; i++) v[i] = lds128(a + i * 16);
#pragma unroll
        for (int i = 0; i < 8; i++)
          dst[8 * i] = make_uint4(bmul((&v[i & 4].x)[i & 3], 0x3f003f00u), bmul((&v[(i & 4) + 1].x)[i & 3], 0x3f003f00u),
                                  bmul((&v[(i & 4) + 2].x)[i & 3], 0x3f003f00u), bmul((&v[(i & 4) + 3].x)[i & 3], 0x3f003f00u));
        dst[64] = make_uint4(bmul(v[8].x, 0x3f003f00u), bmul(v[8].z, 0x3f003f00u), bmul(v[9].x, 0x3f003f00u), bmul(v[9].z, 0x3f003f00u));
        dst[72] = make_uint4(bmul(v[8].y, 0x3f003f00u), bmul(v[8].w, 0x3f003f00u), bmul(v[9].y, 0x3f003f00u), bmul(v[9].w, 0x3f003f00u));
      }
      fence_async_smem();
      __syncwarp();
      if (elect1()) load1(3, &tmX, &tmW1, rj.x, rj.y);
      __syncwarp();
    }
  }

  if (warp < 8) {
    float acc[96];
    const uint32_t alo = ((sb >> 4) | (1 << 16)) + (warp >> 2) * 512;
    bar_arrive(0, 512);
#pragma unroll 1
    for (int s = 0; s < 10; s++) {
      const uint32_t so = (s & 3) * (SLOT1 >> 4);
      mbar_wait(bar + 8 * (B_FULL1 + s), 0);
      if (s == 0) bar_sync(6, 512);
      wg_fence();
#pragma unroll
      for (int kk = 0; kk < 4; kk++)
        wgmma_n192(acc, dsc(alo + so + kk * 2, 0x40000040u), dsc((((sb + 16384) >> 4) | (512 << 16)) + so + kk * 128, 0x40000040u), (s | kk) != 0);
      wg_commit();
      wg_wait<1>();
      if (lane == 0) mbar_arrive(bar + 8 * (B_REL1 + s));
      if (s == 1 && warp == 7) {
        mbar_wait(bar + 8 * (B_REL1 + 1), 0);
        if (elect1()) { const uint2 rj = lds64(sb + OFF_EP + 8); load1(4, &tmX, &tmW1, rj.x, rj.y); }
        __syncwarp();
      }
    }
    wg_wait<0>();
    bar_arrive(14, 384);
    bar_arrive(7, 384);
    mbar_wait(bar + 8 * B_EPI, 0);
    const uint2 s0 = lds64(sb + OFF_STAT + (warp * 16 + g) * 8), s1 = lds64(sb + OFF_STAT + (warp * 16 + g + 8) * 8);
    const float nm0 = __uint_as_float(s0.x), r0 = __uint_as_float(s0.y), nm1 = __uint_as_float(s1.x), r1 = __uint_as_float(s1.y);
    const uint4 erj = lds128(sb + OFF_EP);
    const unsigned ep = erj.x;
    const int rg1 = erj.z, j1 = erj.w;
    uint4* hd = p.scr->h + (rg1 * 24 + j1) * 1024 + warp * 128 + g * 4 + (q ^ (g >> 1));
#pragma unroll
    for (int grp = 0; grp < 6; grp++) {
      uint32_t o0[4], o1[4];
      const uint4 cs[2] = {lds128(sb + OFF_CS + grp * 128 + q * 32), lds128(sb + OFF_CS + grp * 128 + q * 32 + 16)};
#pragma unroll
      for (int tl = 0; tl < 4; tl++) {
        const int nt = grp * 4 + tl;
        const float ca = __uint_as_float((&cs[tl >> 1].x)[(tl & 1) * 2]), cb = __uint_as_float((&cs[tl >> 1].x)[(tl & 1) * 2 + 1]);
        const float a = fmaf(nm0, ca, acc[4 * nt]) * r0, b = fmaf(nm0, cb, acc[4 * nt + 1]) * r0;
        const float c = fmaf(nm1, ca, acc[4 * nt + 2]) * r1, d = fmaf(nm1, cb, acc[4 * nt + 3]) * r1;
        o0[tl] = pack_bf(fmaf(a, tanha(a), a), fmaf(b, tanha(b), b));
        o1[tl] = pack_bf(fmaf(c, tanha(c), c), fmaf(d, tanha(d), d));
      }
      uint4* dst = hd + (grp >> 1) * 8192 + (grp & 1) * 32;
      dst[0] = make_uint4(o0[0], o0[1], o0[2], o0[3]);
      dst[64] = make_uint4(o1[0], o1[1], o1[2], o1[3]);
      if (grp < 5) __nanosleep(PACE);
    }
    if (warp == 7) { bar_sync(11, 256); if (lane == 0) publish(cnt + (C_H + rg1) * 32); __syncwarp(); }
    else bar_arrive(11, 256);
    const int go = (rg1 * 128 + warp * 16 + g) * DM + j1 * 80;
    load_x(xv, p.x + go + q * 8, p.x + go + q * 4, 8 * DM);
    if (warp < 4) {
      mbar_wait(bar + 8 * B_PART, 0);
      Comb cmb;
      {
        const uint4 a = lds128(sb + OFF_CMB + tid * 16);
        const uint2 b = lds64(sb + OFF_CMB + 2048 + tid * 8);
        cmb.o[0] = a.x; cmb.o[1] = a.y; cmb.o[2] = a.z; cmb.o[3] = a.w; cmb.o[4] = b.x; cmb.o[5] = b.y;
        cmb.o[6] = lds32(sb + OFF_CMB + 3072 + tid * 4);
      }
#pragma unroll 1
      for (int ch = 0; ch < 3; ch++) {
        combine(cmb, ch, wid, p.scr->sT, [] {});
      }
    } else if (warp == 4) {
      if (elect1()) {
        const uint4* srcA = p.scr->h + rg1 * 24 * 1024;
        const uint4* srcB = p.scr->w2p + j1 * 24 * 640;
        asm volatile("fence.proxy.async.global;" ::: "memory");
        mbar_wait(bar + 8 * B_PART, 0);
#pragma unroll
        for (int s = 0; s < 3; s++) {
          mbar_expect(bar + 8 * (B_FULL2 + s), SLOT2);
          bulk_g2s(sb + s * SLOT2 + 16384, srcB + s * 640, 10240, bar + 8 * (B_FULL2 + s));
        }
        poll_cnt(cnt + (C_H + rg1) * 32, ep * 8);
#pragma unroll
        for (int s = 0; s < 3; s++) bulk_g2s(sb + s * SLOT2, srcA + s * 1024, 16384, bar + 8 * (B_FULL2 + s));
#pragma unroll
        for (int s = 3; s < 5; s++) {
          mbar_wait(bar + 8 * (B_FREE + s - 2), 0);
          load2(s, sb + s * SLOT2, srcA + s * 1024, srcB + s * 640);
        }
      }
      __syncwarp();
    }
    float acc2[40];
    bar_sync(8, 512);
    {
      const uint32_t al2 = ((sb >> 4) | (1 << 16)) + (warp >> 2) * 512;
      uint32_t so = 0;
#pragma unroll 1
      for (int s = 0; s < 24; s++) {
        mbar_wait(bar + 8 * (B_FULL2 + s), 0);
        if (s == SK2 && warp < 4) bar_sync(4, 256);
        wg_fence();
#pragma unroll
        for (int kk = 0; kk < 4; kk++)
          wgmma_n80(acc2, dsc(al2 + so + (kk >> 1) * 32 + (kk & 1) * 2, 0x80000040u), dsc((((sb + 16384) >> 4) | (80 << 16)) + so + kk * 160, 8), (s | kk) != 0);
        wg_commit();
        so = so == (NS2 - 1) * (SLOT2 >> 4) ? 0 : so + (SLOT2 >> 4);
        if (s < SK2 - 1) {
          wg_wait<1>();
          if (lane == 0) mbar_arrive(bar + 8 * (B_REL2 + s));
        }
      }
      if (warp >= 4) { wg_wait<1>(); bar_arrive(4, 256); }
    }
    mbar_wait(bar + 8 * B_SFULL, 0);
    uint32_t sv[5][4];
    {
      const int i = lane & 7, mi = lane >> 3;
      const uint32_t a = sb + OFF_U + ((mi >> 1) * 8 + i) * 256 + (((2 * warp + (mi & 1)) ^ i) << 4);
#pragma unroll
      for (int k = 0; k < 5; k++) ldsm4t(sv[k], a + k * 4096);
    }
    wg_wait<0>();
#pragma unroll
    for (int hh = 0; hh < 2; hh++) {
      uint32_t o[10];
      __nv_bfloat16* op = p.out + go + hh * 8 * DM;
#pragma unroll
      for (int tl = 0; tl < 10; tl++) {
        const float a = acc2[4 * tl + 2 * hh], b = acc2[4 * tl + 2 * hh + 1];
        o[tl] = bfma(sv[tl >> 1][(tl & 1) * 2 + hh], pack_bf(fmaf(a, tanhv(a), a), fmaf(b, tanhv(b), b)), xv[hh][tl]);
        if ((tl & 3) == 3)
          asm volatile("st.global.v4.u32 [%0], {%1, %2, %3, %4};" ::"l"((uint4*)op + (tl >> 2) * 4 + q), "r"(o[tl - 3]), "r"(o[tl - 2]), "r"(o[tl - 1]), "r"(o[tl]) : "memory");
      }
      asm volatile("st.global.v2.u32 [%0], {%1, %2};" ::"l"((uint2*)(op + 64) + q), "r"(o[8]), "r"(o[9]) : "memory");
    }
  } else {
    const int cw = warp - 8;
    bar_sync(0, 512);
    const uint4 erj = lds128(sb + OFF_EP);
    const unsigned ep = erj.x;
    const int rg1 = erj.z, j1 = erj.w;
    {
      const uint4 st = lds128(sb + OFF_STAT + g * 16);
      const float n0 = __uint_as_float(st.x), r0 = __uint_as_float(st.y), n1 = __uint_as_float(st.z), r1 = __uint_as_float(st.w);
      const int up = upos(2 * wid);
      uint2* dst = (uint2*)p.scr->uT + ((up >> 1) * DM + cw * 80) * 4 + (lane ^ ((up & 1) << 1));
#pragma unroll
      for (int i = 0; i < 10; i++) {
        const uint32_t a = movm(pack_h(fmaf(bflo(xv[0][i]), r0, n0), fmaf(bfhi(xv[0][i]), r0, n0)));
        const uint32_t b = movm(pack_h(fmaf(bflo(xv[1][i]), r1, n1), fmaf(bfhi(xv[1][i]), r1, n1)));
        dst[i * 32] = make_uint2(a, b);
      }
    }
    if (warp == 8) {
      bar_sync(12, 256);
      if (lane == 0) publish(cnt + C_LN * 32);
      __syncwarp();
    } else bar_arrive(12, 256);
    if (warp == 15) {
      if (elect1()) {
#pragma unroll 1
        for (int s = 5; s < 10; s++) {
          mbar_wait(bar + 8 * (B_REL1 + s - 3), 0);
          load1(s, &tmX, &tmW1, rg1, j1);
        }
        poll_cnt(cnt + (C_CS + (j1 >> 1)) * 32, ep);
        bulk_g2s(sb + OFF_CS, p.scr->cs + j1 * 192, 768, bar + 8 * B_EPI);
      }
      __syncwarp();
    }
    if (warp >= 10 && warp < 15) {
      const uint32_t pb = sb + OFF_P + kch * 3072, pk = sb + OFF_KS + kch * 4096;
      const uint2 e0 = lds64(pk + 3072 + lane * 8), e1 = lds64(pk + 5 * 4096 + 3072 + lane * 8);
      const float dsk = bflo(pds);
      uint32_t kex = __float_as_uint(fmaxf(__uint_as_float(max(max(e0.y, e1.y), mw)) * dt, fabsf(dsk) * (1.f / 256.f))) >> 23;
      kex = min(max(kex, 20u), 240u);
      const float s2 = __uint_as_float((258 - kex) << 23), sd = s2 * dt * (1.f / 32.f);
      const float f0 = __uint_as_float(e0.y) * sd, f1 = __uint_as_float(e1.y) * sd, f2 = __uint_as_float(mw) * sd;
      k0 += __uint_as_float(e0.x) + __uint_as_float(e1.x);
#pragma unroll
      for (int o = 16; o; o >>= 1) k0 += __shfl_xor_sync(0xffffffffu, k0, o);
      const float k0n = fmaf(k0, dt, dsk) * s2;
      uint32_t h[5][2];
#pragma unroll
      for (int j = 0; j < 6; j++) {
        const uint4 a = lds128(pk + j * 512 + lane * 16), b = lds128(pk + 5 * 4096 + j * 512 + lane * 16);
#pragma unroll
        for (int e = 0; e < 4; e++) kacc[j][e] = fmaf(__uint_as_float((&a.x)[e]), f0, fmaf(__uint_as_float((&b.x)[e]), f1, kacc[j][e] * f2));
        if (j == 1) {
          const float k256 = __shfl_sync(0xffffffffu, kacc[1][3], 28);
          if (lane == 31) kacc[1][3] -= k256;
        }
        if (j == 2 || j == 3) { h[j][0] = pack_h(kacc[j][0], kacc[j][2]); h[j][1] = pack_h(kacc[j][1], kacc[j][3]); }
        else if (j < 2) { h[j][0] = pack_h(kacc[j][0], kacc[j][1]); h[j][1] = pack_h(kacc[j][2], kacc[j][3]); }
      }
      {
        const bool sw = q >> 1;
        float v[4];
#pragma unroll
        for (int e = 0; e < 4; e++) v[e] = (sw ? kacc[5][e] : kacc[4][e]) + __shfl_xor_sync(0xffffffffu, sw ? kacc[4][e] : kacc[5][e], 2);
        h[4][0] = pack_h(v[0], v[1]); h[4][1] = pack_h(v[2], v[3]);
#pragma unroll
        for (int e = 0; e < 2; e++) {
          const uint32_t r = __shfl_xor_sync(0xffffffffu, sw ? h[2][e] : h[3][e], 2);
          if (sw) h[2][e] = r; else h[3][e] = r;
        }
      }
      fence_async_smem();
      bar_arrive(13, 192);
#pragma unroll
      for (int i = 0; i < 6; i++) sts128(pb + i * 512 + lane * 16, 0, 0, 0, 0);
      __syncwarp();
      {
        const int sw = g >> 2;
        const uint32_t sel = sw ? 0x1032 : 0x3210;
        const uint32_t a = pb + (P0 + 8 * g + ((0x3124 >> (4 * q)) & 7)) * 4, a0 = a + sw * 16, a1 = a + 16 - sw * 16;
        put2<1>(a0, a1, h[0][0], sel);
        put2<1>(a0 + 256, a1 + 256, h[0][1], sel);
        put2<1>(a0 + 512, a1 + 512, h[1][0], sel);
        put2<1>(lane == 28 ? pb + PB1 * 4 : a0 + 768, a1 + 768, h[1][1], sel);
      }
      {
        const int sw = q >> 1;
        const uint32_t sel = sw ? 0x1032 : 0x3210;
        uint32_t a = pb + (((q & 1) ? PA1 : PB1 + 1) + 32 * sw + 2 * g) * 4;
        put2<1>(a + sw * 64, a + 64 - sw * 64, h[2][0], sel);
        put2<1>(a + 4 + sw * 64, a + 68 - sw * 64, h[2][1], sel);
        const int s1 = q & 1;
        const uint32_t sel1 = s1 ? 0x1032 : 0x3210;
        a = pb + (PA2 + g + 16 * sw + 32 * s1) * 4;
        put2<1>(a + s1 * 32, a + 32 - s1 * 32, h[3][0], sel1);
        put2<1>(a + (PB2 - PA2) * 4 + s1 * 32, a + (PB2 - PA2) * 4 + 32 - s1 * 32, h[3][1], sel1);
        a = pb + (((g & 1) ? PB3 : PA3) + (g >> 1) + 8 * sw + 32 * s1) * 4;
        const uint32_t hx = s1 ? h[4][1] : h[4][0], hy = s1 ? h[4][0] : h[4][1];
        put2<1>(a + s1 * 16, a + 64 + s1 * 16, hx, 0x3210);
        put2<1>(a + 16 - s1 * 16, a + 80 - s1 * 16, hy, 0x3210);
      }
      if (lane == 30) put2<1>(pb + P0 * 4, pb + (PA1 + 64) * 4, __byte_perm(pack_h(k0n, 0.f), h[2][1], 0x7610), 0x3210);
      if (lane == 31) sts64(sb + OFF_CHC + kch * 8, (kex - 4) * 0x00800080u, __byte_perm(h[3][1], 0, 0x3232));
    }
    if (warp == 8) {
      bar_sync(13, 192);
      if (elect1()) {
        mbar_expect(bar + 8 * B_UFULL, 144 * 160);
        mbar_expect(bar + 8 * B_EPI, 1024 + 768);
        poll_cnt(cnt + C_LN * 32, ep * 128);
        tma2d(sb + OFF_U - 16 * 160, &tmU, wid * 80, -16, bar + 8 * B_UFULL);
        bulk_g2s(sb + OFF_STAT, p.scr->stats + rg1 * 128, 1024, bar + 8 * B_EPI);
      }
      __syncwarp();
    }
    const int wg = warp >> 2, role = (warp + 2 * wg) & 3;
    uint32_t co[6], cpa = (g - 2 * q) * 4;
    if (role < 2) {
#pragma unroll
      for (int gm = 0; gm < 3; gm++) {
        const int hb = 2 * (lane & 7) + role - 2 + gm, l3 = ((lane >> 3) ^ (hb >> 1)) & 7;
        co[2 * gm] = hb * 1280 + uoff(l3); co[2 * gm + 1] = hb * 1280 + uoff(l3 ^ 4);
      }
    } else {
      const int mi = lane >> 3, hf = (lane >> 2) & 1;
      co[0] = hf * 1792 + (mi ^ hf) * 64 + ((q ^ (mi >> 1) ^ (hf * 2)) << 4);
      co[1] = co[0] ^ 96;
      const int i = lane & 7;
      if (role == 3) co[0] = (16 * (mi >> 1) + ((4 * (mi & 1) + (i >> 1) + 8 * (i & 1)) ^ (4 * (i & 1)))) << 4;
      co[2] = (role == 2 ? (16 * (mi >> 1) + 2 * i + (mi & 1)) ^ (i >> 2) : lane ^ ((lane >> 1) & 4)) << 4;
      co[3] = lane * 16;
      co[4] = (g >> 1) == q ? ((g & 1) ? 0xffff0000u : 0xffffu) : 0u;
      co[5] = (g - q) * 8;
    }
    const uint32_t zero = lds32(sb + OFF_ZERO), nz = zero | 0x80000000u;
#pragma unroll
    for (int i = 0; i < 6; i++) co[i] = pin(co[i], zero);
    cpa = pin(cpa, zero);
    const Comb cmb = comb_setup(tid, zero);
    if (warp >= 10 && warp < 15) bar_sync(15, 160);
    const int qt = (0x3120 >> (4 * (cw & 3))) & 3, jz = qt * 32 + lane;
    uint32_t zo[13];
    {
      const int j = jz < 112 ? jz : jz - 128, gr = j >> 1;
      zo[0] = uoff(upos(max(2 * j - 2, -32))); zo[1] = zo[0] ^ 16; zo[2] = uoff(upos(2 * j)); zo[3] = zo[2] ^ 16; zo[4] = uoff(upos(2 * j + 2));
#pragma unroll
      for (int pp = 0; pp < 4; pp++) zo[5 + pp] = ZA1 + 512 + (gr ^ ((gr >> 2) & 1)) * 64 + ((((gr >> 1) & 3) ^ pp) << 4) + (j & 1) * 8;
      zo[9] = ((j >> 3) * 16 + (j & 7)) * 16;
      zo[10] = ((j >> 4) * 32 + (j & 15)) * 16;
      zo[11] = zo[10] + ((j & 15) == 15 ? 272 : 16);
      zo[12] = (zo[9] ^ 64) + 128;
#pragma unroll
      for (int i = 0; i < 13; i++) zo[i] = pin(zo[i], zero);
    }
    if (warp < 12) {
      mbar_wait(bar + 8 * (B_REL1 + 7), 0);
      sts128(sb + OFF_CMB + (tid - 256) * 16, cmb.o[0], cmb.o[1], cmb.o[2], cmb.o[3]);
      sts64(sb + OFF_CMB + 2048 + (tid - 256) * 8, cmb.o[4], cmb.o[5]);
      sts32(sb + OFF_CMB + 3072 + (tid - 256) * 4, cmb.o[6]);
    }
    mbar_wait(bar + 8 * B_UFULL, 0);
#pragma unroll 1
    for (unsigned seq = (cw >> 2) ? 0xb9ac : 0x8; seq; seq >>= 4) {
      const int ch = seq & 7;
      if (ch == 1) bar_arrive(0, 256);
      if (ch == 2) mbar_wait(bar + 8 * (B_REL1 + 8), 0);
      const uint32_t ub = sb + OFF_U + ch * 32, zb = sb + OFF_Z + ch * ZSZ;
      uint32_t w_[20], o_[20], d_[20], b3_[20];
      uint32_t *w = w_ + 8, *o = o_ + 8, *d = d_ + 8, *b3 = b3_ + 8;
      {
        const uint4 c = lds128(ub + zo[2]), e = lds128(ub + zo[3]), b = lds128(ub + zo[1]);
        w[8] = lds32(ub + zo[4]);
        const uint2 a = lds64(ub + zo[0] + 8);
        w[-6] = a.x; w[-5] = a.y; w[-4] = b.x; w[-3] = b.y; w[-2] = b.z; w[-1] = b.w;
        w[0] = c.x; w[1] = c.y; w[2] = c.z; w[3] = c.w; w[4] = e.x; w[5] = e.y; w[6] = e.z; w[7] = e.w;
      }
#pragma unroll
      for (int i = -1; i <= 7; i++) o[i] = odd_pair(w[i], w[i + 1]);
#pragma unroll
      for (int i = 0; i <= 7; i++) { d[i] = hadd(w[i], o[i]); b3[i] = hadd(d[i], o[i - 1]); }
#pragma unroll
      for (int pp = 0; pp < 4; pp++) {
        const uint32_t sel = (pp & 1) ? 0x7632 : 0x5410;
        const int k = pp >> 1;
        sts64(zb + zo[5 + pp], __byte_perm(w[k - 1], w[k + 1], sel), __byte_perm(w[k + 3], w[k + 5], sel));
        sts64(zb + zo[5 + pp] + (ZB1 - ZA1), __byte_perm(b3[k], b3[k + 2], sel), __byte_perm(b3[k + 4], b3[k + 6], sel));
      }
      if (qt < 3) {
        uint32_t e_[20], b5_[20];
        uint32_t *e = e_ + 8, *b5 = b5_ + 8;
#pragma unroll
        for (int i = -6; i <= -2; i++) o[i] = odd_pair(w[i], w[i + 1]);
#pragma unroll
        for (int i = -6; i <= -1; i++) d[i] = hadd(w[i], o[i]);
#pragma unroll
        for (int i = -5; i <= -1; i++) b3[i] = hadd(d[i], o[i - 1]);
#pragma unroll
        for (int i = -5; i <= 4; i++) e[i] = hadd(d[i - 1], d[i]);
#pragma unroll
        for (int i = -4; i <= 4; i++) b5[i] = hadd(e[i], w[i + 1]);
        const uint32_t a2 = zb + zo[9];
        sts128(a2 + ZA2, b3[-2], b3[-1], b3[0], b3[1]);
        sts128(zb + zo[12] + ZA2, b3[2], b3[3], b3[4], b3[5]);
        sts128(a2 + ZB2, b5[-4], b5[-3], b5[-2], b5[-1]);
        sts128(zb + zo[12] + ZB2, b5[0], b5[1], b5[2], b5[3]);
        if (qt < 2) {
          sts128(a2 + ZS, d[-2], d[-1], d[0], d[1]);
          sts128(a2 + ZS + 128, d[2], d[3], d[4], d[5]);
          uint32_t b7[8], b9[8];
#pragma unroll
          for (int i = -4; i <= 3; i++) { b7[i + 4] = hadd(b3[i - 1], e[i + 1]); b9[i + 4] = hadd(e[i - 1], b5[i + 1]); }
          const uint32_t a3 = zb + zo[10];
          sts128(a3 + ZA3, b7[0], b7[1], b7[2], b7[3]);
          sts128(a3 + ZA3 + 256, b7[4], b7[5], b7[6], b7[7]);
          sts128(a3 + ZB3 + 256, b9[0], b9[1], b9[2], b9[3]);
          if (jz < 63) sts128(zb + zo[11] + ZB3, b9[4], b9[5], b9[6], b9[7]);
          else sts128(zb + ZB3, 0, 0, 0, 0);
        }
      }
    }
    bar_sync(wg == 2 ? 14 : 7, 384);
#pragma unroll 1
    for (int ch = wg - 2; ch < 5; ch += 2) {
      const uint32_t ub = sb + OFF_U + ch * 32, zb = sb + OFF_Z + ch * ZSZ, pb = sb + OFF_P + ch * 3072;
      if (ch == 2) bar_sync(0, 256);
      const uint32_t pa = pb + cpa;
      if (role < 2) {
        float acc[8][4];
#pragma unroll
        for (int r = 0; r < 8; r++) { acc[r][0] = acc[r][1] = acc[r][2] = acc[r][3] = 0.f; }
        float fix = 0.f;
        if (role == 1 && lane == 28) {
          const uint32_t k = lds32(pb + PB1 * 4), u0 = lds32(ub);
          fix = __low2float(*reinterpret_cast<const __half2*>(&k)) * __low2float(*reinterpret_cast<const __half2*>(&u0));
        }
        uint32_t b[12][4], A[17][4];
#pragma unroll
        for (int i = 11; i >= 8; i--) ldsm4(b[i], ub + (co[4 + (i & 1)] ^ (((i >> 1) & 1) * 16)) + ((i >> 1) & 1) * 640);
        A[0][0] = lds32(pa + P0 * 4); A[0][1] = lds32(pa + P0 * 4 + 32); A[0][2] = lds32(sb + OFF_ZERO + 4);
#pragma unroll
        for (int m = 0; m <= 16; m++) {
          if (m < 16) {
            A[m + 1][0] = lds32(pa + P0 * 4 + (2 * m + 2) * 32);
            A[m + 1][1] = m < 15 ? lds32(pa + P0 * 4 + (2 * m + 3) * 32) : lds32(sb + OFF_ZERO + 8);
          }
          if ((m & 1) == 0 && m < 16) {
            const int i = 7 - (m >> 1);
            ldsm4(b[i], ub + (co[2 * (i >> 2) + (i & 1)] ^ (((i >> 1) & 1) * 16)) + ((i >> 1) & 1) * 640);
          }
          if (m == 9 && elect1()) mbar_arrive(bar + 8 * (B_PAIR + ch));
          A[m][3] = dup(A[m][0], nz);
          if (m < 16) A[m + 1][2] = dup(A[m][1], nz);
#pragma unroll
          for (int r = 7; r >= 0; r--) {
            const int f = 16 + r - m;
            hmma(acc[r], A[m][0], A[m][1], A[m][2], A[m][3], b[f >> 1][(f & 1) * 2], b[f >> 1][(f & 1) * 2 + 1]);
          }
        }
        acc[7][2] += fix;
        mbar_wait(bar + 8 * (B_PAIR + ch), 0);
#pragma unroll
        for (int i = 3; i >= 0; i--)
          stsm4t(ub + (co[4 + (i & 1)] ^ (((i >> 1) & 1) * 16)) + ((i >> 1) & 1) * 640, pack_bf(acc[2 * i][0], acc[2 * i][1]), pack_bf(acc[2 * i][2], acc[2 * i][3]),
                 pack_bf(acc[2 * i + 1][0], acc[2 * i + 1][1]), pack_bf(acc[2 * i + 1][2], acc[2 * i + 1][3]));
      } else if (role == 2) {
        float acc[14][4];
#pragma unroll
        for (int r = 0; r < 14; r++) { acc[r][0] = acc[r][1] = acc[r][2] = acc[r][3] = 0.f; }
#pragma unroll
        for (int arr = 0; arr < 2; arr++) {
          uint32_t A[5][4];
#pragma unroll
          for (int m = 4; m >= 0; m--) {
            const uint2 v = lds64(pb + co[5] + (arr ? PB1 : PA1) * 4 + m * 64), w = lds64(pb + co[5] + (arr ? PB1 : PA1) * 4 + m * 64 - 32);
            A[m][0] = v.x; A[m][1] = v.y; A[m][2] = w.x; A[m][3] = w.y;
          }
#pragma unroll
          for (int ip = 0; ip < 9; ip++) {
            uint32_t b[4];
            ldsm4(b, zb + co[ip & 1] + (arr ? ZB1 : ZA1) + ip * 256);
#pragma unroll
            for (int hh = 0; hh < 2; hh++)
#pragma unroll
              for (int m = 0; m < 5; m++) {
                const int i = 2 * ip + hh - 4 + m;
                if (i >= 0 && i < 14) hmma(acc[i], A[m][0], A[m][1], A[m][2], A[m][3], b[2 * hh], b[2 * hh + 1]);
              }
          }
        }
        const uint32_t a = zb + ZA1 + 512 + co[2];
#pragma unroll
        for (int i = 0; i < 7; i++)
          stsm4(a + i * 512, pack_bf(acc[2 * i][0], acc[2 * i][1]), pack_bf(acc[2 * i][2], acc[2 * i][3]),
                pack_bf(acc[2 * i + 1][0], acc[2 * i + 1][1]), pack_bf(acc[2 * i + 1][2], acc[2 * i + 1][3]));
      } else {
        float acc[12][4];
        const uint32_t za = zb + co[3];
        {
          float d[4][2][4];
#pragma unroll
          for (int r = 0; r < 8; r++) { d[r >> 1][r & 1][0] = d[r >> 1][r & 1][1] = d[r >> 1][r & 1][2] = d[r >> 1][r & 1][3] = 0.f; }
#pragma unroll
          for (int arr = 0; arr < 2; arr++) {
            uint32_t A[4][4];
#pragma unroll
            for (int m = 0; m < 4; m++) { A[m][0] = lds32(pa + (arr ? PB3 : PA3) * 4 + m * 64); A[m][1] = lds32(pa + (arr ? PB3 : PA3) * 4 + m * 64 + 32); }
#pragma unroll
            for (int m = 0; m < 4; m++) { A[m][2] = m ? dup(A[m - 1][1], nz) : lds32(sb + OFF_ZERO + 4 + arr * 4); A[m][3] = dup(A[m][0], nz); }
#pragma unroll
            for (int io = 0; io < 4; io++) {
              uint32_t b[4];
              ldsm4t(b, za + (arr ? ZB3 : ZA3) + io * 512);
#pragma unroll
              for (int m = 0; m + io < 4; m++) {
                hmma(d[io + m][0], A[m][0], A[m][1], A[m][2], A[m][3], b[0], b[1]);
                hmma(d[io + m][1], A[m][0], A[m][1], A[m][2], A[m][3], b[2], b[3]);
              }
            }
          }
#pragma unroll
          for (int r = 0; r < 4; r++) {
            acc[r][0] = acc[r][1] = acc[r][2] = acc[r][3] = 0.f;
            acc[4 + 2 * r][0] = d[r][0][0]; acc[4 + 2 * r][1] = d[r][0][1]; acc[4 + 2 * r][2] = d[r][1][0]; acc[4 + 2 * r][3] = d[r][1][1];
            acc[5 + 2 * r][0] = d[r][0][2]; acc[5 + 2 * r][1] = d[r][0][3]; acc[5 + 2 * r][2] = d[r][1][2]; acc[5 + 2 * r][3] = d[r][1][3];
          }
        }
        {
          const uint32_t k0 = lds32(sb + OFF_CHC + ch * 8 + 4) & co[4];
          const uint32_t k1 = lds32(sb + OFF_ZERO + 12), k2 = lds32(sb + OFF_ZERO + 16), k3 = dup(k0, nz);
#pragma unroll
          for (int ip = 0; ip < 4; ip++) {
            uint32_t b[4];
            ldsm4t(b, za + ZS + ip * 512);
            hmma(acc[4 + 2 * ip], k0, k1, k2, k3, b[0], b[1]);
            hmma(acc[5 + 2 * ip], k0, k1, k2, k3, b[2], b[3]);
          }
        }
        const uint32_t pa2 = pb + co[5];
#pragma unroll
        for (int arr = 0; arr < 2; arr++) {
          uint32_t A[5][4];
#pragma unroll
          for (int m = 0; m < 5; m++) {
            const uint2 v = lds64(pa2 + (arr ? PB2 : PA2) * 4 + m * 64), w = lds64(pa2 + (arr ? PB2 : PA2) * 4 + m * 64 - 32);
            A[m][0] = v.x; A[m][1] = v.y; A[m][2] = w.x; A[m][3] = w.y;
          }
#pragma unroll
          for (int ip = 0; ip < 6; ip++) {
            uint32_t b[4];
            ldsm4t(b, zb + co[0] + (arr ? ZB2 : ZA2) + ip * 512);
#pragma unroll
            for (int hh = 0; hh < 2; hh++)
#pragma unroll
              for (int m = 0; m < 5; m++) {
                const int i = 2 * ip + hh + m;
                if (i < 12) hmma(acc[i], A[m][0], A[m][1], A[m][2], A[m][3], b[2 * hh], b[2 * hh + 1]);
              }
          }
        }
        const uint32_t a = zb + ZA2 + co[2];
#pragma unroll
        for (int i = 0; i < 6; i++)
          stsm4(a + i * 512, pack_bf(acc[2 * i][0], acc[2 * i][1]), pack_bf(acc[2 * i][2], acc[2 * i][3]),
                pack_bf(acc[2 * i + 1][0], acc[2 * i + 1][1]), pack_bf(acc[2 * i + 1][2], acc[2 * i + 1][3]));
      }
      __syncwarp();
      if (elect1()) mbar_arrive(bar + 8 * (B_PART + ch));
    }
    const uint4* srcA = p.scr->h + (rg1 * 24 + NS2 - 2) * 1024;
    const uint4* srcB = p.scr->w2p + (j1 * 24 + NS2 - 2) * 640;
    combine(cmb, 6 - wg, wid, p.scr->sT, [&] {
      if (warp == 12) {
        bar_sync(8, 512);
        if (elect1()) {
          asm volatile("fence.proxy.async.global;" ::: "memory");
          load2(NS2 - 2, sb + (NS2 - 2) * SLOT2, srcA, srcB);
          load2(NS2 - 1, sb + (NS2 - 1) * SLOT2, srcA + 1024, srcB + 640);
        }
        __syncwarp();
      } else bar_arrive(8, 512);
    });
    if (warp == 12) {
      if (elect1()) {
        uint32_t d = sb;
#pragma unroll 1
        for (int s = NS2; s < 24; s++) {
          mbar_wait(bar + 8 * (B_REL2 + s - NS2 + 1), 0);
          load2(s, d, srcA + 2048, srcB + 1280);
          srcA += 1024; srcB += 640;
          d = d == sb + (NS2 - 1) * SLOT2 ? sb : d + SLOT2;
        }
      }
      __syncwarp();
    } else if (warp == 13) {
      if (elect1()) {
#pragma unroll 1
        for (int c = 2; c < 5; c++) mbar_wait(bar + 8 * (B_FREE + c), 0);
        publish(cnt + (C_S + (wid >> 4)) * 32);
        mbar_expect(bar + 8 * B_SFULL, 20480);
        poll_cnt(cnt + (C_S + j1) * 32, ep * 16);
        mbar_wait(bar + 8 * (B_REL2 + 24 - NS2), 0);
        bulk_g2s(sb + OFF_U, p.scr->sT + (j1 * 16 + rg1) * 1280, 20480, bar + 8 * B_SFULL);
      }
      __syncwarp();
    }
  }
}

typedef CUresult (*EncodeFn)(CUtensorMap*, CUtensorMapDataType, cuuint32_t, void*, const cuuint64_t*, const cuuint64_t*,
                             const cuuint32_t*, const cuuint32_t*, CUtensorMapInterleave, CUtensorMapSwizzle,
                             CUtensorMapL2promotion, CUtensorMapFloatOOBfill);

}

extern "C" void kernel_launch(void* const* d_in, const int* in_sizes, int n_in, void* d_out, int out_size) {
  static EncodeFn enc = nullptr;
  static int nsm = 0;
  static void* scr = nullptr;
  if (!enc) {
    void* fn = nullptr;
    cudaDriverEntryPointQueryResult qr;
    cudaGetDriverEntryPoint("cuTensorMapEncodeTiled", &fn, cudaEnableDefault, &qr);
    enc = (EncodeFn)fn;
    int dev = 0;
    cudaGetDevice(&dev);
    cudaDeviceGetAttribute(&nsm, cudaDevAttrMultiProcessorCount, dev);
    cudaFuncSetAttribute(fused_s4_ffn_kernel<true>, cudaFuncAttributeMaxDynamicSharedMemorySize, SMEM_BYTES);
    cudaFuncSetAttribute(fused_s4_ffn_kernel<false>, cudaFuncAttributeMaxDynamicSharedMemorySize, SMEM_BYTES);
    cudaGetSymbolAddress(&scr, g_scr);
  }
  Params p;
  p.x = (const __nv_bfloat16*)d_in[0];
  p.are = (const __nv_bfloat16*)d_in[1]; p.aim = (const __nv_bfloat16*)d_in[2];
  p.bre = (const __nv_bfloat16*)d_in[3]; p.bim = (const __nv_bfloat16*)d_in[4];
  p.cre = (const __nv_bfloat16*)d_in[5]; p.cim = (const __nv_bfloat16*)d_in[6];
  p.logdt = (const __nv_bfloat16*)d_in[7]; p.dskip = (const __nv_bfloat16*)d_in[8];
  p.w1 = (const __nv_bfloat16*)d_in[10]; p.w2 = (const __nv_bfloat16*)d_in[11];
  p.out = (__nv_bfloat16*)d_out;
  p.scr = (Scratch*)scr;
  CUtensorMap tmX, tmW1, tmU, tmW2;
  const cuuint32_t es[5] = {1, 1, 1, 1, 1};
  {
    const cuuint64_t gd[5] = {DM, 2, 4, 4, FF / 32}, gs[4] = {DM * 2, DM * 16, DM * 4, DM * 64};
    const cuuint32_t bx[5] = {88, 2, 4, 4, 3};
    enc(&tmW2, CU_TENSOR_MAP_DATA_TYPE_BFLOAT16, 5, d_in[11], gd, gs, bx, es, CU_TENSOR_MAP_INTERLEAVE_NONE,
        CU_TENSOR_MAP_SWIZZLE_NONE, CU_TENSOR_MAP_L2_PROMOTION_NONE, CU_TENSOR_MAP_FLOAT_OOB_FILL_NONE);
  }
  {
    const cuuint64_t gd[2] = {16 * DM, 128}, gs[1] = {DM * 32};
    const cuuint32_t bx[2] = {80, 144};
    enc(&tmU, CU_TENSOR_MAP_DATA_TYPE_FLOAT16, 2, p.scr->uT, gd, gs, bx, es, CU_TENSOR_MAP_INTERLEAVE_NONE,
        CU_TENSOR_MAP_SWIZZLE_NONE, CU_TENSOR_MAP_L2_PROMOTION_NONE, CU_TENSOR_MAP_FLOAT_OOB_FILL_NONE);
  }
  {
    const cuuint64_t gd[2] = {DM, SEQ}, gs[1] = {DM * 2};
    const cuuint32_t bx[2] = {64, 128};
    enc(&tmX, CU_TENSOR_MAP_DATA_TYPE_BFLOAT16, 2, d_in[0], gd, gs, bx, es, CU_TENSOR_MAP_INTERLEAVE_NONE,
        CU_TENSOR_MAP_SWIZZLE_128B, CU_TENSOR_MAP_L2_PROMOTION_L2_128B, CU_TENSOR_MAP_FLOAT_OOB_FILL_NONE);
  }
  {
    const cuuint64_t gd[3] = {64, DM, FF / 64}, gs[2] = {FF * 2, 128};
    const cuuint32_t bx[3] = {64, 64, 3};
    enc(&tmW1, CU_TENSOR_MAP_DATA_TYPE_BFLOAT16, 3, d_in[10], gd, gs, bx, es, CU_TENSOR_MAP_INTERLEAVE_NONE,
        CU_TENSOR_MAP_SWIZZLE_128B, CU_TENSOR_MAP_L2_PROMOTION_L2_128B, CU_TENSOR_MAP_FLOAT_OOB_FILL_NONE);
  }
  if (nsm == 132) fused_s4_ffn_kernel<true><<<132, 512, SMEM_BYTES>>>(p, tmX, tmW1, tmU, tmW2);
  else fused_s4_ffn_kernel<false><<<132, 512, SMEM_BYTES>>>(p, tmX, tmW1, tmU, tmW2);
}
```

```cpp
#include <cuda_runtime.h>
#include <cuda_bf16.h>
#include <cuda_fp16.h>
#include <cuda.h>
#include <stdint.h>

namespace {

constexpr int SEQ = 2048, DM = 640, FF = 1536;

constexpr int SLOT1 = 40960;
constexpr int SLOT2 = 26624;
constexpr int NS2 = 7;
constexpr int LDLY = 150;
constexpr int XDLY = 100;
constexpr int PACE = 20;
constexpr int SK2 = 21;
constexpr int OFF_Z = 85504, ZSZ = 20480;
constexpr int ZA3 = 0, ZB3 = 2048, ZS = 4096, ZA2 = 6144, ZB2 = 9216, ZA1 = 12288, ZB1 = 16384;
constexpr int OFF_CMB = 2 * SLOT1;
constexpr int OFF_W2S = 3 * SLOT1;
constexpr int OFF_U = 190464;
constexpr int OFF_P = 210944;
constexpr int OFF_KS = 163840;
constexpr int OFF_LNP = 225280;
constexpr int OFF_MISC = 226304;
constexpr int OFF_CHC = OFF_MISC + 16;
constexpr int OFF_EP = OFF_MISC + 64;
constexpr int OFF_ZERO = OFF_MISC + 128;
constexpr int OFF_SH = OFF_MISC + 256;
constexpr int OFF_STAT = OFF_MISC + 1024;
constexpr int OFF_CS = OFF_MISC + 2048;
constexpr int OFF_BAR = OFF_MISC + 2816;
constexpr int SMEM_BYTES = OFF_MISC + 6144;
constexpr int P0 = 8, PA1 = 280, PB1 = 360, PA2 = 448, PB2 = 544, PA3 = 632, PB3 = 704;
enum { B_W2 = 0, B_FULL1 = 1, B_FULL2 = 11, B_UFULL = 35, B_EPI = 36, B_SFULL = 37,
       B_PAIR = 42,
       B_FREE = 48, B_PART = 54,
       B_REL1 = 60, B_REL2 = 70 };
enum { C_LN = 0, C_H = 2, C_S = 34, C_CS = 42, C_NUM = 46 };

struct Scratch {
  unsigned cnt[64 * 32];
  unsigned epoch[256];
  float2 stats[SEQ];
  float cs[FF];
  uint4 uT[DM * 256];
  uint4 w2p[8 * 24 * 640];
  uint4 sT[8 * 16 * 1280];
  uint4 h[16 * 24 * 1024];
};
__device__ __align__(1024) Scratch g_scr;
constexpr uint32_t sb = 1024;
constexpr uint32_t bar = sb + OFF_BAR;

struct Params {
  const __nv_bfloat16 *are, *aim, *bre, *bim, *cre, *cim, *logdt, *dskip, *x, *w1, *w2;
  __nv_bfloat16* out;
  Scratch* scr;
};

__device__ __forceinline__ void mbar_init(uint32_t a, int c) { asm volatile("mbarrier.init.shared::cta.b64 [%0], %1;" ::"r"(a), "r"(c)); }
__device__ __forceinline__ void mbar_expect(uint32_t a, int b) { asm volatile("mbarrier.arrive.expect_tx.shared::cta.b64 _, [%0], %1;" ::"r"(a), "r"(b) : "memory"); }
__device__ __forceinline__ void mbar_arrive(uint32_t a) { asm volatile("mbarrier.arrive.shared::cta.b64 _, [%0];" ::"r"(a) : "memory"); }
__device__ __forceinline__ void mbar_wait(uint32_t a, int ph) {
  asm volatile(
      "{\n.reg .pred p;\n.reg .u32 n;\n"
      "mbarrier.try_wait.parity.shared::cta.b64 p, [%0], %1;\n@p bra LD;\nmov.u32 n, 0;\n"
      "LW:\nmbarrier.try_wait.parity.shared::cta.b64 p, [%0], %1, 20000;\n@p bra LD;\n"
      "add.u32 n, n, 1;\nsetp.lt.u32 p, n, 100000;\n@p bra LW;\ntrap;\nLD:\n}\n" ::"r"(a), "r"(ph) : "memory");
}
__device__ __forceinline__ void poll_cnt(const unsigned* p, unsigned target) {
  asm volatile(
      "{\n.reg .pred p;\n.reg .u32 n;\n.reg .s32 v;\nmov.u32 n, 0;\n"
      "LW:\nld.relaxed.gpu.global.u32 v, [%0];\nsub.s32 v, v, %1;\nsetp.ge.s32 p, v, 0;\n@p bra LD;\n"
      "nanosleep.u32 64;\nadd.u32 n, n, 1;\nsetp.lt.u32 p, n, 4000000;\n@p bra LW;\ntrap;\n"
      "LD:\nfence.acquire.gpu;\nfence.proxy.async.global;\n}\n" ::"l"(p), "r"(target) : "memory");
}
__device__ __forceinline__ void publish(unsigned* p) {
  asm volatile("fence.proxy.async.global;\nfence.release.gpu;\nred.relaxed.gpu.global.add.u32 [%0], 1;" ::"l"(p) : "memory");
}
__device__ __forceinline__ uint32_t movm(uint32_t v) { uint32_t r; asm volatile("movmatrix.sync.aligned.m8n8.trans.b16 %0, %1;" : "=r"(r) : "r"(v)); return r; }
__device__ __forceinline__ void fence_async_smem() { asm volatile("fence.proxy.async.shared::cta;" ::: "memory"); }
__device__ __forceinline__ bool elect1() { uint32_t p; asm volatile("{\n.reg .pred P;\nelect.sync _|P, 0xffffffff;\nselp.u32 %0,1,0,P;\n}\n" : "=r"(p)); return p; }
__device__ __forceinline__ void bar_sync(int id, int n) { asm volatile("bar.sync %0, %1;" ::"r"(id), "r"(n) : "memory"); }
__device__ __forceinline__ void bar_arrive(int id, int n) { asm volatile("bar.arrive %0, %1;" ::"r"(id), "r"(n) : "memory"); }
__device__ __forceinline__ void bulk_g2s(uint32_t dst, const void* src, int bytes, uint32_t mb) {
  asm volatile("cp.async.bulk.shared::cluster.global.mbarrier::complete_tx::bytes [%0], [%1], %2, [%3];" ::"r"(dst), "l"(src), "r"(bytes), "r"(mb) : "memory");
}
__device__ __forceinline__ void bulk_prefetch(const void* src, int bytes) { asm volatile("cp.async.bulk.prefetch.L2.global [%0], %1;" ::"l"(src), "r"(bytes) : "memory"); }
__device__ __forceinline__ void tma2d(uint32_t dst, const CUtensorMap* m, int c0, int c1, uint32_t mb) {
  asm volatile("cp.async.bulk.tensor.2d.shared::cluster.global.mbarrier::complete_tx::bytes [%0], [%1, {%3, %4}], [%2];" ::"r"(dst), "l"(m), "r"(mb), "r"(c0), "r"(c1) : "memory");
}
__device__ __forceinline__ void tma3d(uint32_t dst, const CUtensorMap* m, int c0, int c1, int c2, uint32_t mb) {
  asm volatile("cp.async.bulk.tensor.3d.shared::cluster.global.mbarrier::complete_tx::bytes [%0], [%1, {%3, %4, %5}], [%2];" ::"r"(dst), "l"(m), "r"(mb), "r"(c0), "r"(c1), "r"(c2) : "memory");
}
__device__ __forceinline__ unsigned frag_col(unsigned l) { return (l & 0x61) | ((l & 6) << (2 - (l >> 6))) | ((l >> 2) & 6); }
__device__ __forceinline__ void tma5d(uint32_t dst, const CUtensorMap* m, int c0, int c4, uint32_t mb) {
  asm volatile("cp.async.bulk.tensor.5d.shared::cluster.global.mbarrier::complete_tx::bytes [%0], [%1, {%3, %5, %5, %5, %4}], [%2];" ::"r"(dst), "l"(m), "r"(mb), "r"(c0), "r"(c4), "r"(0) : "memory");
}
__device__ __forceinline__ uint64_t dsc(uint32_t lo, uint32_t hi) { return ((uint64_t)hi << 32) | lo; }
__device__ __forceinline__ void wg_fence() { asm volatile("wgmma.fence.sync.aligned;" ::: "memory"); }
__device__ __forceinline__ void wg_commit() { asm volatile("wgmma.commit_group.sync.aligned;" ::: "memory"); }
template <int N> __device__ __forceinline__ void wg_wait() { asm volatile("wgmma.wait_group.sync.aligned %0;" ::"n"(N) : "memory"); }
__device__ __forceinline__ void wgmma_n192(float (&d)[96], uint64_t da, uint64_t db, int scale_d) {
  asm volatile("{\n.reg .pred p;\nsetp.ne.b32 p, %98, 0;\n"
    "wgmma.mma_async.sync.aligned.m64n192k16.f32.bf16.bf16 "
    "{"
    "%0, %1, %2, %3, %4, %5, %6, %7, %8, %9, %10, %11, %12, %13, %14, %15, "
    "%16, %17, %18, %19, %20, %21, %22, %23, %24, %25, %26, %27, %28, %29, %30, %31, "
    "%32, %33, %34, %35, %36, %37, %38, %39, %40, %41, %42, %43, %44, %45, %46, %47, "
    "%48, %49, %50, %51, %52, %53, %54, %55, %56, %57, %58, %59, %60, %61, %62, %63, "
    "%64, %65, %66, %67, %68, %69, %70, %71, %72, %73, %74, %75, %76, %77, %78, %79, "
    "%80, %81, %82, %83, %84, %85, %86, %87, %88, %89, %90, %91, %92, %93, %94, %95"
    "}, "
    "%96, %97, p, 1, 1, 0, 1;\n}\n"
    : "+f"(d[0]), "+f"(d[1]), "+f"(d[2]), "+f"(d[3]), "+f"(d[4]), "+f"(d[5]), "+f"(d[6]), "+f"(d[7]),
      "+f"(d[8]), "+f"(d[9]), "+f"(d[10]), "+f"(d[11]), "+f"(d[12]), "+f"(d[13]), "+f"(d[14]), "+f"(d[15]),
      "+f"(d[16]), "+f"(d[17]), "+f"(d[18]), "+f"(d[19]), "+f"(d[20]), "+f"(d[21]), "+f"(d[22]), "+f"(d[23]),
      "+f"(d[24]), "+f"(d[25]), "+f"(d[26]), "+f"(d[27]), "+f"(d[28]), "+f"(d[29]), "+f"(d[30]), "+f"(d[31]),
      "+f"(d[32]), "+f"(d[33]), "+f"(d[34]), "+f"(d[35]), "+f"(d[36]), "+f"(d[37]), "+f"(d[38]), "+f"(d[39]),
      "+f"(d[40]), "+f"(d[41]), "+f"(d[42]), "+f"(d[43]), "+f"(d[44]), "+f"(d[45]), "+f"(d[46]), "+f"(d[47]),
      "+f"(d[48]), "+f"(d[49]), "+f"(d[50]), "+f"(d[51]), "+f"(d[52]), "+f"(d[53]), "+f"(d[54]), "+f"(d[55]),
      "+f"(d[56]), "+f"(d[57]), "+f"(d[58]), "+f"(d[59]), "+f"(d[60]), "+f"(d[61]), "+f"(d[62]), "+f"(d[63]),
      "+f"(d[64]), "+f"(d[65]), "+f"(d[66]), "+f"(d[67]), "+f"(d[68]), "+f"(d[69]), "+f"(d[70]), "+f"(d[71]),
      "+f"(d[72]), "+f"(d[73]), "+f"(d[74]), "+f"(d[75]), "+f"(d[76]), "+f"(d[77]), "+f"(d[78]), "+f"(d[79]),
      "+f"(d[80]), "+f"(d[81]), "+f"(d[82]), "+f"(d[83]), "+f"(d[84]), "+f"(d[85]), "+f"(d[86]), "+f"(d[87]),
      "+f"(d[88]), "+f"(d[89]), "+f"(d[90]), "+f"(d[91]), "+f"(d[92]), "+f"(d[93]), "+f"(d[94]), "+f"(d[95])
    : "l"(da), "l"(db), "r"(scale_d));
}

__device__ __forceinline__ void wgmma_n80(float (&d)[40], uint64_t da, uint64_t db, int scale_d) {
  asm volatile("{\n.reg .pred p;\nsetp.ne.b32 p, %42, 0;\n"
    "wgmma.mma_async.sync.aligned.m64n80k16.f32.bf16.bf16 "
    "{"
    "%0, %1, %2, %3, %4, %5, %6, %7, %8, %9, %10, %11, %12, %13, %14, %15, "
    "%16, %17, %18, %19, %20, %21, %22, %23, %24, %25, %26, %27, %28, %29, %30, %31, "
    "%32, %33, %34, %35, %36, %37, %38, %39"
    "}, "
    "%40, %41, p, 1, 1, 0, 1;\n}\n"
    : "+f"(d[0]), "+f"(d[1]), "+f"(d[2]), "+f"(d[3]), "+f"(d[4]), "+f"(d[5]), "+f"(d[6]), "+f"(d[7]),
      "+f"(d[8]), "+f"(d[9]), "+f"(d[10]), "+f"(d[11]), "+f"(d[12]), "+f"(d[13]), "+f"(d[14]), "+f"(d[15]),
      "+f"(d[16]), "+f"(d[17]), "+f"(d[18]), "+f"(d[19]), "+f"(d[20]), "+f"(d[21]), "+f"(d[22]), "+f"(d[23]),
      "+f"(d[24]), "+f"(d[25]), "+f"(d[26]), "+f"(d[27]), "+f"(d[28]), "+f"(d[29]), "+f"(d[30]), "+f"(d[31]),
      "+f"(d[32]), "+f"(d[33]), "+f"(d[34]), "+f"(d[35]), "+f"(d[36]), "+f"(d[37]), "+f"(d[38]), "+f"(d[39])
    : "l"(da), "l"(db), "r"(scale_d));
}

__device__ __forceinline__ void hmma(float* c, uint32_t a0, uint32_t a1, uint32_t a2, uint32_t a3, uint32_t b0, uint32_t b1) {
  asm volatile("mma.sync.aligned.m16n8k16.row.col.f32.f16.f16.f32 {%0,%1,%2,%3}, {%4,%5,%6,%7}, {%8,%9}, {%0,%1,%2,%3};"
      : "+f"(c[0]), "+f"(c[1]), "+f"(c[2]), "+f"(c[3]) : "r"(a0), "r"(a1), "r"(a2), "r"(a3), "r"(b0), "r"(b1));
}
__device__ __forceinline__ void ldsm4(uint32_t* r, uint32_t a) { asm volatile("ldmatrix.sync.aligned.m8n8.x4.shared.b16 {%0,%1,%2,%3}, [%4];" : "=r"(r[0]), "=r"(r[1]), "=r"(r[2]), "=r"(r[3]) : "r"(a) : "memory"); }
__device__ __forceinline__ void ldsm4t(uint32_t* r, uint32_t a) { asm volatile("ldmatrix.sync.aligned.m8n8.x4.trans.shared.b16 {%0,%1,%2,%3}, [%4];" : "=r"(r[0]), "=r"(r[1]), "=r"(r[2]), "=r"(r[3]) : "r"(a) : "memory"); }
__device__ __forceinline__ void stsm4(uint32_t a, uint32_t r0, uint32_t r1, uint32_t r2, uint32_t r3) { asm volatile("stmatrix.sync.aligned.m8n8.x4.shared.b16 [%0], {%1,%2,%3,%4};" ::"r"(a), "r"(r0), "r"(r1), "r"(r2), "r"(r3) : "memory"); }
__device__ __forceinline__ void stsm4t(uint32_t a, uint32_t r0, uint32_t r1, uint32_t r2, uint32_t r3) { asm volatile("stmatrix.sync.aligned.m8n8.x4.trans.shared.b16 [%0], {%1,%2,%3,%4};" ::"r"(a), "r"(r0), "r"(r1), "r"(r2), "r"(r3) : "memory"); }
__device__ __forceinline__ uint32_t lds32(uint32_t a) { uint32_t v; asm volatile("ld.shared.u32 %0, [%1];" : "=r"(v) : "r"(a) : "memory"); return v; }
__device__ __forceinline__ uint2 lds64(uint32_t a) { uint2 v; asm volatile("ld.shared.v2.u32 {%0,%1}, [%2];" : "=r"(v.x), "=r"(v.y) : "r"(a) : "memory"); return v; }
__device__ __forceinline__ uint4 lds128(uint32_t a) { uint4 v; asm volatile("ld.shared.v4.u32 {%0,%1,%2,%3}, [%4];" : "=r"(v.x), "=r"(v.y), "=r"(v.z), "=r"(v.w) : "r"(a) : "memory"); return v; }
__device__ __forceinline__ void sts16(uint32_t a, uint32_t v) { asm volatile("st.shared.u16 [%0], %1;" ::"r"(a), "h"((unsigned short)v) : "memory"); }
__device__ __forceinline__ void sts32(uint32_t a, uint32_t v) { asm volatile("st.shared.u32 [%0], %1;" ::"r"(a), "r"(v) : "memory"); }
__device__ __forceinline__ void sts64(uint32_t a, uint32_t x, uint32_t y) { asm volatile("st.shared.v2.u32 [%0], {%1,%2};" ::"r"(a), "r"(x), "r"(y) : "memory"); }
__device__ __forceinline__ void sts128(uint32_t a, uint32_t x, uint32_t y, uint32_t z, uint32_t w) { asm volatile("st.shared.v4.u32 [%0], {%1,%2,%3,%4};" ::"r"(a), "r"(x), "r"(y), "r"(z), "r"(w) : "memory"); }
__device__ __forceinline__ uint32_t ldg32(const void* a) { uint32_t v; asm volatile("ld.global.nc.u32 %0, [%1];" : "=r"(v) : "l"(a)); return v; }
__device__ __forceinline__ uint32_t ldg16(const void* a) { uint32_t v; asm volatile("ld.global.nc.u16 %0, [%1];" : "=r"(v) : "l"(a)); return v; }
__device__ __forceinline__ float bflo(uint32_t v) { return __uint_as_float(v << 16); }
__device__ __forceinline__ float bfhi(uint32_t v) { return __uint_as_float(v & 0xffff0000u); }
__device__ __forceinline__ uint32_t pack_bf(float lo, float hi) { uint32_t r; asm("cvt.rn.bf16x2.f32 %0, %1, %2;" : "=r"(r) : "f"(hi), "f"(lo)); return r; }
__device__ __forceinline__ uint32_t pack_h(float lo, float hi) { uint32_t r; asm("cvt.rn.f16x2.f32 %0, %1, %2;" : "=r"(r) : "f"(hi), "f"(lo)); return r; }
__device__ __forceinline__ float rnd_bf(float v) { return __bfloat162float(__float2bfloat16_rn(v)); }
__device__ __forceinline__ float ex2a(float v) { float r; asm("ex2.approx.ftz.f32 %0, %1;" : "=f"(r) : "f"(v)); return r; }
__device__ __forceinline__ float tanha(float v) { float r; asm("tanh.approx.f32 %0, %1;" : "=f"(r) : "f"(v)); return r; }
__device__ __forceinline__ uint32_t hadd(uint32_t a, uint32_t b) { uint32_t r; asm("add.rn.f16x2 %0, %1, %2;" : "=r"(r) : "r"(a), "r"(b)); return r; }
__device__ __forceinline__ uint32_t badd(uint32_t a, uint32_t b) { uint32_t r; asm("add.rn.bf16x2 %0, %1, %2;" : "=r"(r) : "r"(a), "r"(b)); return r; }
__device__ __forceinline__ uint32_t bmul(uint32_t a, uint32_t b) { uint32_t r; asm("mul.rn.bf16x2 %0, %1, %2;" : "=r"(r) : "r"(a), "r"(b)); return r; }
__device__ __forceinline__ uint32_t bfma(uint32_t a, uint32_t b, uint32_t c) { uint32_t r; asm("fma.rn.bf16x2 %0, %1, %2, %3;" : "=r"(r) : "r"(a), "r"(b), "r"(c)); return r; }
__device__ __forceinline__ float tanhv(float v) { float r; asm volatile("tanh.approx.f32 %0, %1;" : "=f"(r) : "f"(v)); return r; }
__device__ __forceinline__ uint32_t bsub(uint32_t a, uint32_t b) { uint32_t r; asm("sub.rn.bf16x2 %0, %1, %2;" : "=r"(r) : "r"(a), "r"(b)); return r; }
__device__ __forceinline__ uint32_t dup(uint32_t v, uint32_t nz) { uint32_t r; asm volatile("add.rn.f32 %0, %1, %2;" : "=r"(r) : "r"(v), "r"(nz)); return r; }
__device__ __forceinline__ void bmma(float* c, uint32_t a0, uint32_t a1, uint32_t a2, uint32_t a3, uint32_t b0, uint32_t b1) {
  asm("mma.sync.aligned.m16n8k16.row.col.f32.bf16.bf16.f32 {%0,%1,%2,%3}, {%4,%5,%6,%7}, {%8,%9}, {%0,%1,%2,%3};"
      : "+f"(c[0]), "+f"(c[1]), "+f"(c[2]), "+f"(c[3]) : "r"(a0), "r"(a1), "r"(a2), "r"(a3), "r"(b0), "r"(b1));
}
__device__ __forceinline__ uint32_t odd_pair(uint32_t a, uint32_t b) { return __byte_perm(a, b, 0x5432); }
__device__ __forceinline__ int upos(int c) { return c ^ ((c >> 5) & 7) ^ ((c >> 3) & 1); }
__device__ __forceinline__ int uoff(int pos) { return (pos >> 1) * 160 + (pos & 1) * 16; }

struct cf { float r, i; };
__device__ __forceinline__ cf cmul(cf a, cf b) { cf o; o.r = fmaf(a.r, b.r, -a.i * b.i); o.i = fmaf(a.r, b.i, a.i * b.r); return o; }
__device__ __forceinline__ cf cmulj(cf a, cf b) { cf o; o.r = fmaf(a.r, b.r, a.i * b.i); o.i = fmaf(a.i, b.r, -a.r * b.i); return o; }
__device__ __forceinline__ cf csq(cf a) { cf o; o.r = fmaf(a.r, a.r, -a.i * a.i); o.i = (a.r + a.r) * a.i; return o; }
struct hp { uint32_t r, i; };
__device__ __forceinline__ hp hpack(cf a, cf b) { hp o; o.r = pack_h(a.r, b.r); o.i = pack_h(a.i, b.i); return o; }
__device__ __forceinline__ hp hmulc(hp a, uint32_t c) {
  __half2 ar = *reinterpret_cast<__half2*>(&a.r), ai = *reinterpret_cast<__half2*>(&a.i), cc = *reinterpret_cast<__half2*>(&c);
  __half2 orr = __hfma2(ar, __low2half2(cc), __hneg2(__hmul2(ai, __high2half2(cc))));
  __half2 oi = __hfma2(ar, __high2half2(cc), __hmul2(ai, __low2half2(cc)));
  hp o; o.r = *reinterpret_cast<uint32_t*>(&orr); o.i = *reinterpret_cast<uint32_t*>(&oi); return o;
}
__device__ __forceinline__ hp hmulj(hp a, uint32_t c) {
  __half2 ar = *reinterpret_cast<__half2*>(&a.r), ai = *reinterpret_cast<__half2*>(&a.i), cc = *reinterpret_cast<__half2*>(&c);
  __half2 orr = __hfma2(ar, __low2half2(cc), __hmul2(ai, __high2half2(cc)));
  __half2 oi = __hfma2(ai, __low2half2(cc), __hneg2(__hmul2(ar, __high2half2(cc))));
  hp o; o.r = *reinterpret_cast<uint32_t*>(&orr); o.i = *reinterpret_cast<uint32_t*>(&oi); return o;
}
__device__ __forceinline__ hp hmule(hp a, hp b) {
  __half2 ar = *reinterpret_cast<__half2*>(&a.r), ai = *reinterpret_cast<__half2*>(&a.i);
  __half2 br = *reinterpret_cast<__half2*>(&b.r), bi = *reinterpret_cast<__half2*>(&b.i);
  __half2 orr = __hfma2(ar, br, __hneg2(__hmul2(ai, bi))), oi = __hfma2(ar, bi, __hmul2(ai, br));
  hp o; o.r = *reinterpret_cast<uint32_t*>(&orr); o.i = *reinterpret_cast<uint32_t*>(&oi); return o;
}
__device__ __forceinline__ void sts_tile(uint32_t a, const hp* t) {
  sts128(a, t[0].r, t[1].r, t[2].r, t[3].r);
  sts128(a + 512, t[0].i, t[1].i, t[2].i, t[3].i);
}
template <int STEP> __device__ __forceinline__ void put2(uint32_t a0, uint32_t a1, uint32_t h, uint32_t sel) {
  const uint32_t x = __byte_perm(h, h, sel), y = x >> 16;
  sts16(a0, x); sts16(a0 + STEP * 4 + 2, x);
  sts16(a1, y); sts16(a1 + STEP * 4 + 2, y);
}

__device__ __forceinline__ void spare_work(const Params& p, const CUtensorMap* tmW1, int k, int tid) {
  const int lane = tid & 31;
  unsigned ep = 0;
  if (tid >= 480) ep = p.scr->epoch[128 + k] + 1;
  if (tid == 480) {
    for (int i = 0; i < 8; i++) mbar_init(bar + 8 * i, i < 4 ? 1 : 12);
    asm volatile("fence.mbarrier_init.release.cluster;" ::: "memory");
    fence_async_smem();
  }
  __syncthreads();
  float a[2][4] = {{0.f, 0.f, 0.f, 0.f}, {0.f, 0.f, 0.f, 0.f}};
  if (tid >= 480) {
    if (elect1()) {
#pragma unroll 1
      for (int s = 0; s < 10; s++) {
        mbar_wait(bar + 8 * (4 + (s & 3)), ((s >> 2) & 1) ^ 1);
        mbar_expect(bar + 8 * (s & 3), 49152);
#pragma unroll 1
        for (int b = 0; b < 2; b++) tma3d(sb + (s & 3) * 49152 + b * 24576, tmW1, 0, s * 64, k * 6 + b * 3, bar + 8 * (s & 3));
      }
    }
    __syncwarp();
  } else if (tid < 384) {
    const uint32_t idn = (lane >> 3) == (lane & 3) ? ((lane & 4) ? 0x3f800000u : 0x3f80u) : 0u;
#pragma unroll 1
    for (int s = 0; s < 10; s++) {
      mbar_wait(bar + 8 * (s & 3), (s >> 2) & 1);
      const uint32_t ad = sb + (s & 3) * 49152 + (tid >> 6) * 8192 + (tid & 63) * 16;
#pragma unroll
      for (int i = 0; i < 8; i += 2) {
        const uint4 v = lds128(ad + i * 1024), w = lds128(ad + i * 1024 + 1024);
        bmma(a[0], v.x, v.y, w.x, w.y, idn, idn);
        bmma(a[1], v.z, v.w, w.z, w.w, idn, idn);
      }
      __syncwarp();
      if (lane == 0) mbar_arrive(bar + 8 * (4 + (s & 3)));
    }
#pragma unroll
    for (int e = 0; e < 8; e++) {
      float v = a[e >> 2][e & 3];
      v += __shfl_xor_sync(0xffffffffu, v, 9);
      v += __shfl_xor_sync(0xffffffffu, v, 18);
      a[e >> 2][e & 3] = v;
    }
    const int odd = (tid >> 5) & 1, c8 = (tid >> 6) * 8 + ((lane & 7) ^ (odd * 4));
    if (odd && lane < 8) {
      sts128(sb + 196608 + c8 * 32, __float_as_uint(a[0][0]), __float_as_uint(a[0][1]), __float_as_uint(a[0][2]), __float_as_uint(a[0][3]));
      sts128(sb + 196608 + c8 * 32 + 16, __float_as_uint(a[1][0]), __float_as_uint(a[1][1]), __float_as_uint(a[1][2]), __float_as_uint(a[1][3]));
    }
    __syncwarp();
    bar_sync(1 + (tid >> 6), 64);
    if (!odd && lane < 8) {
      const uint4 v = lds128(sb + 196608 + c8 * 32), w = lds128(sb + 196608 + c8 * 32 + 16);
      float2* dst = (float2*)(p.scr->cs + k * 384 + (c8 >> 2) * 32) + (c8 & 3);
      dst[0] = make_float2(a[0][0] + __uint_as_float(v.x), a[0][1] + __uint_as_float(v.y));
      dst[4] = make_float2(a[0][2] + __uint_as_float(v.z), a[0][3] + __uint_as_float(v.w));
      dst[8] = make_float2(a[1][0] + __uint_as_float(w.x), a[1][1] + __uint_as_float(w.y));
      dst[12] = make_float2(a[1][2] + __uint_as_float(w.z), a[1][3] + __uint_as_float(w.w));
    }
  }
  __syncthreads();
  if (tid == 480) {
    publish(p.scr->cnt + (C_CS + k) * 32);
    p.scr->epoch[128 + k] = ep;
    poll_cnt(p.scr->cnt + C_LN * 32, ep * 128);
  }
}

__device__ __forceinline__ void load1(int s, const CUtensorMap* tmX, const CUtensorMap* tmW1, int rg1, int j1) {
  const uint32_t d = sb + (s & 3) * SLOT1, mb = bar + 8 * (B_FULL1 + s);
  mbar_expect(mb, SLOT1);
  tma2d(d, tmX, s * 64, rg1 * 128, mb);
  tma3d(d + 16384, tmW1, 0, s * 64, j1 * 3, mb);
}
__device__ __forceinline__ void load_x(uint32_t (&xv)[2][10], const __nv_bfloat16* xa, const __nv_bfloat16* xb, int rstep) {
#pragma unroll
  for (int r = 0; r < 2; r++) {
    const uint4 a = __ldg((const uint4*)(xa + r * rstep)), b = __ldg((const uint4*)(xa + r * rstep + 32));
    const uint2 c = __ldg((const uint2*)(xb + r * rstep + 64));
    xv[r][0] = a.x; xv[r][1] = a.y; xv[r][2] = a.z; xv[r][3] = a.w; xv[r][4] = b.x; xv[r][5] = b.y; xv[r][6] = b.z; xv[r][7] = b.w;
    xv[r][8] = c.x; xv[r][9] = c.y;
  }
}

__device__ __forceinline__ uint32_t pin(uint32_t v, uint32_t z) { uint32_t r; asm volatile("add.u32 %0, %1, %2;" : "=r"(r) : "r"(v), "r"(z)); return r; }
struct Comb { uint32_t o[7]; };
__device__ __forceinline__ Comb comb_setup(int tid, uint32_t z) {
  Comb k;
  const int c = tid & 127, c1 = c < 112 ? c + 32 : c - 112, c2 = c < 112 ? c + 144 : c - 96;
  const uint32_t zr = ZA1 + (c & 7) * 16, a2 = ZA2 + ((c & ~15) - 32 + ((((c >> 1) & 7) + (c & 1) * 8) ^ ((c & 1) * 4))) * 16;
  k.o[0] = uoff(upos(c1)); k.o[1] = uoff(upos(c2));
  k.o[2] = c < 112 ? ZA1 + 512 + ((2 * c) ^ ((c >> 2) & 1)) * 16 : zr;
  k.o[3] = c1 >= 64 ? a2 : zr; k.o[4] = c < 112 ? a2 + 112 * 16 : zr;
  k.o[5] = ((c1 >> 4) * 1280 + (c & 15)) * 16; k.o[6] = ((c2 >> 4) * 1280 + (c & 15)) * 16;
#pragma unroll
  for (int i = 0; i < 7; i++) k.o[i] = pin(k.o[i], z);
  return k;
}
template <class F> __device__ __forceinline__ void combine(const Comb& k, int ch, int wid, uint4* sT, F&& after_reads) {
  const uint32_t ub = sb + OFF_U + ch * 32, zb = sb + OFF_Z + ch * ZSZ;
  const int row = (wid & 15) * 5 + ch;
  char* dst = (char*)(sT + ((wid >> 4) * 16 * 80 + row) * 16);
  mbar_wait(bar + 8 * (B_PART + ch), 0);
  const uint32_t sc = lds32(sb + OFF_CHC + ch * 8);
  const uint4 y0 = lds128(zb + k.o[2]), y1 = lds128(zb + (k.o[2] ^ 16));
  const uint4 v2 = lds128(zb + k.o[3]), u2 = lds128(zb + k.o[4]);
  const uint4 v0 = lds128(ub + k.o[0]), u0 = lds128(ub + k.o[1]);
  fence_async_smem();
  after_reads();
  *(uint4*)(dst + (k.o[5] ^ ((row & 7) * 16))) =
      make_uint4(bmul(badd(badd(y0.x, v2.x), v0.x), sc), bmul(badd(badd(y0.y, v2.y), v0.y), sc),
                 bmul(badd(badd(y1.x, v2.z), v0.z), sc), bmul(badd(badd(y1.y, v2.w), v0.w), sc));
  *(uint4*)(dst + (k.o[6] ^ ((row & 7) * 16))) =
      make_uint4(bmul(badd(badd(y0.z, u2.x), u0.x), sc), bmul(badd(badd(y0.w, u2.y), u0.y), sc),
                 bmul(badd(badd(y1.z, u2.z), u0.z), sc), bmul(badd(badd(y1.w, u2.w), u0.w), sc));
  __syncwarp();
  if (elect1()) mbar_arrive(bar + 8 * (B_FREE + ch));
}

__device__ __forceinline__ void load2(int s, uint32_t d, const uint4* srcA, const uint4* srcB) {
  const uint32_t mb = bar + 8 * (B_FULL2 + s);
  mbar_expect(mb, SLOT2);
  bulk_g2s(d, srcA, 16384, mb);
  bulk_g2s(d + 16384, srcB, 10240, mb);
}

template <bool USE_SMID>
__global__ void __launch_bounds__(512, 1)
fused_s4_ffn_kernel(const Params p, const __grid_constant__ CUtensorMap tmX, const __grid_constant__ CUtensorMap tmW1,
                    const __grid_constant__ CUtensorMap tmU, const __grid_constant__ CUtensorMap tmW2) {
  extern __shared__ __align__(1024) unsigned char smem_raw[];
  const int tid = threadIdx.x, lane = tid & 31;
  uint32_t sid;
  if (USE_SMID) asm("mov.u32 %0, %smid;" : "=r"(sid)); else sid = blockIdx.x;
  const int wid = sid < 120 ? sid : sid - 4;
  uint32_t pa[6], pld, pds;
  const unsigned pw = min(tid >> 5, 14), part = (pw * 13) >> 6;
  const unsigned ch = (wid >> 4) * 80 + frag_col(((wid & 15) - part) * 5 + pw);
  const unsigned o = (ch * 3 + part) * 32 + lane;
  {
    asm volatile("{\n.reg .pred p;\nsetp.lt.u32 p, %0, 256;\n@p nanosleep.u32 %1;\n}" ::"r"(tid), "n"(LDLY));
    pld = ldg16(p.logdt + ch);
    pa[0] = ldg32((const uint32_t*)p.are + o); pa[1] = ldg32((const uint32_t*)p.aim + o);
    pds = ldg16(p.dskip + ch);
    pa[2] = ldg32((const uint32_t*)p.bre + o); pa[3] = ldg32((const uint32_t*)p.bim + o);
    pa[4] = ldg32((const uint32_t*)p.cre + o); pa[5] = ldg32((const uint32_t*)p.cim + o);
  }
  const int warp = __shfl_sync(0xffffffffu, tid >> 5, 0);
  const int g = lane >> 2, q = lane & 3;
  if (sid - 120u < 4u) { spare_work(p, &tmW1, sid - 120, tid); return; }
  unsigned* const cnt = p.scr->cnt;

  float kacc[6][4];
  const int kch = warp - 10;
  float dt, k0;
  uint32_t xv[2][10], xs[2], mw;
  {
    unsigned ep0;
    if (warp == 15) {
      ep0 = p.scr->epoch[wid];
      if ((uint32_t)__cvta_generic_to_shared(smem_raw) != sb) __trap();
    }
    if (elect1()) {
      const int gi = (warp + 1) & 15;
#pragma unroll
      for (int i = 0; i < 6; i++) mbar_init(bar + 48 * gi + 8 * i, gi < 7 ? 1 : gi == 7 ? 2 : gi < 10 ? 4 : 8);
      asm volatile("fence.mbarrier_init.release.cluster;" ::: "memory");
    }
    const uint32_t z0 = sid >> 8;
#pragma unroll
    for (int j = 0; j < 24; j++) kacc[j >> 2][j & 3] = __uint_as_float(pin(z0, z0));
    const uint32_t ks = sb + OFF_KS + warp * 4096;
    const uint32_t st = pin(ks + lane * 16, z0);
    const uint32_t kw = pin(ks + 3584 + (lane >> 1) * 8 + (lane & 1) * 2, z0), kr = pin(ks + 3584 + q * 8, z0);
    const uint32_t kb = pin(ks + ((lane >> 3) & 1) * 512 + ((lane >> 4) * 8 + (lane & 7)) * 16, z0);
    const __nv_bfloat16* xr = p.x + (wid * 16 + ((g >> 1) << 2) + (g & 1)) * DM;
    const __nv_bfloat16 *xa = xr + (warp & 7) * 80 + q * 8, *xb = xr + (warp & 7) * 80 + q * 4;
    xr += q * 2;
    asm volatile("add.u64 %0, %0, %2;\nadd.u64 %1, %1, %2;" : "+l"(xa), "+l"(xb) : "l"((uint64_t)z0));
    if (warp < 8) bar_sync(14, 512); else bar_arrive(14, 512);
    if (warp == 15) {
      sts32(sb + OFF_ZERO + lane * 4, 0);
      int gpc, i;
      if (sid < 64) { gpc = (sid & 15) >> 1; i = sid >> 4; }
      else if (sid < 120) { const int t = sid - 64; i = t / 14; gpc = 1 + ((t - i * 14) >> 1); i += 4; }
      else { gpc = 0; i = 4 + ((sid - 124) >> 1); }
      const int qi = ((0x52741630 >> (4 * i)) & 7) * 2 + (sid & 1);
      const int blk = (0x51674230 >> (4 * gpc)) & 7;
      const int rg = 4 * (blk >> 1) + (qi >> 3) * 2 + (qi & 1), jc = 4 * (blk & 1) + ((qi >> 1) & 3);
      sts64(sb + OFF_EP + 8, rg, jc);
      __syncwarp();
      if (elect1()) {
        asm volatile("prefetch.tensormap [%0];\nprefetch.tensormap [%1];\nprefetch.tensormap [%2];\nprefetch.tensormap [%3];" ::"l"(&tmW2), "l"(&tmX), "l"(&tmW1), "l"(&tmU) : "memory");
        __nanosleep(XDLY);
        bulk_prefetch(p.x + wid * 16 * DM, 16 * DM * 2);
        mbar_expect(bar + 8 * B_W2, 96 * 176);
      }
      __syncwarp();
      load_x(xv, xa, xb, 2 * DM);
      xs[0] = __ldg((const uint32_t*)xr); xs[1] = __ldg((const uint32_t*)(xr + 2 * DM));
      bar_sync(5, 256);
      sts32(sb + OFF_EP + 4, xv[1][9]);
      if (elect1()) {
        tma5d(sb + OFF_W2S, &tmW2, (wid & 7) * 80, (wid >> 3) * 3, bar + 8 * B_W2);
        p.scr->epoch[wid] = ep0 + 1;
        sts32(sb + OFF_EP, ep0 + 1);
      }
      __syncwarp();
#pragma unroll
      for (int r = 0; r < 2; r++) {
        const uint32_t w0 = __shfl_sync(0xffffffffu, xs[r], lane & 28);
        const float x0 = bflo(w0);
        const unsigned far = __ballot_sync(0xffffffffu, fmaxf(fabsf(bflo(xs[r]) - x0), fabsf(bfhi(xs[r]) - x0)) * 16.f >= fabsf(x0));
        xs[r] = ((far >> (lane & 28)) & 15) ? 0u : __byte_perm(w0, 0, 0x1010);
      }
      sts64(sb + OFF_SH + g * 8, xs[0], xs[1]);
      bar_arrive(3, 256);
    }
    float zr, th, zr1, th1;
    cf c, c1;
    dt = rnd_bf(expf(bflo(pld)));
    {
      const float dl2 = dt * 1.4426950408889634f;
      zr = bflo(pa[0]) * dl2; th = bflo(pa[1]) * dt; zr1 = bfhi(pa[0]) * dl2; th1 = bfhi(pa[1]) * dt;
    }
    if (warp < 15) {
      c = cmul(cf{bflo(pa[4]), bflo(pa[5])}, cf{bflo(pa[2]), bflo(pa[3])});
      c1 = cmul(cf{bfhi(pa[4]), bfhi(pa[5])}, cf{bfhi(pa[2]), bfhi(pa[3])});
      mw = __reduce_max_sync(0xffffffffu, __float_as_uint(fmaxf(fmaxf(fabsf(c.r), fabsf(c.i)), fmaxf(fabsf(c1.r), fabsf(c1.i)))));
      mw = min(max(mw & 0x7f800000u, 20u << 23), 240u << 23);
      const float sc = __uint_as_float((259u << 23) - mw);
      k0 = c.r + c1.r;
      c.r *= sc; c.i *= -sc; c1.r *= sc; c1.i *= -sc;
      if (warp >= 8) {
        load_x(xv, xa, xb, 2 * DM);
        bar_arrive(5, 256);
      }
    }
    {
#pragma unroll 1
      for (int it = 0; it < 2; it++) {
        if (it == 1 && warp >= 8) {
          float sm[4] = {0.f, 0.f, 0.f, 0.f}, g0[4] = {0.f, 0.f, 0.f, 0.f}, g1[4] = {0.f, 0.f, 0.f, 0.f};
          if (warp < 15) bar_sync(3, 256);
          { const uint2 v = lds64(sb + OFF_SH + g * 8); xs[0] = v.x; xs[1] = v.y; }
#pragma unroll
          for (int i = 0; i < 10; i += 2) {
            const uint32_t a0 = bsub(xv[0][i], xs[0]), a1 = bsub(xv[1][i], xs[1]), a2 = bsub(xv[0][i + 1], xs[0]), a3 = bsub(xv[1][i + 1], xs[1]);
            bmma(sm, a0, a1, a2, a3, 0x3f803f80u, 0x3f803f80u);
            bmma(g0, a0, a1, a2, a3, xv[0][i], xv[0][i + 1]);
            bmma(g1, a0, a1, a2, a3, xv[1][i], xv[1][i + 1]);
          }
          if (q == (g >> 1))
            sts128(sb + OFF_LNP + (warp - 8) * 128 + g * 16, __float_as_uint(sm[0]), __float_as_uint((g & 1) ? g0[1] : g0[0]),
                   __float_as_uint(sm[2]), __float_as_uint((g & 1) ? g1[3] : g1[2]));
          __syncwarp();
          if (warp != 11) bar_arrive(1, 256);
        }
        if (warp == 15) continue;
        float m = ex2a(zr);
        const cf w1 = cf{m * __cosf(th), m * __sinf(th)};
        m = ex2a(zr * 8.f);
        const cf w8 = cf{m * __cosf(th * 8.f), m * __sinf(th * 8.f)};
        const cf w16 = csq(w8), w32 = csq(w16), w64 = csq(w32), w128 = csq(w64), w256 = csq(w128), w512 = csq(w256), w1024 = csq(w512);
        hp lo[4];
        lo[0] = hpack(cf{1.f, 0.f}, w8);
        lo[1] = hmulc(lo[0], pack_h(w16.r, w16.i));
        { const uint32_t k = pack_h(w32.r, w32.i); lo[2] = hmulc(lo[0], k); lo[3] = hmulc(lo[1], k); }
        sts_tile(st, lo);
        { const uint32_t k = pack_h(w64.r, w64.i); sts16(kw, k); sts16(kw + 4, k >> 16); }
        const uint32_t k256 = pack_h(w256.r, w256.i), k512 = pack_h(w512.r, w512.i);
        const cf t8 = cmulj(c, w8);
        { const cf u0 = cmulj(t8, w1024), u1 = cmulj(u0, w256);
          const hp a = hpack(u0, u1), b = hmulj(a, k512);
          sts128(st + 3072, a.r, b.r, a.i, b.i); }
        const cf t1 = cmulj(c, w1), t2 = cmulj(t1, w1), t3 = cmulj(t2, w1), t4 = cmulj(t3, w1);
        const cf t5 = cmulj(t4, w1), t6 = cmulj(t5, w1), t7 = cmulj(t6, w1);
        hp T0[4], T1[4];
        T0[0] = hpack(t4, t8); T0[1] = hpack(t2, t6); T0[2] = hpack(t1, t5); T0[3] = hpack(t3, t7);
        T1[0] = hmulj(T0[0], k256); T1[1] = hmulj(T0[1], k256); T1[2] = hmulj(T0[0], k512); T1[3] = hmulj(T1[0], k512);
        sts_tile(st + 2048, T1);
        sts_tile(st + 1024, T0);
        __syncwarp();
        uint32_t bc[4];
        ldsm4t(bc, st + 3072);
#pragma unroll
        for (int m2 = 0; m2 < 4; m2 += 2) {
          uint32_t l0[4], b0[4], b1[4];
          ldsm4t(l0, kb + m2 * 128);
          ldsm4t(b0, kb + 1024 + m2 * 128);
          ldsm4t(b1, kb + 2048 + m2 * 128);
#pragma unroll
          for (int i = 0; i < 2; i++) {
            const uint2 kv = lds64(kr + (m2 + i) * 32);
            const hp k64 = {kv.x, kv.y}, L0 = {l0[2 * i], l0[2 * i + 1]};
            const hp L1 = hmule(L0, k64), L2 = hmule(L1, k64), L3 = hmule(L2, k64);
            const uint32_t c0 = lane < 16 ? bc[m2 + i] : 0u, c1b = lane < 16 ? 0u : bc[m2 + i];
            const uint32_t a0 = pin(L0.r, z0), a2 = pin(L0.i, z0);
            hmma(kacc[0], a0, L1.r, a2, L1.i, b0[2 * i], b0[2 * i + 1]);
            hmma(kacc[2], a0, L1.r, a2, L1.i, b1[2 * i], b1[2 * i + 1]);
            hmma(kacc[4], a0, L1.r, a2, L1.i, c0, c1b);
            hmma(kacc[1], L2.r, L3.r, L2.i, L3.i, b0[2 * i], b0[2 * i + 1]);
            hmma(kacc[3], L2.r, L3.r, L2.i, L3.i, b1[2 * i], b1[2 * i + 1]);
            hmma(kacc[5], L2.r, L3.r, L2.i, L3.i, c0, c1b);
          }
        }
        __syncwarp();
        zr = zr1; th = th1; c = c1;
      }
    }
    if (warp >= 8) bar_arrive(6, 512);
    if (warp < 10) {
#pragma unroll
      for (int j = 0; j < 6; j++)
        sts128(st + j * 512, __float_as_uint(kacc[j][0]), __float_as_uint(kacc[j][1]), __float_as_uint(kacc[j][2]), __float_as_uint(kacc[j][3]));
      sts64(ks + 3072 + lane * 8, __float_as_uint(k0), mw);
    }
    if (warp == 11) {
      bar_sync(1, 256);
      float s1 = 0.f, s2 = 0.f;
#pragma unroll
      for (int w = 0; w < 8; w++) {
        const uint2 v = lds64(sb + OFF_LNP + w * 128 + g * 16 + (q & 1) * 8);
        s1 += __uint_as_float(v.x); s2 += __uint_as_float(v.y);
      }
      const float md0 = s1 * (1.f / DM), md = fmaf(fmaf(md0, -(float)DM, s1), 1.f / DM, md0), mean = bflo((q & 1) ? xs[1] : xs[0]) + md;
      const float var = fmaxf(fmaf(-md, mean, s2 * (1.f / DM)), 0.f);
      const float m = rnd_bf(mean);
      float sd, ri;
      asm("sqrt.approx.f32 %0, %1;" : "=f"(sd) : "f"(rnd_bf(rnd_bf(var) + 1e-5f)));
      asm("rcp.approx.f32 %0, %1;" : "=f"(ri) : "f"(rnd_bf(sd)));
      if (q < 2) {
        p.scr->stats[wid * 16 + ((g >> 1) << 2) + (g & 1) + 2 * q] = make_float2(-m, 0.5f * ri);
        sts64(sb + OFF_STAT + g * 16 + q * 8, __float_as_uint(-m * ri), __float_as_uint(ri));
      }
      __syncwarp();
    }
    if (warp == 15) {
      const uint2 rj = lds64(sb + OFF_EP + 8);
      mbar_wait(bar + 8 * B_W2, 0);
#pragma unroll 1
      for (int uu = 0; uu < 3; uu++) {
        if (elect1()) load1(uu, &tmX, &tmW1, rj.x, rj.y);
        const uint32_t a = sb + OFF_W2S + (uu * 32 + lane) * 176;
        const int rem = ((wid >> 3) & 1) * 3 + uu;
        uint4* dst = p.scr->w2p + ((wid & 7) * 24 + 8 * (rem >> 1) + (wid >> 4)) * 640 + ((rem & 1) * 4 + (lane >> 3)) * 80 + (lane & 7);
        uint4 v[10];
#pragma unroll
        for (int i = 0; i < 10; i++) v[i] = lds128(a + i * 16);
#pragma unroll
        for (int i = 0; i < 8; i++)
          dst[8 * i] = make_uint4(bmul((&v[i & 4].x)[i & 3], 0x3f003f00u), bmul((&v[(i & 4) + 1].x)[i & 3], 0x3f003f00u),
                                  bmul((&v[(i & 4) + 2].x)[i & 3], 0x3f003f00u), bmul((&v[(i & 4) + 3].x)[i & 3], 0x3f003f00u));
        dst[64] = make_uint4(bmul(v[8].x, 0x3f003f00u), bmul(v[8].z, 0x3f003f00u), bmul(v[9].x, 0x3f003f00u), bmul(v[9].z, 0x3f003f00u));
        dst[72] = make_uint4(bmul(v[8].y, 0x3f003f00u), bmul(v[8].w, 0x3f003f00u), bmul(v[9].y, 0x3f003f00u), bmul(v[9].w, 0x3f003f00u));
      }
      fence_async_smem();
      __syncwarp();
      if (elect1()) load1(3, &tmX, &tmW1, rj.x, rj.y);
      __syncwarp();
    }
  }

  if (warp < 8) {
    float acc[96];
    const uint32_t alo = ((sb >> 4) | (1 << 16)) + (warp >> 2) * 512;
    bar_arrive(0, 512);
    bar_sync(6, 512);
#pragma unroll 1
    for (int s = 0; s < 10; s++) {
      const uint32_t so = (s & 3) * (SLOT1 >> 4);
      mbar_wait(bar + 8 * (B_FULL1 + s), 0);
      wg_fence();
#pragma unroll
      for (int kk = 0; kk < 4; kk++)
        wgmma_n192(acc, dsc(alo + so + kk * 2, 0x40000040u), dsc((((sb + 16384) >> 4) | (512 << 16)) + so + kk * 128, 0x40000040u), (s | kk) != 0);
      wg_commit();
      wg_wait<1>();
      if (lane == 0) mbar_arrive(bar + 8 * (B_REL1 + s));
      if (s == 1 && warp == 7) {
        mbar_wait(bar + 8 * (B_REL1 + 1), 0);
        if (elect1()) { const uint2 rj = lds64(sb + OFF_EP + 8); load1(4, &tmX, &tmW1, rj.x, rj.y); }
        __syncwarp();
      }
    }
    wg_wait<0>();
    bar_arrive(14, 384);
    bar_arrive(7, 384);
    mbar_wait(bar + 8 * B_EPI, 0);
    const uint2 s0 = lds64(sb + OFF_STAT + (warp * 16 + g) * 8), s1 = lds64(sb + OFF_STAT + (warp * 16 + g + 8) * 8);
    const float nm0 = __uint_as_float(s0.x), r0 = __uint_as_float(s0.y), nm1 = __uint_as_float(s1.x), r1 = __uint_as_float(s1.y);
    const uint4 erj = lds128(sb + OFF_EP);
    const unsigned ep = erj.x;
    const int rg1 = erj.z, j1 = erj.w;
    uint4* hd = p.scr->h + (rg1 * 24 + j1) * 1024 + warp * 128 + g * 4 + (q ^ (g >> 1));
#pragma unroll
    for (int grp = 0; grp < 6; grp++) {
      uint32_t o0[4], o1[4];
      const uint4 cs[2] = {lds128(sb + OFF_CS + grp * 128 + q * 32), lds128(sb + OFF_CS + grp * 128 + q * 32 + 16)};
#pragma unroll
      for (int tl = 0; tl < 4; tl++) {
        const int nt = grp * 4 + tl;
        const float ca = __uint_as_float((&cs[tl >> 1].x)[(tl & 1) * 2]), cb = __uint_as_float((&cs[tl >> 1].x)[(tl & 1) * 2 + 1]);
        const float a = fmaf(nm0, ca, acc[4 * nt]) * r0, b = fmaf(nm0, cb, acc[4 * nt + 1]) * r0;
        const float c = fmaf(nm1, ca, acc[4 * nt + 2]) * r1, d = fmaf(nm1, cb, acc[4 * nt + 3]) * r1;
        o0[tl] = pack_bf(fmaf(a, tanha(a), a), fmaf(b, tanha(b), b));
        o1[tl] = pack_bf(fmaf(c, tanha(c), c), fmaf(d, tanha(d), d));
      }
      uint4* dst = hd + (grp >> 1) * 8192 + (grp & 1) * 32;
      dst[0] = make_uint4(o0[0], o0[1], o0[2], o0[3]);
      dst[64] = make_uint4(o1[0], o1[1], o1[2], o1[3]);
      if (grp < 5) __nanosleep(PACE);
    }
    if (warp == 7) { bar_sync(11, 256); if (lane == 0) publish(cnt + (C_H + rg1) * 32); __syncwarp(); }
    else bar_arrive(11, 256);
    const int go = (rg1 * 128 + warp * 16 + g) * DM + j1 * 80;
    load_x(xv, p.x + go + q * 8, p.x + go + q * 4, 8 * DM);
    if (warp < 4) {
      mbar_wait(bar + 8 * B_PART, 0);
      Comb cmb;
      {
        const uint4 a = lds128(sb + OFF_CMB + tid * 16);
        const uint2 b = lds64(sb + OFF_CMB + 2048 + tid * 8);
        cmb.o[0] = a.x; cmb.o[1] = a.y; cmb.o[2] = a.z; cmb.o[3] = a.w; cmb.o[4] = b.x; cmb.o[5] = b.y;
        cmb.o[6] = lds32(sb + OFF_CMB + 3072 + tid * 4);
      }
#pragma unroll 1
      for (int ch = 0; ch < 3; ch++) {
        combine(cmb, ch, wid, p.scr->sT, [] {});
      }
    } else if (warp == 4) {
      if (elect1()) {
        const uint4* srcA = p.scr->h + rg1 * 24 * 1024;
        const uint4* srcB = p.scr->w2p + j1 * 24 * 640;
        asm volatile("fence.proxy.async.global;" ::: "memory");
        mbar_wait(bar + 8 * B_PART, 0);
#pragma unroll
        for (int s = 0; s < 3; s++) {
          mbar_expect(bar + 8 * (B_FULL2 + s), SLOT2);
          bulk_g2s(sb + s * SLOT2 + 16384, srcB + s * 640, 10240, bar + 8 * (B_FULL2 + s));
        }
        poll_cnt(cnt + (C_H + rg1) * 32, ep * 8);
#pragma unroll
        for (int s = 0; s < 3; s++) bulk_g2s(sb + s * SLOT2, srcA + s * 1024, 16384, bar + 8 * (B_FULL2 + s));
#pragma unroll
        for (int s = 3; s < 5; s++) {
          mbar_wait(bar + 8 * (B_FREE + s - 2), 0);
          load2(s, sb + s * SLOT2, srcA + s * 1024, srcB + s * 640);
        }
      }
      __syncwarp();
    }
    float acc2[40];
    bar_sync(8, 512);
    {
      const uint32_t al2 = ((sb >> 4) | (1 << 16)) + (warp >> 2) * 512;
      uint32_t so = 0;
#pragma unroll 1
      for (int s = 0; s < 24; s++) {
        mbar_wait(bar + 8 * (B_FULL2 + s), 0);
        if (s == SK2 && warp < 4) bar_sync(4, 256);
        wg_fence();
#pragma unroll
        for (int kk = 0; kk < 4; kk++)
          wgmma_n80(acc2, dsc(al2 + so + (kk >> 1) * 32 + (kk & 1) * 2, 0x80000040u), dsc((((sb + 16384) >> 4) | (80 << 16)) + so + kk * 160, 8), (s | kk) != 0);
        wg_commit();
        so = so == (NS2 - 1) * (SLOT2 >> 4) ? 0 : so + (SLOT2 >> 4);
        if (s < SK2 - 1) {
          wg_wait<1>();
          if (lane == 0) mbar_arrive(bar + 8 * (B_REL2 + s));
        }
      }
      if (warp >= 4) { wg_wait<1>(); bar_arrive(4, 256); }
    }
    mbar_wait(bar + 8 * B_SFULL, 0);
    uint32_t sv[5][4];
    {
      const int i = lane & 7, mi = lane >> 3;
      const uint32_t a = sb + OFF_U + ((mi >> 1) * 8 + i) * 256 + (((2 * warp + (mi & 1)) ^ i) << 4);
#pragma unroll
      for (int k = 0; k < 5; k++) ldsm4t(sv[k], a + k * 4096);
    }
    wg_wait<0>();
#pragma unroll
    for (int hh = 0; hh < 2; hh++) {
      uint32_t o[10];
      __nv_bfloat16* op = p.out + go + hh * 8 * DM;
#pragma unroll
      for (int tl = 0; tl < 10; tl++) {
        const float a = acc2[4 * tl + 2 * hh], b = acc2[4 * tl + 2 * hh + 1];
        o[tl] = bfma(sv[tl >> 1][(tl & 1) * 2 + hh], pack_bf(fmaf(a, tanhv(a), a), fmaf(b, tanhv(b), b)), xv[hh][tl]);
        if ((tl & 3) == 3)
          asm volatile("st.global.v4.u32 [%0], {%1, %2, %3, %4};" ::"l"((uint4*)op + (tl >> 2) * 4 + q), "r"(o[tl - 3]), "r"(o[tl - 2]), "r"(o[tl - 1]), "r"(o[tl]) : "memory");
      }
      asm volatile("st.global.v2.u32 [%0], {%1, %2};" ::"l"((uint2*)(op + 64) + q), "r"(o[8]), "r"(o[9]) : "memory");
    }
  } else {
    const int cw = warp - 8;
    bar_sync(0, 512);
    const uint4 erj = lds128(sb + OFF_EP);
    const unsigned ep = erj.x;
    const int rg1 = erj.z, j1 = erj.w;
    {
      const uint4 st = lds128(sb + OFF_STAT + g * 16);
      const float n0 = __uint_as_float(st.x), r0 = __uint_as_float(st.y), n1 = __uint_as_float(st.z), r1 = __uint_as_float(st.w);
      const int up = upos(2 * wid);
      uint2* dst = (uint2*)p.scr->uT + ((up >> 1) * DM + cw * 80) * 4 + (lane ^ ((up & 1) << 1));
#pragma unroll
      for (int i = 0; i < 10; i++) {
        const uint32_t a = movm(pack_h(fmaf(bflo(xv[0][i]), r0, n0), fmaf(bfhi(xv[0][i]), r0, n0)));
        const uint32_t b = movm(pack_h(fmaf(bflo(xv[1][i]), r1, n1), fmaf(bfhi(xv[1][i]), r1, n1)));
        dst[i * 32] = make_uint2(a, b);
      }
    }
    if (warp == 8) {
      bar_sync(12, 256);
      if (lane == 0) publish(cnt + C_LN * 32);
      __syncwarp();
    } else bar_arrive(12, 256);
    if (warp == 15) {
      if (elect1()) {
#pragma unroll 1
        for (int s = 5; s < 10; s++) {
          mbar_wait(bar + 8 * (B_REL1 + s - 3), 0);
          load1(s, &tmX, &tmW1, rg1, j1);
        }
        poll_cnt(cnt + (C_CS + (j1 >> 1)) * 32, ep);
        bulk_g2s(sb + OFF_CS, p.scr->cs + j1 * 192, 768, bar + 8 * B_EPI);
      }
      __syncwarp();
    }
    if (warp >= 10 && warp < 15) {
      const uint32_t pb = sb + OFF_P + kch * 3072, pk = sb + OFF_KS + kch * 4096;
      const uint2 e0 = lds64(pk + 3072 + lane * 8), e1 = lds64(pk + 5 * 4096 + 3072 + lane * 8);
      const float dsk = bflo(pds);
      uint32_t kex = __float_as_uint(fmaxf(__uint_as_float(max(max(e0.y, e1.y), mw)) * dt, fabsf(dsk) * (1.f / 256.f))) >> 23;
      kex = min(max(kex, 20u), 240u);
      const float s2 = __uint_as_float((258 - kex) << 23), sd = s2 * dt * (1.f / 32.f);
      const float f0 = __uint_as_float(e0.y) * sd, f1 = __uint_as_float(e1.y) * sd, f2 = __uint_as_float(mw) * sd;
      k0 += __uint_as_float(e0.x) + __uint_as_float(e1.x);
#pragma unroll
      for (int o = 16; o; o >>= 1) k0 += __shfl_xor_sync(0xffffffffu, k0, o);
      const float k0n = fmaf(k0, dt, dsk) * s2;
      uint32_t h[5][2];
#pragma unroll
      for (int j = 0; j < 6; j++) {
        const uint4 a = lds128(pk + j * 512 + lane * 16), b = lds128(pk + 5 * 4096 + j * 512 + lane * 16);
#pragma unroll
        for (int e = 0; e < 4; e++) kacc[j][e] = fmaf(__uint_as_float((&a.x)[e]), f0, fmaf(__uint_as_float((&b.x)[e]), f1, kacc[j][e] * f2));
        if (j == 1) {
          const float k256 = __shfl_sync(0xffffffffu, kacc[1][3], 28);
          if (lane == 31) kacc[1][3] -= k256;
        }
        if (j == 2 || j == 3) { h[j][0] = pack_h(kacc[j][0], kacc[j][2]); h[j][1] = pack_h(kacc[j][1], kacc[j][3]); }
        else if (j < 2) { h[j][0] = pack_h(kacc[j][0], kacc[j][1]); h[j][1] = pack_h(kacc[j][2], kacc[j][3]); }
      }
      {
        const bool sw = q >> 1;
        float v[4];
#pragma unroll
        for (int e = 0; e < 4; e++) v[e] = (sw ? kacc[5][e] : kacc[4][e]) + __shfl_xor_sync(0xffffffffu, sw ? kacc[4][e] : kacc[5][e], 2);
        h[4][0] = pack_h(v[0], v[1]); h[4][1] = pack_h(v[2], v[3]);
#pragma unroll
        for (int e = 0; e < 2; e++) {
          const uint32_t r = __shfl_xor_sync(0xffffffffu, sw ? h[2][e] : h[3][e], 2);
          if (sw) h[2][e] = r; else h[3][e] = r;
        }
      }
      fence_async_smem();
      bar_arrive(13, 192);
#pragma unroll
      for (int i = 0; i < 6; i++) sts128(pb + i * 512 + lane * 16, 0, 0, 0, 0);
      __syncwarp();
      {
        const int sw = g >> 2;
        const uint32_t sel = sw ? 0x1032 : 0x3210;
        const uint32_t a = pb + (P0 + 8 * g + ((0x3124 >> (4 * q)) & 7)) * 4, a0 = a + sw * 16, a1 = a + 16 - sw * 16;
        put2<1>(a0, a1, h[0][0], sel);
        put2<1>(a0 + 256, a1 + 256, h[0][1], sel);
        put2<1>(a0 + 512, a1 + 512, h[1][0], sel);
        put2<1>(lane == 28 ? pb + PB1 * 4 : a0 + 768, a1 + 768, h[1][1], sel);
      }
      {
        const int sw = q >> 1;
        const uint32_t sel = sw ? 0x1032 : 0x3210;
        uint32_t a = pb + (((q & 1) ? PA1 : PB1 + 1) + 32 * sw + 2 * g) * 4;
        put2<1>(a + sw * 64, a + 64 - sw * 64, h[2][0], sel);
        put2<1>(a + 4 + sw * 64, a + 68 - sw * 64, h[2][1], sel);
        const int s1 = q & 1;
        const uint32_t sel1 = s1 ? 0x1032 : 0x3210;
        a = pb + (PA2 + g + 16 * sw + 32 * s1) * 4;
        put2<1>(a + s1 * 32, a + 32 - s1 * 32, h[3][0], sel1);
        put2<1>(a + (PB2 - PA2) * 4 + s1 * 32, a + (PB2 - PA2) * 4 + 32 - s1 * 32, h[3][1], sel1);
        a = pb + (((g & 1) ? PB3 : PA3) + (g >> 1) + 8 * sw + 32 * s1) * 4;
        const uint32_t hx = s1 ? h[4][1] : h[4][0], hy = s1 ? h[4][0] : h[4][1];
        put2<1>(a + s1 * 16, a + 64 + s1 * 16, hx, 0x3210);
        put2<1>(a + 16 - s1 * 16, a + 80 - s1 * 16, hy, 0x3210);
      }
      if (lane == 30) put2<1>(pb + P0 * 4, pb + (PA1 + 64) * 4, __byte_perm(pack_h(k0n, 0.f), h[2][1], 0x7610), 0x3210);
      if (lane == 31) sts64(sb + OFF_CHC + kch * 8, (kex - 4) * 0x00800080u, __byte_perm(h[3][1], 0, 0x3232));
    }
    if (warp == 8) {
      bar_sync(13, 192);
      if (elect1()) {
        mbar_expect(bar + 8 * B_UFULL, 144 * 160);
        mbar_expect(bar + 8 * B_EPI, 1024 + 768);
        poll_cnt(cnt + C_LN * 32, ep * 128);
        tma2d(sb + OFF_U - 16 * 160, &tmU, wid * 80, -16, bar + 8 * B_UFULL);
        bulk_g2s(sb + OFF_STAT, p.scr->stats + rg1 * 128, 1024, bar + 8 * B_EPI);
      }
      __syncwarp();
    }
    const int wg = warp >> 2, role = (warp + 2 * wg) & 3;
    uint32_t co[6], cpa = (g - 2 * q) * 4;
    if (role < 2) {
#pragma unroll
      for (int gm = 0; gm < 3; gm++) {
        const int hb = 2 * (lane & 7) + role - 2 + gm, l3 = ((lane >> 3) ^ (hb >> 1)) & 7;
        co[2 * gm] = hb * 1280 + uoff(l3); co[2 * gm + 1] = hb * 1280 + uoff(l3 ^ 4);
      }
    } else {
      const int mi = lane >> 3, hf = (lane >> 2) & 1;
      co[0] = hf * 1792 + (mi ^ hf) * 64 + ((q ^ (mi >> 1) ^ (hf * 2)) << 4);
      co[1] = co[0] ^ 96;
      const int i = lane & 7;
      if (role == 3) co[0] = (16 * (mi >> 1) + ((4 * (mi & 1) + (i >> 1) + 8 * (i & 1)) ^ (4 * (i & 1)))) << 4;
      co[2] = (role == 2 ? (16 * (mi >> 1) + 2 * i + (mi & 1)) ^ (i >> 2) : lane ^ ((lane >> 1) & 4)) << 4;
      co[3] = lane * 16;
      co[4] = (g >> 1) == q ? ((g & 1) ? 0xffff0000u : 0xffffu) : 0u;
      co[5] = (g - q) * 8;
    }
    const uint32_t zero = lds32(sb + OFF_ZERO), nz = zero | 0x80000000u;
#pragma unroll
    for (int i = 0; i < 6; i++) co[i] = pin(co[i], zero);
    cpa = pin(cpa, zero);
    const Comb cmb = comb_setup(tid, zero);
    if (warp >= 10 && warp < 15) bar_sync(15, 160);
    const int qt = (0x3120 >> (4 * (cw & 3))) & 3, jz = qt * 32 + lane;
    uint32_t zo[13];
    {
      const int j = jz < 112 ? jz : jz - 128, gr = j >> 1;
      zo[0] = uoff(upos(max(2 * j - 2, -32))); zo[1] = zo[0] ^ 16; zo[2] = uoff(upos(2 * j)); zo[3] = zo[2] ^ 16; zo[4] = uoff(upos(2 * j + 2));
#pragma unroll
      for (int pp = 0; pp < 4; pp++) zo[5 + pp] = ZA1 + 512 + (gr ^ ((gr >> 2) & 1)) * 64 + ((((gr >> 1) & 3) ^ pp) << 4) + (j & 1) * 8;
      zo[9] = ((j >> 3) * 16 + (j & 7)) * 16;
      zo[10] = ((j >> 4) * 32 + (j & 15)) * 16;
      zo[11] = zo[10] + ((j & 15) == 15 ? 272 : 16);
      zo[12] = (zo[9] ^ 64) + 128;
#pragma unroll
      for (int i = 0; i < 13; i++) zo[i] = pin(zo[i], zero);
    }
    if (warp < 12) {
      mbar_wait(bar + 8 * (B_REL1 + 7), 0);
      sts128(sb + OFF_CMB + (tid - 256) * 16, cmb.o[0], cmb.o[1], cmb.o[2], cmb.o[3]);
      sts64(sb + OFF_CMB + 2048 + (tid - 256) * 8, cmb.o[4], cmb.o[5]);
      sts32(sb + OFF_CMB + 3072 + (tid - 256) * 4, cmb.o[6]);
    }
    mbar_wait(bar + 8 * B_UFULL, 0);
#pragma unroll 1
    for (unsigned seq = (cw >> 2) ? 0xb9ac : 0x8; seq; seq >>= 4) {
      const int ch = seq & 7;
      if (ch == 1) bar_arrive(0, 256);
      if (ch == 2) mbar_wait(bar + 8 * (B_REL1 + 8), 0);
      const uint32_t ub = sb + OFF_U + ch * 32, zb = sb + OFF_Z + ch * ZSZ;
      uint32_t w_[20], o_[20], d_[20], b3_[20];
      uint32_t *w = w_ + 8, *o = o_ + 8, *d = d_ + 8, *b3 = b3_ + 8;
      {
        const uint4 c = lds128(ub + zo[2]), e = lds128(ub + zo[3]), b = lds128(ub + zo[1]);
        w[8] = lds32(ub + zo[4]);
        const uint2 a = lds64(ub + zo[0] + 8);
        w[-6] = a.x; w[-5] = a.y; w[-4] = b.x; w[-3] = b.y; w[-2] = b.z; w[-1] = b.w;
        w[0] = c.x; w[1] = c.y; w[2] = c.z; w[3] = c.w; w[4] = e.x; w[5] = e.y; w[6] = e.z; w[7] = e.w;
      }
#pragma unroll
      for (int i = -1; i <= 7; i++) o[i] = odd_pair(w[i], w[i + 1]);
#pragma unroll
      for (int i = 0; i <= 7; i++) { d[i] = hadd(w[i], o[i]); b3[i] = hadd(d[i], o[i - 1]); }
#pragma unroll
      for (int pp = 0; pp < 4; pp++) {
        const uint32_t sel = (pp & 1) ? 0x7632 : 0x5410;
        const int k = pp >> 1;
        sts64(zb + zo[5 + pp], __byte_perm(w[k - 1], w[k + 1], sel), __byte_perm(w[k + 3], w[k + 5], sel));
        sts64(zb + zo[5 + pp] + (ZB1 - ZA1), __byte_perm(b3[k], b3[k + 2], sel), __byte_perm(b3[k + 4], b3[k + 6], sel));
      }
      if (qt < 3) {
        uint32_t e_[20], b5_[20];
        uint32_t *e = e_ + 8, *b5 = b5_ + 8;
#pragma unroll
        for (int i = -6; i <= -2; i++) o[i] = odd_pair(w[i], w[i + 1]);
#pragma unroll
        for (int i = -6; i <= -1; i++) d[i] = hadd(w[i], o[i]);
#pragma unroll
        for (int i = -5; i <= -1; i++) b3[i] = hadd(d[i], o[i - 1]);
#pragma unroll
        for (int i = -5; i <= 4; i++) e[i] = hadd(d[i - 1], d[i]);
#pragma unroll
        for (int i = -4; i <= 4; i++) b5[i] = hadd(e[i], w[i + 1]);
        const uint32_t a2 = zb + zo[9];
        sts128(a2 + ZA2, b3[-2], b3[-1], b3[0], b3[1]);
        sts128(zb + zo[12] + ZA2, b3[2], b3[3], b3[4], b3[5]);
        sts128(a2 + ZB2, b5[-4], b5[-3], b5[-2], b5[-1]);
        sts128(zb + zo[12] + ZB2, b5[0], b5[1], b5[2], b5[3]);
        if (qt < 2) {
          sts128(a2 + ZS, d[-2], d[-1], d[0], d[1]);
          sts128(a2 + ZS + 128, d[2], d[3], d[4], d[5]);
          uint32_t b7[8], b9[8];
#pragma unroll
          for (int i = -4; i <= 3; i++) { b7[i + 4] = hadd(b3[i - 1], e[i + 1]); b9[i + 4] = hadd(e[i - 1], b5[i + 1]); }
          const uint32_t a3 = zb + zo[10];
          sts128(a3 + ZA3, b7[0], b7[1], b7[2], b7[3]);
          sts128(a3 + ZA3 + 256, b7[4], b7[5], b7[6], b7[7]);
          sts128(a3 + ZB3 + 256, b9[0], b9[1], b9[2], b9[3]);
          if (jz < 63) sts128(zb + zo[11] + ZB3, b9[4], b9[5], b9[6], b9[7]);
          else sts128(zb + ZB3, 0, 0, 0, 0);
        }
      }
    }
    bar_sync(wg == 2 ? 14 : 7, 384);
#pragma unroll 1
    for (int ch = wg - 2; ch < 5; ch += 2) {
      const uint32_t ub = sb + OFF_U + ch * 32, zb = sb + OFF_Z + ch * ZSZ, pb = sb + OFF_P + ch * 3072;
      if (ch == 2) bar_sync(0, 256);
      const uint32_t pa = pb + cpa;
      if (role < 2) {
        float acc[8][4];
#pragma unroll
        for (int r = 0; r < 8; r++) { acc[r][0] = acc[r][1] = acc[r][2] = acc[r][3] = 0.f; }
        float fix = 0.f;
        if (role == 1 && lane == 28) {
          const uint32_t k = lds32(pb + PB1 * 4), u0 = lds32(ub);
          fix = __low2float(*reinterpret_cast<const __half2*>(&k)) * __low2float(*reinterpret_cast<const __half2*>(&u0));
        }
        uint32_t b[12][4], A[17][4];
#pragma unroll
        for (int i = 11; i >= 8; i--) ldsm4(b[i], ub + (co[4 + (i & 1)] ^ (((i >> 1) & 1) * 16)) + ((i >> 1) & 1) * 640);
        A[0][0] = lds32(pa + P0 * 4); A[0][1] = lds32(pa + P0 * 4 + 32); A[0][2] = lds32(sb + OFF_ZERO + 4);
#pragma unroll
        for (int m = 0; m <= 16; m++) {
          if (m < 16) {
            A[m + 1][0] = lds32(pa + P0 * 4 + (2 * m + 2) * 32);
            A[m + 1][1] = m < 15 ? lds32(pa + P0 * 4 + (2 * m + 3) * 32) : lds32(sb + OFF_ZERO + 8);
          }
          if ((m & 1) == 0 && m < 16) {
            const int i = 7 - (m >> 1);
            ldsm4(b[i], ub + (co[2 * (i >> 2) + (i & 1)] ^ (((i >> 1) & 1) * 16)) + ((i >> 1) & 1) * 640);
          }
          if (m == 9 && elect1()) mbar_arrive(bar + 8 * (B_PAIR + ch));
          A[m][3] = dup(A[m][0], nz);
          if (m < 16) A[m + 1][2] = dup(A[m][1], nz);
#pragma unroll
          for (int r = 7; r >= 0; r--) {
            const int f = 16 + r - m;
            hmma(acc[r], A[m][0], A[m][1], A[m][2], A[m][3], b[f >> 1][(f & 1) * 2], b[f >> 1][(f & 1) * 2 + 1]);
          }
        }
        acc[7][2] += fix;
        mbar_wait(bar + 8 * (B_PAIR + ch), 0);
#pragma unroll
        for (int i = 3; i >= 0; i--)
          stsm4t(ub + (co[4 + (i & 1)] ^ (((i >> 1) & 1) * 16)) + ((i >> 1) & 1) * 640, pack_bf(acc[2 * i][0], acc[2 * i][1]), pack_bf(acc[2 * i][2], acc[2 * i][3]),
                 pack_bf(acc[2 * i + 1][0], acc[2 * i + 1][1]), pack_bf(acc[2 * i + 1][2], acc[2 * i + 1][3]));
      } else if (role == 2) {
        float acc[14][4];
#pragma unroll
        for (int r = 0; r < 14; r++) { acc[r][0] = acc[r][1] = acc[r][2] = acc[r][3] = 0.f; }
#pragma unroll
        for (int arr = 0; arr < 2; arr++) {
          uint32_t A[5][4];
#pragma unroll
          for (int m = 4; m >= 0; m--) {
            const uint2 v = lds64(pb + co[5] + (arr ? PB1 : PA1) * 4 + m * 64), w = lds64(pb + co[5] + (arr ? PB1 : PA1) * 4 + m * 64 - 32);
            A[m][0] = v.x; A[m][1] = v.y; A[m][2] = w.x; A[m][3] = w.y;
          }
#pragma unroll
          for (int ip = 0; ip < 9; ip++) {
            uint32_t b[4];
            ldsm4(b, zb + co[ip & 1] + (arr ? ZB1 : ZA1) + ip * 256);
#pragma unroll
            for (int hh = 0; hh < 2; hh++)
#pragma unroll
              for (int m = 0; m < 5; m++) {
                const int i = 2 * ip + hh - 4 + m;
                if (i >= 0 && i < 14) hmma(acc[i], A[m][0], A[m][1], A[m][2], A[m][3], b[2 * hh], b[2 * hh + 1]);
              }
          }
        }
        const uint32_t a = zb + ZA1 + 512 + co[2];
#pragma unroll
        for (int i = 0; i < 7; i++)
          stsm4(a + i * 512, pack_bf(acc[2 * i][0], acc[2 * i][1]), pack_bf(acc[2 * i][2], acc[2 * i][3]),
                pack_bf(acc[2 * i + 1][0], acc[2 * i + 1][1]), pack_bf(acc[2 * i + 1][2], acc[2 * i + 1][3]));
      } else {
        float acc[12][4];
        const uint32_t za = zb + co[3];
        {
          float d[4][2][4];
#pragma unroll
          for (int r = 0; r < 8; r++) { d[r >> 1][r & 1][0] = d[r >> 1][r & 1][1] = d[r >> 1][r & 1][2] = d[r >> 1][r & 1][3] = 0.f; }
#pragma unroll
          for (int arr = 0; arr < 2; arr++) {
            uint32_t A[4][4];
#pragma unroll
            for (int m = 0; m < 4; m++) { A[m][0] = lds32(pa + (arr ? PB3 : PA3) * 4 + m * 64); A[m][1] = lds32(pa + (arr ? PB3 : PA3) * 4 + m * 64 + 32); }
#pragma unroll
            for (int m = 0; m < 4; m++) { A[m][2] = m ? dup(A[m - 1][1], nz) : lds32(sb + OFF_ZERO + 4 + arr * 4); A[m][3] = dup(A[m][0], nz); }
#pragma unroll
            for (int io = 0; io < 4; io++) {
              uint32_t b[4];
              ldsm4t(b, za + (arr ? ZB3 : ZA3) + io * 512);
#pragma unroll
              for (int m = 0; m + io < 4; m++) {
                hmma(d[io + m][0], A[m][0], A[m][1], A[m][2], A[m][3], b[0], b[1]);
                hmma(d[io + m][1], A[m][0], A[m][1], A[m][2], A[m][3], b[2], b[3]);
              }
            }
          }
#pragma unroll
          for (int r = 0; r < 4; r++) {
            acc[r][0] = acc[r][1] = acc[r][2] = acc[r][3] = 0.f;
            acc[4 + 2 * r][0] = d[r][0][0]; acc[4 + 2 * r][1] = d[r][0][1]; acc[4 + 2 * r][2] = d[r][1][0]; acc[4 + 2 * r][3] = d[r][1][1];
            acc[5 + 2 * r][0] = d[r][0][2]; acc[5 + 2 * r][1] = d[r][0][3]; acc[5 + 2 * r][2] = d[r][1][2]; acc[5 + 2 * r][3] = d[r][1][3];
          }
        }
        {
          const uint32_t k0 = lds32(sb + OFF_CHC + ch * 8 + 4) & co[4];
          const uint32_t k1 = lds32(sb + OFF_ZERO + 12), k2 = lds32(sb + OFF_ZERO + 16), k3 = dup(k0, nz);
#pragma unroll
          for (int ip = 0; ip < 4; ip++) {
            uint32_t b[4];
            ldsm4t(b, za + ZS + ip * 512);
            hmma(acc[4 + 2 * ip], k0, k1, k2, k3, b[0], b[1]);
            hmma(acc[5 + 2 * ip], k0, k1, k2, k3, b[2], b[3]);
          }
        }
        const uint32_t pa2 = pb + co[5];
#pragma unroll
        for (int arr = 0; arr < 2; arr++) {
          uint32_t A[5][4];
#pragma unroll
          for (int m = 0; m < 5; m++) {
            const uint2 v = lds64(pa2 + (arr ? PB2 : PA2) * 4 + m * 64), w = lds64(pa2 + (arr ? PB2 : PA2) * 4 + m * 64 - 32);
            A[m][0] = v.x; A[m][1] = v.y; A[m][2] = w.x; A[m][3] = w.y;
          }
#pragma unroll
          for (int ip = 0; ip < 6; ip++) {
            uint32_t b[4];
            ldsm4t(b, zb + co[0] + (arr ? ZB2 : ZA2) + ip * 512);
#pragma unroll
            for (int hh = 0; hh < 2; hh++)
#pragma unroll
              for (int m = 0; m < 5; m++) {
                const int i = 2 * ip + hh + m;
                if (i < 12) hmma(acc[i], A[m][0], A[m][1], A[m][2], A[m][3], b[2 * hh], b[2 * hh + 1]);
              }
          }
        }
        const uint32_t a = zb + ZA2 + co[2];
#pragma unroll
        for (int i = 0; i < 6; i++)
          stsm4(a + i * 512, pack_bf(acc[2 * i][0], acc[2 * i][1]), pack_bf(acc[2 * i][2], acc[2 * i][3]),
                pack_bf(acc[2 * i + 1][0], acc[2 * i + 1][1]), pack_bf(acc[2 * i + 1][2], acc[2 * i + 1][3]));
      }
      __syncwarp();
      if (elect1()) mbar_arrive(bar + 8 * (B_PART + ch));
    }
    const uint4* srcA = p.scr->h + (rg1 * 24 + NS2 - 2) * 1024;
    const uint4* srcB = p.scr->w2p + (j1 * 24 + NS2 - 2) * 640;
    combine(cmb, 6 - wg, wid, p.scr->sT, [&] {
      if (warp == 12) {
        bar_sync(8, 512);
        if (elect1()) {
          asm volatile("fence.proxy.async.global;" ::: "memory");
          load2(NS2 - 2, sb + (NS2 - 2) * SLOT2, srcA, srcB);
          load2(NS2 - 1, sb + (NS2 - 1) * SLOT2, srcA + 1024, srcB + 640);
        }
        __syncwarp();
      } else bar_arrive(8, 512);
    });
    if (warp == 12) {
      if (elect1()) {
        uint32_t d = sb;
#pragma unroll 1
        for (int s = NS2; s < 24; s++) {
          mbar_wait(bar + 8 * (B_REL2 + s - NS2 + 1), 0);
          load2(s, d, srcA + 2048, srcB + 1280);
          srcA += 1024; srcB += 640;
          d = d == sb + (NS2 - 1) * SLOT2 ? sb : d + SLOT2;
        }
      }
      __syncwarp();
    } else if (warp == 13) {
      if (elect1()) {
#pragma unroll 1
        for (int c = 2; c < 5; c++) mbar_wait(bar + 8 * (B_FREE + c), 0);
        publish(cnt + (C_S + (wid >> 4)) * 32);
        mbar_expect(bar + 8 * B_SFULL, 20480);
        poll_cnt(cnt + (C_S + j1) * 32, ep * 16);
        mbar_wait(bar + 8 * (B_REL2 + 24 - NS2), 0);
        bulk_g2s(sb + OFF_U, p.scr->sT + (j1 * 16 + rg1) * 1280, 20480, bar + 8 * B_SFULL);
      }
      __syncwarp();
    }
  }
}

typedef CUresult (*EncodeFn)(CUtensorMap*, CUtensorMapDataType, cuuint32_t, void*, const cuuint64_t*, const cuuint64_t*,
                             const cuuint32_t*, const cuuint32_t*, CUtensorMapInterleave, CUtensorMapSwizzle,
                             CUtensorMapL2promotion, CUtensorMapFloatOOBfill);

}

extern "C" void kernel_launch(void* const* d_in, const int* in_sizes, int n_in, void* d_out, int out_size) {
  static EncodeFn enc = nullptr;
  static int nsm = 0;
  static void* scr = nullptr;
  if (!enc) {
    void* fn = nullptr;
    cudaDriverEntryPointQueryResult qr;
    cudaGetDriverEntryPoint("cuTensorMapEncodeTiled", &fn, cudaEnableDefault, &qr);
    enc = (EncodeFn)fn;
    int dev = 0;
    cudaGetDevice(&dev);
    cudaDeviceGetAttribute(&nsm, cudaDevAttrMultiProcessorCount, dev);
    cudaFuncSetAttribute(fused_s4_ffn_kernel<true>, cudaFuncAttributeMaxDynamicSharedMemorySize, SMEM_BYTES);
    cudaFuncSetAttribute(fused_s4_ffn_kernel<false>, cudaFuncAttributeMaxDynamicSharedMemorySize, SMEM_BYTES);
    cudaGetSymbolAddress(&scr, g_scr);
  }
  Params p;
  p.x = (const __nv_bfloat16*)d_in[0];
  p.are = (const __nv_bfloat16*)d_in[1]; p.aim = (const __nv_bfloat16*)d_in[2];
  p.bre = (const __nv_bfloat16*)d_in[3]; p.bim = (const __nv_bfloat16*)d_in[4];
  p.cre = (const __nv_bfloat16*)d_in[5]; p.cim = (const __nv_bfloat16*)d_in[6];
  p.logdt = (const __nv_bfloat16*)d_in[7]; p.dskip = (const __nv_bfloat16*)d_in[8];
  p.w1 = (const __nv_bfloat16*)d_in[10]; p.w2 = (const __nv_bfloat16*)d_in[11];
  p.out = (__nv_bfloat16*)d_out;
  p.scr = (Scratch*)scr;
  CUtensorMap tmX, tmW1, tmU, tmW2;
  const cuuint32_t es[5] = {1, 1, 1, 1, 1};
  {
    const cuuint64_t gd[5] = {DM, 2, 4, 4, FF / 32}, gs[4] = {DM * 2, DM * 16, DM * 4, DM * 64};
    const cuuint32_t bx[5] = {88, 2, 4, 4, 3};
    enc(&tmW2, CU_TENSOR_MAP_DATA_TYPE_BFLOAT16, 5, d_in[11], gd, gs, bx, es, CU_TENSOR_MAP_INTERLEAVE_NONE,
        CU_TENSOR_MAP_SWIZZLE_NONE, CU_TENSOR_MAP_L2_PROMOTION_NONE, CU_TENSOR_MAP_FLOAT_OOB_FILL_NONE);
  }
  {
    const cuuint64_t gd[2] = {16 * DM, 128}, gs[1] = {DM * 32};
    const cuuint32_t bx[2] = {80, 144};
    enc(&tmU, CU_TENSOR_MAP_DATA_TYPE_FLOAT16, 2, p.scr->uT, gd, gs, bx, es, CU_TENSOR_MAP_INTERLEAVE_NONE,
        CU_TENSOR_MAP_SWIZZLE_NONE, CU_TENSOR_MAP_L2_PROMOTION_NONE, CU_TENSOR_MAP_FLOAT_OOB_FILL_NONE);
  }
  {
    const cuuint64_t gd[2] = {DM, SEQ}, gs[1] = {DM * 2};
    const cuuint32_t bx[2] = {64, 128};
    enc(&tmX, CU_TENSOR_MAP_DATA_TYPE_BFLOAT16, 2, d_in[0], gd, gs, bx, es, CU_TENSOR_MAP_INTERLEAVE_NONE,
        CU_TENSOR_MAP_SWIZZLE_128B, CU_TENSOR_MAP_L2_PROMOTION_L2_128B, CU_TENSOR_MAP_FLOAT_OOB_FILL_NONE);
  }
  {
    const cuuint64_t gd[3] = {64, DM, FF / 64}, gs[2] = {FF * 2, 128};
    const cuuint32_t bx[3] = {64, 64, 3};
    enc(&tmW1, CU_TENSOR_MAP_DATA_TYPE_BFLOAT16, 3, d_in[10], gd, gs, bx, es, CU_TENSOR_MAP_INTERLEAVE_NONE,
        CU_TENSOR_MAP_SWIZZLE_128B, CU_TENSOR_MAP_L2_PROMOTION_L2_128B, CU_TENSOR_MAP_FLOAT_OOB_FILL_NONE);
  }
  if (nsm == 132) fused_s4_ffn_kernel<true><<<132, 512, SMEM_BYTES>>>(p, tmX, tmW1, tmU, tmW2);
  else fused_s4_ffn_kernel<false><<<132, 512, SMEM_BYTES>>>(p, tmX, tmW1, tmU, tmW2);
}
```
